```python
import torch

def _softmax(x, axis=-1):
    return torch.softmax(x, dim=axis)

def _gelu(x):
    return torch.nn.functional.gelu(x, approximate='tanh')

def _silu(x):
    return torch.nn.functional.silu(x)

def _sigmoid(x):
    return torch.sigmoid(x)

def _layernorm(x, axis=-1, eps=1e-05):
    m = x.mean(dim=axis, keepdim=True)
    v = x.var(dim=axis, keepdim=True, unbiased=False)
    return (x - m) / torch.sqrt(v + eps)

def _scatter_add(tgt, idx, src, axis=0):
    return tgt.clone().index_add_(axis, idx, src)

def _segment_sum(src, seg, n):
    out = torch.zeros((n,) + src.shape[1:], dtype=src.dtype)
    return out.index_add_(0, seg, src)

def _pad(x, pw):
    flat = tuple((v for pair in reversed(pw) for v in pair))
    return torch.nn.functional.pad(x, flat)
kernel_name = 'adaLN_cond__spectral_gfnet__glu_gated_geglu__prompt'

def setup_inputs():

    _w = lambda a: (lambda t: t.to(torch.bfloat16) if t.is_floating_point() else t)(torch.as_tensor(a))

    def _A_setup():
        B, S, D = (1, 2048, 640)
        Df = D // 2 + 1
        return {'x': _w((lambda *s: torch.randn(*s, dtype=torch.bfloat16) * 0.05)(B, S, D)), 'w_r': _w((lambda *s: torch.randn(*s, dtype=torch.bfloat16) * 3.2)(S, Df) * 0.02), 'w_i': _w((lambda *s: torch.randn(*s, dtype=torch.bfloat16) * 3.2)(S, Df) * 0.02)}
    _A_in = _A_setup()

    def _B_setup():
        B, S, Dm, Df = (1, 2048, 640, 1536)
        return {'x': _w((lambda *s: torch.randn(*s, dtype=torch.bfloat16) * 0.05)(B, S, Dm)), 'w_gate': _w((lambda *s: torch.randn(*s, dtype=torch.bfloat16) * 0.4)(Dm, Df) * Dm ** (-0.5)), 'w_up': _w((lambda *s: torch.randn(*s, dtype=torch.bfloat16) * 0.4)(Dm, Df) * Dm ** (-0.5)), 'w_down': _w((lambda *s: torch.randn(*s, dtype=torch.bfloat16) * 0.4)(Df, Dm) * Df ** (-0.5))}
    _B_in = _B_setup()
    return {'A_x': _A_in['x'], 'A_w_r': _A_in['w_r'], 'A_w_i': _A_in['w_i'], 'B_x': _B_in['x'], 'B_w_gate': _B_in['w_gate'], 'B_w_up': _B_in['w_up'], 'B_w_down': _B_in['w_down'], 'c': _w((lambda *s: torch.randn(*s, dtype=torch.bfloat16) * 0.1)(1, 640) * 8.0), 'w_mod': _w((lambda *s: torch.randn(*s, dtype=torch.bfloat16) * 0.1)(640, 6 * 640) * 640 ** (-0.5) * 8.0)}

def reference(A_x, A_w_r, A_w_i, B_x, B_w_gate, B_w_up, B_w_down, c, w_mod):

    def _A_ref(x, w_r, w_i):
        B, S, D = x.shape
        X = (lambda x, axes=(-2, -1): torch.fft.rfft2(x.float(), dim=axes))(x, axes=(-2, -1))
        W = w_r + 1j * w_i
        X = X * W
        y = (lambda x, s, axes=(-2, -1): torch.fft.irfft2(x, s=s, dim=axes).to(torch.bfloat16))(X, (S, D), axes=(-2, -1))
        return y

    def _B_ref(x, w_gate, w_up, w_down):
        g = torch.einsum('bsd,df->bsf', x, w_gate)
        u = torch.einsum('bsd,df->bsf', x, w_up)
        h = _gelu(g) * u
        return torch.einsum('bsf,fd->bsd', h, w_down)
    x = A_x
    mod = (_silu(c) @ w_mod).reshape(c.shape[0], 6, 1, -1)
    sa, ca, ga, sb, cb, gb = (mod[:, 0].clone(), mod[:, 1].clone(), mod[:, 2].clone(), mod[:, 3].clone(), mod[:, 4].clone(), mod[:, 5].clone())
    h = _layernorm(x, axis=-1) * (1 + ca) + sa
    x = x + ga * _A_ref(h, A_w_r, A_w_i)
    h = _layernorm(x, axis=-1) * (1 + cb) + sb
    x = x + gb * _B_ref(h, B_w_gate, B_w_up, B_w_down)
    return x
```

```cpp
#include <cuda_runtime.h>
#include <cuda_bf16.h>
#include <cuda.h>
#include <stdint.h>

namespace {

constexpr int NMAIN = 128, NCTA = 130, NTHR = 384;
constexpr int TROW = 1296;
constexpr int STAGE = 20480, NSLOT = 8, NSTAGES = 36, NPRE = 6;
constexpr int OFF_WF = 3 * STAGE, WSZ = 22528;
constexpr int OFF_MB = 6 * STAGE;
constexpr int OFF_CC = OFF_WF + 2 * WSZ;
constexpr int OFF_SILU = OFF_CC + 6144;
constexpr int OFF_MODA = OFF_SILU + 1280;
constexpr int OFF_RED = OFF_MODA + 2560;
constexpr int OFF_ZERO = OFF_RED + 1024;
constexpr int OFF_M40 = 8 * STAGE;
constexpr int OFF_LANE = OFF_M40 + 12800;
constexpr int OFF_XS = 9 * STAGE;
constexpr int OFF_EX = OFF_XS + 20480;
constexpr int EX_TOK = 1424, EX_SLOT = 176;
constexpr int OFF_BAR = OFF_EX + 22784;
constexpr int OFF_MODB = OFF_BAR + 336;
constexpr int OFF_HST = OFF_M40 + 7 * 8192;
constexpr int OFF_GB = OFF_MODB + 3840;
constexpr int OFF_ROLE = OFF_GB + 320;
constexpr int OFF_EV = OFF_ROLE + 8;
constexpr int OFF_PROF = OFF_ROLE + 16;
constexpr int SMEM_BYTES = OFF_PROF + 352;
constexpr int BAR_MA = 0, BAR_TAB = 8, BAR_WF = 9, BAR_PART = 10, BAR_WD = 11, BAR_FULL = 12, BAR_EMPTY = 20, BAR_HF = 28, BAR_HE = 35;
#define HANDOFF 7
#define MOD_POLL 3500
#define ROLEMAP 0
#define A_DELAY 400
#define PF2_STEP 700
#define RS1B 2
#define RS2 2
#define RS2B 4
#define D_DELAY 1850
#define NG 12
#define G2_HAND 9
#define MOD_POLL2 800
#define PF2_START 3500
#define H_MIN 3500
#define H_POLL 1200
#define ST_PACE 120
#define W9_N 4
#define W9_STEP 500
#define TICK 250
#define E3_DELAY 0
#define PF_START 2800
#define PF_STEP 400
#define XDELAY 1500
constexpr int SPIN = 1 << 17;

__device__ __align__(128) const uint32_t g_tab[30848] = {
0x3f803f80,0x3f803f80,0x3f803f80,0x3f803f80,0,0,0,0,0x3f7d3f80,0x3f643f73,0x3f353f4f,0x3ee83f16,0xbe200000,0xbee8be9e,0xbf35bf16,0xbf64bf4f,
0x3f733f80,0x3f163f4f,0x3e9e,0xbf16be9e,0xbe9e0000,0xbf4fbf16,0xbf80bf73,0xbf4fbf73,0x3f643f80,0x3e203f16,0xbf35be9e,0xbf7dbf73,0xbee80000,0xbf7dbf4f,0xbf35bf73,0x3e20be9e,
0,0,0,0,0x3f803f80,0x3f803f80,0x3f803f80,0x3f803f80,0x3e200000,0x3ee83e9e,0x3f353f16,0x3f643f4f,0x3f7d3f80,0x3f643f73,0x3f353f4f,0x3ee83f16,
0x3e9e0000,0x3f4f3f16,0x3f803f73,0x3f4f3f73,0x3f733f80,0x3f163f4f,0x3e9e,0xbf16be9e,0x3ee80000,0x3f7d3f4f,0x3f353f73,0xbe203e9e,0x3f643f80,0x3e203f16,0xbf35be9e,0xbf7dbf73,
0x3f803f80,0x3f803f80,0x3f803f80,0x3f803f80,0,0,0,0,0x3e203e9e,0xbe200000,0xbee8be9e,0xbf35bf16,0xbf7dbf73,0xbf7dbf80,0xbf64bf73,0xbf35bf4f,
0xbf73bf4f,0xbf73bf80,0xbf16bf4f,0xbe9e,0xbe9ebf16,0x3e9e0000,0x3f4f3f16,0x3f803f73,0xbee8bf4f,0x3ee80000,0x3f7d3f4f,0x3f353f73,0x3f643f16,0x3f643f80,0x3e203f16,0xbf35be9e,
0,0,0,0,0x3f803f80,0x3f803f80,0x3f803f80,0x3f803f80,0x3f7d3f73,0x3f7d3f80,0x3f643f73,0x3f353f4f,0x3e203e9e,0xbe200000,0xbee8be9e,0xbf35bf16,
0x3e9e3f16,0xbe9e0000,0xbf4fbf16,0xbf80bf73,0xbf73bf4f,0xbf73bf80,0xbf16bf4f,0xbe9e,0xbf64bf16,0xbf64bf80,0xbe20bf16,0x3f353e9e,0xbee8bf4f,0x3ee80000,0x3f7d3f4f,0x3f353f73,
0x3f803f80,0x3f803f80,0x3f803f80,0x3f803f80,0,0,0,0,0xbf64bf4f,0xbf7dbf73,0xbf7dbf80,0xbf64bf73,0xbee8bf16,0xbe20be9e,0x3e200000,0x3ee83e9e,
0x3f163e9e,0x3f733f4f,0x3f733f80,0x3f163f4f,0x3f4f3f73,0x3e9e3f16,0xbe9e0000,0xbf4fbf16,0xbe203e9e,0xbf64bf16,0xbf64bf80,0xbe20bf16,0xbf7dbf73,0xbee8bf4f,0x3ee80000,0x3f7d3f4f,
0,0,0,0,0x3f803f80,0x3f803f80,0x3f803f80,0x3f803f80,0x3ee83f16,0x3e203e9e,0xbe200000,0xbee8be9e,0xbf64bf4f,0xbf7dbf73,0xbf7dbf80,0xbf64bf73,
0xbf4fbf73,0xbe9ebf16,0x3e9e0000,0x3f4f3f16,0x3f163e9e,0x3f733f4f,0x3f733f80,0x3f163f4f,0x3f7d3f73,0x3ee83f4f,0xbee80000,0xbf7dbf4f,0xbe203e9e,0xbf64bf16,0xbf64bf80,0xbe20bf16,
0x3f803f80,0x3f803f80,0x3f803f80,0x3f803f80,0,0,0,0,0xbf35bf4f,0xbee8bf16,0xbe20be9e,0x3e200000,0x3f353f16,0x3f643f4f,0x3f7d3f73,0x3f7d3f80,
0x3e9e,0xbf16be9e,0xbf73bf4f,0xbf73bf80,0xbf80bf73,0xbf4fbf73,0xbe9ebf16,0x3e9e0000,0x3f353e9e,0x3f7d3f73,0x3ee83f4f,0xbee80000,0x3f353f73,0xbe203e9e,0xbf64bf16,0xbf64bf80,
0,0,0,0,0x3f803f80,0x3f803f80,0x3f803f80,0x3f803f80,0xbf35bf16,0xbf64bf4f,0xbf7dbf73,0xbf7dbf80,0xbf35bf4f,0xbee8bf16,0xbe20be9e,0x3e200000,
0x3f803f73,0x3f4f3f73,0x3e9e3f16,0xbe9e0000,0x3e9e,0xbf16be9e,0xbf73bf4f,0xbf73bf80,0xbf35bf73,0x3e20be9e,0x3f643f16,0x3f643f80,0x3f353e9e,0x3f7d3f73,0x3ee83f4f,0xbee80000,
0x3f803f80,0x3f803f80,0x3f803f80,0x3f803f80,0,0,0,0,0x3ee83e9e,0x3f353f16,0x3f643f4f,0x3f7d3f73,0x3f643f73,0x3f353f4f,0x3ee83f16,0x3e203e9e,
0xbf16bf4f,0xbe9e,0x3f163e9e,0x3f733f4f,0x3f4f3f16,0x3f803f73,0x3f4f3f73,0x3e9e3f16,0xbf7dbf4f,0xbf35bf73,0x3e20be9e,0x3f643f16,0xbe20bf16,0x3f353e9e,0x3f7d3f73,0x3ee83f4f,
0,0,0,0,0x3f803f80,0x3f803f80,0x3f803f80,0x3f803f80,0xbf64bf73,0xbf35bf4f,0xbee8bf16,0xbe20be9e,0x3ee83e9e,0x3f353f16,0x3f643f4f,0x3f7d3f73,
0xbf4fbf16,0xbf80bf73,0xbf4fbf73,0xbe9ebf16,0xbf16bf4f,0xbe9e,0x3f163e9e,0x3f733f4f,0x3e203f16,0xbf35be9e,0xbf7dbf73,0xbee8bf4f,0xbf7dbf4f,0xbf35bf73,0x3e20be9e,0x3f643f16,
0x3f4f3f80,0xbe9e3e9e,0xbf80bf4f,0xbe9ebf4f,0xbf160000,0xbf73bf73,0xbf16,0x3f733f16,0x3f353f80,0xbf350000,0xbf35bf80,0x3f350000,0xbf350000,0xbf35bf80,0x3f350000,0x3f353f80,
0x3f163f80,0xbf73be9e,0xbf4f,0x3f733f4f,0xbf4f0000,0xbe9ebf73,0x3f803f16,0xbe9e3f16,0x3ee83f80,0xbf7dbf16,0x3f35be9e,0x3e203f73,0xbf640000,0x3e20bf4f,0x3f353f73,0xbf7dbe9e,
0x3f160000,0x3f733f73,0x3f16,0xbf73bf16,0x3f4f3f80,0xbe9e3e9e,0xbf80bf4f,0xbe9ebf4f,0x3f350000,0x3f353f80,0xbf350000,0xbf35bf80,0x3f353f80,0xbf350000,0xbf35bf80,0x3f350000,
0x3f4f0000,0x3e9e3f73,0xbf80bf16,0x3e9ebf16,0x3f163f80,0xbf73be9e,0xbf4f,0x3f733f4f,0x3f640000,0xbe203f4f,0xbf35bf73,0x3f7d3e9e,0x3ee83f80,0xbf7dbf16,0x3f35be9e,0x3e203f73,
0x3f4f3e9e,0x3f4f3f80,0xbe9e3e9e,0xbf80bf4f,0x3f163f73,0xbf160000,0xbf73bf73,0xbf16,0x3f353f80,0xbf350000,0xbf35bf80,0x3f350000,0xbf350000,0xbf35bf80,0x3f350000,0x3f353f80,
0xbf163e9e,0xbf16bf80,0x3f733e9e,0x3f4f,0xbf4fbf73,0x3f4f0000,0x3e9e3f73,0xbf80bf16,0xbf64bf4f,0x3f640000,0xbe203f4f,0xbf35bf73,0x3ee8bf16,0x3ee83f80,0xbf7dbf16,0x3f35be9e,
0xbf16bf73,0x3f160000,0x3f733f73,0x3f16,0x3f4f3e9e,0x3f4f3f80,0xbe9e3e9e,0xbf80bf4f,0x3f350000,0x3f353f80,0xbf350000,0xbf35bf80,0x3f353f80,0xbf350000,0xbf35bf80,0x3f350000,
0x3f4f3f73,0xbf4f0000,0xbe9ebf73,0x3f803f16,0xbf163e9e,0xbf16bf80,0x3f733e9e,0x3f4f,0xbee83f16,0xbee8bf80,0x3f7d3f16,0xbf353e9e,0xbf64bf4f,0x3f640000,0xbe203f4f,0xbf35bf73,
0xbe9ebf4f,0x3f4f3e9e,0x3f4f3f80,0xbe9e3e9e,0x3f733f16,0x3f163f73,0xbf160000,0xbf73bf73,0x3f353f80,0xbf350000,0xbf35bf80,0x3f350000,0xbf350000,0xbf35bf80,0x3f350000,0x3f353f80,
0xbf73bf4f,0x3f16be9e,0x3f163f80,0xbf73be9e,0x3e9ebf16,0x3f4f3f73,0xbf4f0000,0xbe9ebf73,0x3f7d3e9e,0xbee83f16,0xbee8bf80,0x3f7d3f16,0x3e203f73,0xbf64bf4f,0x3f640000,0xbe203f4f,
0xbf73bf16,0xbf16bf73,0x3f160000,0x3f733f73,0xbe9ebf4f,0x3f4f3e9e,0x3f4f3f80,0xbe9e3e9e,0x3f350000,0x3f353f80,0xbf350000,0xbf35bf80,0x3f353f80,0xbf350000,0xbf35bf80,0x3f350000,
0xbe9e3f16,0xbf4fbf73,0x3f4f0000,0x3e9e3f73,0xbf73bf4f,0x3f16be9e,0x3f163f80,0xbf73be9e,0xbe20bf73,0x3f643f4f,0xbf640000,0x3e20bf4f,0x3f7d3e9e,0xbee83f16,0xbee8bf80,0x3f7d3f16,
0xbf80bf4f,0xbe9ebf4f,0x3f4f3e9e,0x3f4f3f80,0xbf16,0x3f733f16,0x3f163f73,0xbf160000,0x3f353f80,0xbf350000,0xbf35bf80,0x3f350000,0xbf350000,0xbf35bf80,0x3f350000,0x3f353f80,
0xbf4f,0x3f733f4f,0xbf163e9e,0xbf16bf80,0x3f803f16,0xbe9e3f16,0xbf4fbf73,0x3f4f0000,0xbf353e9e,0xbe20bf73,0x3f643f4f,0xbf640000,0xbf35bf73,0x3f7d3e9e,0xbee83f16,0xbee8bf80,
0x3f16,0xbf73bf16,0xbf16bf73,0x3f160000,0xbf80bf4f,0xbe9ebf4f,0x3f4f3e9e,0x3f4f3f80,0x3f350000,0x3f353f80,0xbf350000,0xbf35bf80,0x3f353f80,0xbf350000,0xbf35bf80,0x3f350000,
0xbf80bf16,0x3e9ebf16,0x3f4f3f73,0xbf4f0000,0xbf4f,0x3f733f4f,0xbf163e9e,0xbf16bf80,0x3f353f73,0xbf7dbe9e,0x3ee8bf16,0x3ee83f80,0xbf353e9e,0xbe20bf73,0x3f643f4f,0xbf640000,
0xbe9e3e9e,0xbf80bf4f,0xbe9ebf4f,0x3f4f3e9e,0xbf73bf73,0xbf16,0x3f733f16,0x3f163f73,0x3f353f80,0xbf350000,0xbf35bf80,0x3f350000,0xbf350000,0xbf35bf80,0x3f350000,0x3f353f80,
0x3f733e9e,0x3f4f,0xbf73bf4f,0x3f16be9e,0x3e9e3f73,0xbf80bf16,0x3e9ebf16,0x3f4f3f73,0x3e20bf4f,0x3f353f73,0xbf7dbe9e,0x3ee8bf16,0x3f7d3f16,0xbf353e9e,0xbe20bf73,0x3f643f4f,
0x3f733f73,0x3f16,0xbf73bf16,0xbf16bf73,0xbe9e3e9e,0xbf80bf4f,0xbe9ebf4f,0x3f4f3e9e,0x3f350000,0x3f353f80,0xbf350000,0xbf35bf80,0x3f353f80,0xbf350000,0xbf35bf80,0x3f350000,
0xbe9ebf73,0x3f803f16,0xbe9e3f16,0xbf4fbf73,0x3f733e9e,0x3f4f,0xbf73bf4f,0x3f16be9e,0xbf7dbf16,0x3f35be9e,0x3e203f73,0xbf64bf4f,0x3e20bf4f,0x3f353f73,0xbf7dbe9e,0x3ee8bf16,
0x3e9e3f80,0xbf4fbf4f,0x3f803e9e,0xbf4f3e9e,0xbf730000,0x3f16bf16,0x3f73,0xbf16bf73,0x3e203f80,0xbee8bf73,0x3f353f4f,0xbf64bf16,0xbf7d0000,0x3f64be9e,0xbf353f16,0x3ee8bf4f,
0x3f80,0xbf80,0x3f80,0xbf80,0xbf800000,0x3f800000,0xbf800000,0x3f800000,0xbe203f80,0x3ee8bf73,0xbf353f4f,0x3f64bf16,0xbf7d0000,0x3f643e9e,0xbf35bf16,0x3ee83f4f,
0x3f730000,0xbf163f16,0xbf73,0x3f163f73,0x3e9e3f80,0xbf4fbf4f,0x3f803e9e,0xbf4f3e9e,0x3f7d0000,0xbf643e9e,0x3f35bf16,0xbee83f4f,0x3e203f80,0xbee8bf73,0x3f353f4f,0xbf64bf16,
0x3f800000,0xbf800000,0x3f800000,0xbf800000,0x3f80,0xbf80,0x3f80,0xbf80,0x3f7d0000,0xbf64be9e,0x3f353f16,0xbee8bf4f,0xbe203f80,0x3ee8bf73,0xbf353f4f,0x3f64bf16,
0x3e9ebf4f,0x3e9e3f80,0xbf4fbf4f,0x3f803e9e,0x3f733f16,0xbf730000,0x3f16bf16,0x3f73,0x3f7d3e9e,0xbf7d0000,0x3f64be9e,0xbf353f16,0xbe203f73,0xbe20bf80,0x3ee83f73,0xbf35bf4f,
0x3f80,0xbf80,0x3f80,0xbf80,0xbf800000,0x3f800000,0xbf800000,0x3f800000,0xbf7d3e9e,0x3f7d0000,0xbf64be9e,0x3f353f16,0xbe20bf73,0xbe203f80,0x3ee8bf73,0xbf353f4f,
0xbf73bf16,0x3f730000,0xbf163f16,0xbf73,0x3e9ebf4f,0x3e9e3f80,0xbf4fbf4f,0x3f803e9e,0x3e20bf73,0x3e203f80,0xbee8bf73,0x3f353f4f,0x3f7d3e9e,0xbf7d0000,0x3f64be9e,0xbf353f16,
0x3f800000,0xbf800000,0x3f800000,0xbf800000,0x3f80,0xbf80,0x3f80,0xbf80,0x3e203f73,0x3e20bf80,0xbee83f73,0x3f35bf4f,0xbf7d3e9e,0x3f7d0000,0xbf64be9e,0x3f353f16,
0xbf4f3e9e,0x3e9ebf4f,0x3e9e3f80,0xbf4fbf4f,0xbf16bf73,0x3f733f16,0xbf730000,0x3f16bf16,0x3ee8bf4f,0xbe203f73,0xbe20bf80,0x3ee83f73,0x3f643f16,0xbf7dbe9e,0x3f7d0000,0xbf643e9e,
0x3f80,0xbf80,0x3f80,0xbf80,0xbf800000,0x3f800000,0xbf800000,0x3f800000,0xbee8bf4f,0x3e203f73,0x3e20bf80,0xbee83f73,0x3f64bf16,0xbf7d3e9e,0x3f7d0000,0xbf64be9e,
0x3f163f73,0xbf73bf16,0x3f730000,0xbf163f16,0xbf4f3e9e,0x3e9ebf4f,0x3e9e3f80,0xbf4fbf4f,0xbf64bf16,0x3f7d3e9e,0xbf7d0000,0x3f64be9e,0x3ee8bf4f,0xbe203f73,0xbe20bf80,0x3ee83f73,
0x3f800000,0xbf800000,0x3f800000,0xbf800000,0x3f80,0xbf80,0x3f80,0xbf80,0xbf643f16,0x3f7dbe9e,0xbf7d0000,0x3f643e9e,0xbee8bf4f,0x3e203f73,0x3e20bf80,0xbee83f73,
0x3f803e9e,0xbf4f3e9e,0x3e9ebf4f,0x3e9e3f80,0x3f73,0xbf16bf73,0x3f733f16,0xbf730000,0xbf35bf4f,0x3f643f16,0xbf7dbe9e,0x3f7d0000,0x3f35bf16,0xbee83f4f,0x3e20bf73,0x3e203f80,
0x3f80,0xbf80,0x3f80,0xbf80,0xbf800000,0x3f800000,0xbf800000,0x3f800000,0x3f35bf4f,0xbf643f16,0x3f7dbe9e,0xbf7d0000,0x3f353f16,0xbee8bf4f,0x3e203f73,0x3e20bf80,
0xbf73,0x3f163f73,0xbf73bf16,0x3f730000,0x3f803e9e,0xbf4f3e9e,0x3e9ebf4f,0x3e9e3f80,0xbf353f16,0x3ee8bf4f,0xbe203f73,0xbe20bf80,0xbf35bf4f,0x3f643f16,0xbf7dbe9e,0x3f7d0000,
0x3f800000,0xbf800000,0x3f800000,0xbf800000,0x3f80,0xbf80,0x3f80,0xbf80,0xbf35bf16,0x3ee83f4f,0xbe20bf73,0xbe203f80,0x3f35bf4f,0xbf643f16,0x3f7dbe9e,0xbf7d0000,
0xbf4fbf4f,0x3f803e9e,0xbf4f3e9e,0x3e9ebf4f,0x3f16bf16,0x3f73,0xbf16bf73,0x3f733f16,0xbf643e9e,0x3f35bf16,0xbee83f4f,0x3e20bf73,0xbee8bf73,0x3f353f4f,0xbf64bf16,0x3f7d3e9e,
0x3f80,0xbf80,0x3f80,0xbf80,0xbf800000,0x3f800000,0xbf800000,0x3f800000,0x3f643e9e,0xbf35bf16,0x3ee83f4f,0xbe20bf73,0xbee83f73,0x3f35bf4f,0xbf643f16,0x3f7dbe9e,
0xbf163f16,0xbf73,0x3f163f73,0xbf73bf16,0xbf4fbf4f,0x3f803e9e,0xbf4f3e9e,0x3e9ebf4f,0x3ee83f73,0xbf35bf4f,0x3f643f16,0xbf7dbe9e,0xbf643e9e,0x3f35bf16,0xbee83f4f,0x3e20bf73,
0x3f800000,0xbf800000,0x3f800000,0xbf800000,0x3f80,0xbf80,0x3f80,0xbf80,0x3ee8bf73,0xbf353f4f,0x3f64bf16,0xbf7d3e9e,0x3f643e9e,0xbf35bf16,0x3ee83f4f,0xbe20bf73,
0xbe9e3f80,0x3f4fbf4f,0xbf803e9e,0x3f4f3e9e,0xbf730000,0x3f163f16,0xbf73,0xbf163f73,0xbee83f80,0x3f7dbf16,0xbf35be9e,0xbe203f73,0xbf640000,0x3e203f4f,0x3f35bf73,0xbf7d3e9e,
0xbf163f80,0x3f73be9e,0xbf4f,0xbf733f4f,0xbf4f0000,0xbe9e3f73,0x3f80bf16,0xbe9ebf16,0xbf353f80,0x3f350000,0x3f35bf80,0xbf350000,0xbf350000,0xbf353f80,0x3f350000,0x3f35bf80,
0x3f730000,0xbf16bf16,0x3f73,0x3f16bf73,0xbe9e3f80,0x3f4fbf4f,0xbf803e9e,0x3f4f3e9e,0x3f640000,0xbe20bf4f,0xbf353f73,0x3f7dbe9e,0xbee83f80,0x3f7dbf16,0xbf35be9e,0xbe203f73,
0x3f4f0000,0x3e9ebf73,0xbf803f16,0x3e9e3f16,0xbf163f80,0x3f73be9e,0xbf4f,0xbf733f4f,0x3f350000,0x3f35bf80,0xbf350000,0xbf353f80,0xbf353f80,0x3f350000,0x3f35bf80,0xbf350000,
0xbe9ebf4f,0xbe9e3f80,0x3f4fbf4f,0xbf803e9e,0x3f73bf16,0xbf730000,0x3f163f16,0xbf73,0x3f64bf4f,0xbf640000,0x3e203f4f,0x3f35bf73,0x3ee83f16,0x3ee8bf80,0xbf7d3f16,0x3f353e9e,
0x3f163e9e,0x3f16bf80,0xbf733e9e,0x3f4f,0xbf4f3f73,0x3f4f0000,0x3e9ebf73,0xbf803f16,0xbf353f80,0x3f350000,0x3f35bf80,0xbf350000,0xbf350000,0xbf353f80,0x3f350000,0x3f35bf80,
0xbf733f16,0x3f730000,0xbf16bf16,0x3f73,0xbe9ebf4f,0xbe9e3f80,0x3f4fbf4f,0xbf803e9e,0xbee8bf16,0xbee83f80,0x3f7dbf16,0xbf35be9e,0x3f64bf4f,0xbf640000,0x3e203f4f,0x3f35bf73,
0x3f4fbf73,0xbf4f0000,0xbe9e3f73,0x3f80bf16,0x3f163e9e,0x3f16bf80,0xbf733e9e,0x3f4f,0x3f350000,0x3f35bf80,0xbf350000,0xbf353f80,0xbf353f80,0x3f350000,0x3f35bf80,0xbf350000,
0x3f4f3e9e,0xbe9ebf4f,0xbe9e3f80,0x3f4fbf4f,0xbf163f73,0x3f73bf16,0xbf730000,0x3f163f16,0xbf7d3e9e,0x3ee83f16,0x3ee8bf80,0xbf7d3f16,0x3e20bf73,0xbf643f4f,0x3f640000,0xbe20bf4f,
0x3f73bf4f,0xbf16be9e,0xbf163f80,0x3f73be9e,0x3e9e3f16,0x3f4fbf73,0xbf4f0000,0xbe9e3f73,0xbf353f80,0x3f350000,0x3f35bf80,0xbf350000,0xbf350000,0xbf353f80,0x3f350000,0x3f35bf80,
0x3f16bf73,0xbf733f16,0x3f730000,0xbf16bf16,0x3f4f3e9e,0xbe9ebf4f,0xbe9e3f80,0x3f4fbf4f,0xbe203f73,0x3f64bf4f,0xbf640000,0x3e203f4f,0xbf7d3e9e,0x3ee83f16,0x3ee8bf80,0xbf7d3f16,
0xbe9ebf16,0xbf4f3f73,0x3f4f0000,0x3e9ebf73,0x3f73bf4f,0xbf16be9e,0xbf163f80,0x3f73be9e,0x3f350000,0x3f35bf80,0xbf350000,0xbf353f80,0xbf353f80,0x3f350000,0x3f35bf80,0xbf350000,
0xbf803e9e,0x3f4f3e9e,0xbe9ebf4f,0xbe9e3f80,0xbf73,0xbf163f73,0x3f73bf16,0xbf730000,0x3f353e9e,0x3e20bf73,0xbf643f4f,0x3f640000,0xbf353f73,0x3f7dbe9e,0xbee8bf16,0xbee83f80,
0xbf4f,0xbf733f4f,0x3f163e9e,0x3f16bf80,0x3f80bf16,0xbe9ebf16,0xbf4f3f73,0x3f4f0000,0xbf353f80,0x3f350000,0x3f35bf80,0xbf350000,0xbf350000,0xbf353f80,0x3f350000,0x3f35bf80,
0x3f73,0x3f16bf73,0xbf733f16,0x3f730000,0xbf803e9e,0x3f4f3e9e,0xbe9ebf4f,0xbe9e3f80,0x3f35bf73,0xbf7d3e9e,0x3ee83f16,0x3ee8bf80,0x3f353e9e,0x3e20bf73,0xbf643f4f,0x3f640000,
0xbf803f16,0x3e9e3f16,0x3f4fbf73,0xbf4f0000,0xbf4f,0xbf733f4f,0x3f163e9e,0x3f16bf80,0x3f350000,0x3f35bf80,0xbf350000,0xbf353f80,0xbf353f80,0x3f350000,0x3f35bf80,0xbf350000,
0x3f4fbf4f,0xbf803e9e,0x3f4f3e9e,0xbe9ebf4f,0x3f163f16,0xbf73,0xbf163f73,0x3f73bf16,0xbe20bf4f,0xbf353f73,0x3f7dbe9e,0xbee8bf16,0x3f7dbf16,0xbf35be9e,0xbe203f73,0x3f64bf4f,
0xbf733e9e,0x3f4f,0x3f73bf4f,0xbf16be9e,0x3e9ebf73,0xbf803f16,0x3e9e3f16,0x3f4fbf73,0xbf353f80,0x3f350000,0x3f35bf80,0xbf350000,0xbf350000,0xbf353f80,0x3f350000,0x3f35bf80,
0xbf16bf16,0x3f73,0x3f16bf73,0xbf733f16,0x3f4fbf4f,0xbf803e9e,0x3f4f3e9e,0xbe9ebf4f,0xbf7d3f16,0x3f353e9e,0x3e20bf73,0xbf643f4f,0xbe20bf4f,0xbf353f73,0x3f7dbe9e,0xbee8bf16,
0xbe9e3f73,0x3f80bf16,0xbe9ebf16,0xbf4f3f73,0xbf733e9e,0x3f4f,0x3f73bf4f,0xbf16be9e,0x3f350000,0x3f35bf80,0xbf350000,0xbf353f80,0xbf353f80,0x3f350000,0x3f35bf80,0xbf350000,
0xbf4f3f80,0x3e9e3e9e,0x3f80bf4f,0x3e9ebf4f,0xbf160000,0xbf733f73,0x3f16,0x3f73bf16,0xbf643f80,0xbe203f16,0x3f35be9e,0x3f7dbf73,0xbee80000,0xbf7d3f4f,0xbf353f73,0x3e203e9e,
0xbf733f80,0xbf163f4f,0x3e9e,0x3f16be9e,0xbe9e0000,0xbf4f3f16,0xbf803f73,0xbf4f3f73,0xbf7d3f80,0xbf643f73,0xbf353f4f,0xbee83f16,0xbe200000,0xbee83e9e,0xbf353f16,0xbf643f4f,
0x3f160000,0x3f73bf73,0xbf16,0xbf733f16,0xbf4f3f80,0x3e9e3e9e,0x3f80bf4f,0x3e9ebf4f,0x3ee80000,0x3f7dbf4f,0x3f35bf73,0xbe20be9e,0xbf643f80,0xbe203f16,0x3f35be9e,0x3f7dbf73,
0x3e9e0000,0x3f4fbf16,0x3f80bf73,0x3f4fbf73,0xbf733f80,0xbf163f4f,0x3e9e,0x3f16be9e,0x3e200000,0x3ee8be9e,0x3f35bf16,0x3f64bf4f,0xbf7d3f80,0xbf643f73,0xbf353f4f,0xbee83f16,
0xbf4f3e9e,0xbf4f3f80,0x3e9e3e9e,0x3f80bf4f,0x3f16bf73,0xbf160000,0xbf733f73,0x3f16,0x3ee8bf4f,0xbee80000,0xbf7d3f4f,0xbf353f73,0x3f64bf16,0x3f64bf80,0x3e20bf16,0xbf353e9e,
0x3f73bf4f,0x3f73bf80,0x3f16bf4f,0xbe9e,0xbe9e3f16,0x3e9e0000,0x3f4fbf16,0x3f80bf73,0xbe203e9e,0x3e200000,0x3ee8be9e,0x3f35bf16,0xbf7d3f73,0xbf7d3f80,0xbf643f73,0xbf353f4f,
0xbf163f73,0x3f160000,0x3f73bf73,0xbf16,0xbf4f3e9e,0xbf4f3f80,0x3e9e3e9e,0x3f80bf4f,0xbf643f16,0xbf643f80,0xbe203f16,0x3f35be9e,0x3ee8bf4f,0xbee80000,0xbf7d3f4f,0xbf353f73,
0x3e9ebf16,0xbe9e0000,0xbf4f3f16,0xbf803f73,0x3f73bf4f,0x3f73bf80,0x3f16bf4f,0xbe9e,0x3f7dbf73,0x3f7dbf80,0x3f64bf73,0x3f35bf4f,0xbe203e9e,0x3e200000,0x3ee8be9e,0x3f35bf16,
0x3e9ebf4f,0xbf4f3e9e,0xbf4f3f80,0x3e9e3e9e,0x3f73bf16,0x3f16bf73,0xbf160000,0xbf733f73,0x3e203e9e,0x3f64bf16,0x3f64bf80,0x3e20bf16,0xbf7d3f73,0xbee83f4f,0x3ee80000,0x3f7dbf4f,
0xbf163e9e,0xbf733f4f,0xbf733f80,0xbf163f4f,0x3f4fbf73,0x3e9ebf16,0xbe9e0000,0xbf4f3f16,0x3f64bf4f,0x3f7dbf73,0x3f7dbf80,0x3f64bf73,0xbee83f16,0xbe203e9e,0x3e200000,0x3ee8be9e,
0xbf733f16,0xbf163f73,0x3f160000,0x3f73bf73,0x3e9ebf4f,0xbf4f3e9e,0xbf4f3f80,0x3e9e3e9e,0x3f7dbf73,0x3ee8bf4f,0xbee80000,0xbf7d3f4f,0x3e203e9e,0x3f64bf16,0x3f64bf80,0x3e20bf16,
0xbf4f3f73,0xbe9e3f16,0x3e9e0000,0x3f4fbf16,0xbf163e9e,0xbf733f4f,0xbf733f80,0xbf163f4f,0x3ee8bf16,0x3e20be9e,0xbe200000,0xbee83e9e,0x3f64bf4f,0x3f7dbf73,0x3f7dbf80,0x3f64bf73,
0x3f80bf4f,0x3e9ebf4f,0xbf4f3e9e,0xbf4f3f80,0x3f16,0x3f73bf16,0x3f16bf73,0xbf160000,0xbf353e9e,0xbf7d3f73,0xbee83f4f,0x3ee80000,0x3f35bf73,0xbe20be9e,0xbf643f16,0xbf643f80,
0x3e9e,0x3f16be9e,0x3f73bf4f,0x3f73bf80,0xbf803f73,0xbf4f3f73,0xbe9e3f16,0x3e9e0000,0x3f35bf4f,0x3ee8bf16,0x3e20be9e,0xbe200000,0x3f35bf16,0x3f64bf4f,0x3f7dbf73,0x3f7dbf80,
0xbf16,0xbf733f16,0xbf163f73,0x3f160000,0x3f80bf4f,0x3e9ebf4f,0xbf4f3e9e,0xbf4f3f80,0xbf353f73,0x3e203e9e,0x3f64bf16,0x3f64bf80,0xbf353e9e,0xbf7d3f73,0xbee83f4f,0x3ee80000,
0x3f80bf73,0x3f4fbf73,0x3e9ebf16,0xbe9e0000,0x3e9e,0x3f16be9e,0x3f73bf4f,0x3f73bf80,0xbf353f16,0xbf643f4f,0xbf7d3f73,0xbf7d3f80,0x3f35bf4f,0x3ee8bf16,0x3e20be9e,0xbe200000,
0x3e9e3e9e,0x3f80bf4f,0x3e9ebf4f,0xbf4f3e9e,0xbf733f73,0x3f16,0x3f73bf16,0x3f16bf73,0x3f7dbf4f,0x3f35bf73,0xbe20be9e,0xbf643f16,0xbe203f16,0x3f35be9e,0x3f7dbf73,0x3ee8bf4f,
0x3f16bf4f,0xbe9e,0xbf163e9e,0xbf733f4f,0x3f4fbf16,0x3f80bf73,0x3f4fbf73,0x3e9ebf16,0xbee83e9e,0xbf353f16,0xbf643f4f,0xbf7d3f73,0x3f64bf73,0x3f35bf4f,0x3ee8bf16,0x3e20be9e,
0x3f73bf73,0xbf16,0xbf733f16,0xbf163f73,0x3e9e3e9e,0x3f80bf4f,0x3e9ebf4f,0xbf4f3e9e,0x3e20bf16,0xbf353e9e,0xbf7d3f73,0xbee83f4f,0x3f7dbf4f,0x3f35bf73,0xbe20be9e,0xbf643f16,
0xbf4f3f16,0xbf803f73,0xbf4f3f73,0xbe9e3f16,0x3f16bf4f,0xbe9e,0xbf163e9e,0xbf733f4f,0xbf643f73,0xbf353f4f,0xbee83f16,0xbe203e9e,0xbee83e9e,0xbf353f16,0xbf643f4f,0xbf7d3f73,
0xbf803f80,0xbf803f80,0xbf803f80,0xbf803f80,0,0,0,0,0xbf7d3f80,0xbf643f73,0xbf353f4f,0xbee83f16,0xbe200000,0xbee83e9e,0xbf353f16,0xbf643f4f,
0xbf733f80,0xbf163f4f,0x3e9e,0x3f16be9e,0xbe9e0000,0xbf4f3f16,0xbf803f73,0xbf4f3f73,0xbf643f80,0xbe203f16,0x3f35be9e,0x3f7dbf73,0xbee80000,0xbf7d3f4f,0xbf353f73,0x3e203e9e,
0,0,0,0,0x3f80bf80,0x3f80bf80,0x3f80bf80,0x3f80bf80,0xbe200000,0xbee83e9e,0xbf353f16,0xbf643f4f,0x3f7dbf80,0x3f64bf73,0x3f35bf4f,0x3ee8bf16,
0xbe9e0000,0xbf4f3f16,0xbf803f73,0xbf4f3f73,0x3f73bf80,0x3f16bf4f,0xbe9e,0xbf163e9e,0xbee80000,0xbf7d3f4f,0xbf353f73,0x3e203e9e,0x3f64bf80,0x3e20bf16,0xbf353e9e,0xbf7d3f73,
0xbf803f80,0xbf803f80,0xbf803f80,0xbf803f80,0,0,0,0,0xbe203e9e,0x3e200000,0x3ee8be9e,0x3f35bf16,0xbf7d3f73,0xbf7d3f80,0xbf643f73,0xbf353f4f,
0x3f73bf4f,0x3f73bf80,0x3f16bf4f,0xbe9e,0xbe9e3f16,0x3e9e0000,0x3f4fbf16,0x3f80bf73,0x3ee8bf4f,0xbee80000,0xbf7d3f4f,0xbf353f73,0x3f64bf16,0x3f64bf80,0x3e20bf16,0xbf353e9e,
0,0,0,0,0x3f80bf80,0x3f80bf80,0x3f80bf80,0x3f80bf80,0xbf7d3f73,0xbf7d3f80,0xbf643f73,0xbf353f4f,0x3e20be9e,0xbe200000,0xbee83e9e,0xbf353f16,
0xbe9e3f16,0x3e9e0000,0x3f4fbf16,0x3f80bf73,0xbf733f4f,0xbf733f80,0xbf163f4f,0x3e9e,0x3f64bf16,0x3f64bf80,0x3e20bf16,0xbf353e9e,0xbee83f4f,0x3ee80000,0x3f7dbf4f,0x3f35bf73,
0xbf803f80,0xbf803f80,0xbf803f80,0xbf803f80,0,0,0,0,0x3f64bf4f,0x3f7dbf73,0x3f7dbf80,0x3f64bf73,0xbee83f16,0xbe203e9e,0x3e200000,0x3ee8be9e,
0xbf163e9e,0xbf733f4f,0xbf733f80,0xbf163f4f,0x3f4fbf73,0x3e9ebf16,0xbe9e0000,0xbf4f3f16,0x3e203e9e,0x3f64bf16,0x3f64bf80,0x3e20bf16,0xbf7d3f73,0xbee83f4f,0x3ee80000,0x3f7dbf4f,
0,0,0,0,0x3f80bf80,0x3f80bf80,0x3f80bf80,0x3f80bf80,0xbee83f16,0xbe203e9e,0x3e200000,0x3ee8be9e,0xbf643f4f,0xbf7d3f73,0xbf7d3f80,0xbf643f73,
0x3f4fbf73,0x3e9ebf16,0xbe9e0000,0xbf4f3f16,0x3f16be9e,0x3f73bf4f,0x3f73bf80,0x3f16bf4f,0xbf7d3f73,0xbee83f4f,0x3ee80000,0x3f7dbf4f,0xbe20be9e,0xbf643f16,0xbf643f80,0xbe203f16,
0xbf803f80,0xbf803f80,0xbf803f80,0xbf803f80,0,0,0,0,0x3f35bf4f,0x3ee8bf16,0x3e20be9e,0xbe200000,0x3f35bf16,0x3f64bf4f,0x3f7dbf73,0x3f7dbf80,
0x3e9e,0x3f16be9e,0x3f73bf4f,0x3f73bf80,0xbf803f73,0xbf4f3f73,0xbe9e3f16,0x3e9e0000,0xbf353e9e,0xbf7d3f73,0xbee83f4f,0x3ee80000,0x3f35bf73,0xbe20be9e,0xbf643f16,0xbf643f80,
0,0,0,0,0x3f80bf80,0x3f80bf80,0x3f80bf80,0x3f80bf80,0x3f35bf16,0x3f64bf4f,0x3f7dbf73,0x3f7dbf80,0xbf353f4f,0xbee83f16,0xbe203e9e,0x3e200000,
0xbf803f73,0xbf4f3f73,0xbe9e3f16,0x3e9e0000,0xbe9e,0xbf163e9e,0xbf733f4f,0xbf733f80,0x3f35bf73,0xbe20be9e,0xbf643f16,0xbf643f80,0x3f35be9e,0x3f7dbf73,0x3ee8bf4f,0xbee80000,
0xbf803f80,0xbf803f80,0xbf803f80,0xbf803f80,0,0,0,0,0xbee83e9e,0xbf353f16,0xbf643f4f,0xbf7d3f73,0x3f64bf73,0x3f35bf4f,0x3ee8bf16,0x3e20be9e,
0x3f16bf4f,0xbe9e,0xbf163e9e,0xbf733f4f,0x3f4fbf16,0x3f80bf73,0x3f4fbf73,0x3e9ebf16,0x3f7dbf4f,0x3f35bf73,0xbe20be9e,0xbf643f16,0xbe203f16,0x3f35be9e,0x3f7dbf73,0x3ee8bf4f,
0,0,0,0,0x3f80bf80,0x3f80bf80,0x3f80bf80,0x3f80bf80,0x3f64bf73,0x3f35bf4f,0x3ee8bf16,0x3e20be9e,0x3ee8be9e,0x3f35bf16,0x3f64bf4f,0x3f7dbf73,
0x3f4fbf16,0x3f80bf73,0x3f4fbf73,0x3e9ebf16,0xbf163f4f,0x3e9e,0x3f16be9e,0x3f73bf4f,0xbe203f16,0x3f35be9e,0x3f7dbf73,0x3ee8bf4f,0xbf7d3f4f,0xbf353f73,0x3e203e9e,0x3f64bf16,
0xbf4f3f80,0x3e9e3e9e,0x3f80bf4f,0x3e9ebf4f,0xbf160000,0xbf733f73,0x3f16,0x3f73bf16,0xbf353f80,0x3f350000,0x3f35bf80,0xbf350000,0xbf350000,0xbf353f80,0x3f350000,0x3f35bf80,
0xbf163f80,0x3f73be9e,0xbf4f,0xbf733f4f,0xbf4f0000,0xbe9e3f73,0x3f80bf16,0xbe9ebf16,0xbee83f80,0x3f7dbf16,0xbf35be9e,0xbe203f73,0xbf640000,0x3e203f4f,0x3f35bf73,0xbf7d3e9e,
0xbf160000,0xbf733f73,0x3f16,0x3f73bf16,0x3f4fbf80,0xbe9ebe9e,0xbf803f4f,0xbe9e3f4f,0xbf350000,0xbf353f80,0x3f350000,0x3f35bf80,0x3f35bf80,0xbf350000,0xbf353f80,0x3f350000,
0xbf4f0000,0xbe9e3f73,0x3f80bf16,0xbe9ebf16,0x3f16bf80,0xbf733e9e,0x3f4f,0x3f73bf4f,0xbf640000,0x3e203f4f,0x3f35bf73,0xbf7d3e9e,0x3ee8bf80,0xbf7d3f16,0x3f353e9e,0x3e20bf73,
0xbf4f3e9e,0xbf4f3f80,0x3e9e3e9e,0x3f80bf4f,0x3f16bf73,0xbf160000,0xbf733f73,0x3f16,0xbf353f80,0x3f350000,0x3f35bf80,0xbf350000,0xbf350000,0xbf353f80,0x3f350000,0x3f35bf80,
0x3f163e9e,0x3f16bf80,0xbf733e9e,0x3f4f,0xbf4f3f73,0x3f4f0000,0x3e9ebf73,0xbf803f16,0x3f64bf4f,0xbf640000,0x3e203f4f,0x3f35bf73,0x3ee83f16,0x3ee8bf80,0xbf7d3f16,0x3f353e9e,
0x3f16bf73,0xbf160000,0xbf733f73,0x3f16,0x3f4fbe9e,0x3f4fbf80,0xbe9ebe9e,0xbf803f4f,0xbf350000,0xbf353f80,0x3f350000,0x3f35bf80,0x3f35bf80,0xbf350000,0xbf353f80,0x3f350000,
0xbf4f3f73,0x3f4f0000,0x3e9ebf73,0xbf803f16,0xbf16be9e,0xbf163f80,0x3f73be9e,0xbf4f,0x3ee83f16,0x3ee8bf80,0xbf7d3f16,0x3f353e9e,0xbf643f4f,0x3f640000,0xbe20bf4f,0xbf353f73,
0x3e9ebf4f,0xbf4f3e9e,0xbf4f3f80,0x3e9e3e9e,0x3f73bf16,0x3f16bf73,0xbf160000,0xbf733f73,0xbf353f80,0x3f350000,0x3f35bf80,0xbf350000,0xbf350000,0xbf353f80,0x3f350000,0x3f35bf80,
0x3f73bf4f,0xbf16be9e,0xbf163f80,0x3f73be9e,0x3e9e3f16,0x3f4fbf73,0xbf4f0000,0xbe9e3f73,0xbf7d3e9e,0x3ee83f16,0x3ee8bf80,0xbf7d3f16,0x3e20bf73,0xbf643f4f,0x3f640000,0xbe20bf4f,
0x3f73bf16,0x3f16bf73,0xbf160000,0xbf733f73,0xbe9e3f4f,0x3f4fbe9e,0x3f4fbf80,0xbe9ebe9e,0xbf350000,0xbf353f80,0x3f350000,0x3f35bf80,0x3f35bf80,0xbf350000,0xbf353f80,0x3f350000,
0x3e9e3f16,0x3f4fbf73,0xbf4f0000,0xbe9e3f73,0xbf733f4f,0x3f163e9e,0x3f16bf80,0xbf733e9e,0x3e20bf73,0xbf643f4f,0x3f640000,0xbe20bf4f,0x3f7dbe9e,0xbee8bf16,0xbee83f80,0x3f7dbf16,
0x3f80bf4f,0x3e9ebf4f,0xbf4f3e9e,0xbf4f3f80,0x3f16,0x3f73bf16,0x3f16bf73,0xbf160000,0xbf353f80,0x3f350000,0x3f35bf80,0xbf350000,0xbf350000,0xbf353f80,0x3f350000,0x3f35bf80,
0xbf4f,0xbf733f4f,0x3f163e9e,0x3f16bf80,0x3f80bf16,0xbe9ebf16,0xbf4f3f73,0x3f4f0000,0x3f353e9e,0x3e20bf73,0xbf643f4f,0x3f640000,0xbf353f73,0x3f7dbe9e,0xbee8bf16,0xbee83f80,
0x3f16,0x3f73bf16,0x3f16bf73,0xbf160000,0xbf803f4f,0xbe9e3f4f,0x3f4fbe9e,0x3f4fbf80,0xbf350000,0xbf353f80,0x3f350000,0x3f35bf80,0x3f35bf80,0xbf350000,0xbf353f80,0x3f350000,
0x3f80bf16,0xbe9ebf16,0xbf4f3f73,0x3f4f0000,0x3f4f,0x3f73bf4f,0xbf16be9e,0xbf163f80,0xbf353f73,0x3f7dbe9e,0xbee8bf16,0xbee83f80,0xbf35be9e,0xbe203f73,0x3f64bf4f,0xbf640000,
0x3e9e3e9e,0x3f80bf4f,0x3e9ebf4f,0xbf4f3e9e,0xbf733f73,0x3f16,0x3f73bf16,0x3f16bf73,0xbf353f80,0x3f350000,0x3f35bf80,0xbf350000,0xbf350000,0xbf353f80,0x3f350000,0x3f35bf80,
0xbf733e9e,0x3f4f,0x3f73bf4f,0xbf16be9e,0x3e9ebf73,0xbf803f16,0x3e9e3f16,0x3f4fbf73,0xbe20bf4f,0xbf353f73,0x3f7dbe9e,0xbee8bf16,0x3f7dbf16,0xbf35be9e,0xbe203f73,0x3f64bf4f,
0xbf733f73,0x3f16,0x3f73bf16,0x3f16bf73,0xbe9ebe9e,0xbf803f4f,0xbe9e3f4f,0x3f4fbe9e,0xbf350000,0xbf353f80,0x3f350000,0x3f35bf80,0x3f35bf80,0xbf350000,0xbf353f80,0x3f350000,
0x3e9ebf73,0xbf803f16,0x3e9e3f16,0x3f4fbf73,0x3f73be9e,0xbf4f,0xbf733f4f,0x3f163e9e,0x3f7dbf16,0xbf35be9e,0xbe203f73,0x3f64bf4f,0x3e203f4f,0x3f35bf73,0xbf7d3e9e,0x3ee83f16,
0xbe9e3f80,0x3f4fbf4f,0xbf803e9e,0x3f4f3e9e,0xbf730000,0x3f163f16,0xbf73,0xbf163f73,0xbe203f80,0x3ee8bf73,0xbf353f4f,0x3f64bf16,0xbf7d0000,0x3f643e9e,0xbf35bf16,0x3ee83f4f,
0x3f80,0xbf80,0x3f80,0xbf80,0xbf800000,0x3f800000,0xbf800000,0x3f800000,0x3e203f80,0xbee8bf73,0x3f353f4f,0xbf64bf16,0xbf7d0000,0x3f64be9e,0xbf353f16,0x3ee8bf4f,
0xbf730000,0x3f163f16,0xbf73,0xbf163f73,0x3e9ebf80,0xbf4f3f4f,0x3f80be9e,0xbf4fbe9e,0xbf7d0000,0x3f643e9e,0xbf35bf16,0x3ee83f4f,0x3e20bf80,0xbee83f73,0x3f35bf4f,0xbf643f16,
0xbf800000,0x3f800000,0xbf800000,0x3f800000,0xbf80,0x3f80,0xbf80,0x3f80,0xbf7d0000,0x3f64be9e,0xbf353f16,0x3ee8bf4f,0xbe20bf80,0x3ee83f73,0xbf35bf4f,0x3f643f16,
0xbe9ebf4f,0xbe9e3f80,0x3f4fbf4f,0xbf803e9e,0x3f73bf16,0xbf730000,0x3f163f16,0xbf73,0xbf7d3e9e,0x3f7d0000,0xbf64be9e,0x3f353f16,0xbe20bf73,0xbe203f80,0x3ee8bf73,0xbf353f4f,
0x3f80,0xbf80,0x3f80,0xbf80,0xbf800000,0x3f800000,0xbf800000,0x3f800000,0x3f7d3e9e,0xbf7d0000,0x3f64be9e,0xbf353f16,0xbe203f73,0xbe20bf80,0x3ee83f73,0xbf35bf4f,
0x3f73bf16,0xbf730000,0x3f163f16,0xbf73,0x3e9e3f4f,0x3e9ebf80,0xbf4f3f4f,0x3f80be9e,0xbe20bf73,0xbe203f80,0x3ee8bf73,0xbf353f4f,0x3f7dbe9e,0xbf7d0000,0x3f643e9e,0xbf35bf16,
0xbf800000,0x3f800000,0xbf800000,0x3f800000,0xbf80,0x3f80,0xbf80,0x3f80,0xbe203f73,0xbe20bf80,0x3ee83f73,0xbf35bf4f,0xbf7dbe9e,0x3f7d0000,0xbf643e9e,0x3f35bf16,
0x3f4f3e9e,0xbe9ebf4f,0xbe9e3f80,0x3f4fbf4f,0xbf163f73,0x3f73bf16,0xbf730000,0x3f163f16,0xbee8bf4f,0x3e203f73,0x3e20bf80,0xbee83f73,0x3f64bf16,0xbf7d3e9e,0x3f7d0000,0xbf64be9e,
0x3f80,0xbf80,0x3f80,0xbf80,0xbf800000,0x3f800000,0xbf800000,0x3f800000,0x3ee8bf4f,0xbe203f73,0xbe20bf80,0x3ee83f73,0x3f643f16,0xbf7dbe9e,0x3f7d0000,0xbf643e9e,
0xbf163f73,0x3f73bf16,0xbf730000,0x3f163f16,0xbf4fbe9e,0x3e9e3f4f,0x3e9ebf80,0xbf4f3f4f,0x3f64bf16,0xbf7d3e9e,0x3f7d0000,0xbf64be9e,0x3ee83f4f,0xbe20bf73,0xbe203f80,0x3ee8bf73,
0xbf800000,0x3f800000,0xbf800000,0x3f800000,0xbf80,0x3f80,0xbf80,0x3f80,0x3f643f16,0xbf7dbe9e,0x3f7d0000,0xbf643e9e,0xbee83f4f,0x3e20bf73,0x3e203f80,0xbee8bf73,
0xbf803e9e,0x3f4f3e9e,0xbe9ebf4f,0xbe9e3f80,0xbf73,0xbf163f73,0x3f73bf16,0xbf730000,0x3f35bf4f,0xbf643f16,0x3f7dbe9e,0xbf7d0000,0x3f353f16,0xbee8bf4f,0x3e203f73,0x3e20bf80,
0x3f80,0xbf80,0x3f80,0xbf80,0xbf800000,0x3f800000,0xbf800000,0x3f800000,0xbf35bf4f,0x3f643f16,0xbf7dbe9e,0x3f7d0000,0x3f35bf16,0xbee83f4f,0x3e20bf73,0x3e203f80,
0xbf73,0xbf163f73,0x3f73bf16,0xbf730000,0x3f80be9e,0xbf4fbe9e,0x3e9e3f4f,0x3e9ebf80,0x3f353f16,0xbee8bf4f,0x3e203f73,0x3e20bf80,0xbf353f4f,0x3f64bf16,0xbf7d3e9e,0x3f7d0000,
0xbf800000,0x3f800000,0xbf800000,0x3f800000,0xbf80,0x3f80,0xbf80,0x3f80,0x3f35bf16,0xbee83f4f,0x3e20bf73,0x3e203f80,0x3f353f4f,0xbf64bf16,0x3f7d3e9e,0xbf7d0000,
0x3f4fbf4f,0xbf803e9e,0x3f4f3e9e,0xbe9ebf4f,0x3f163f16,0xbf73,0xbf163f73,0x3f73bf16,0x3f643e9e,0xbf35bf16,0x3ee83f4f,0xbe20bf73,0xbee83f73,0x3f35bf4f,0xbf643f16,0x3f7dbe9e,
0x3f80,0xbf80,0x3f80,0xbf80,0xbf800000,0x3f800000,0xbf800000,0x3f800000,0xbf643e9e,0x3f35bf16,0xbee83f4f,0x3e20bf73,0xbee8bf73,0x3f353f4f,0xbf64bf16,0x3f7d3e9e,
0x3f163f16,0xbf73,0xbf163f73,0x3f73bf16,0xbf4f3f4f,0x3f80be9e,0xbf4fbe9e,0x3e9e3f4f,0xbee83f73,0x3f35bf4f,0xbf643f16,0x3f7dbe9e,0xbf64be9e,0x3f353f16,0xbee8bf4f,0x3e203f73,
0xbf800000,0x3f800000,0xbf800000,0x3f800000,0xbf80,0x3f80,0xbf80,0x3f80,0xbee8bf73,0x3f353f4f,0xbf64bf16,0x3f7d3e9e,0x3f64be9e,0xbf353f16,0x3ee8bf4f,0xbe203f73,
0x3e9e3f80,0xbf4fbf4f,0x3f803e9e,0xbf4f3e9e,0xbf730000,0x3f16bf16,0x3f73,0xbf16bf73,0x3ee83f80,0xbf7dbf16,0x3f35be9e,0x3e203f73,0xbf640000,0x3e20bf4f,0x3f353f73,0xbf7dbe9e,
0x3f163f80,0xbf73be9e,0xbf4f,0x3f733f4f,0xbf4f0000,0xbe9ebf73,0x3f803f16,0xbe9e3f16,0x3f353f80,0xbf350000,0xbf35bf80,0x3f350000,0xbf350000,0xbf35bf80,0x3f350000,0x3f353f80,
0xbf730000,0x3f16bf16,0x3f73,0xbf16bf73,0xbe9ebf80,0x3f4f3f4f,0xbf80be9e,0x3f4fbe9e,0xbf640000,0x3e20bf4f,0x3f353f73,0xbf7dbe9e,0xbee8bf80,0x3f7d3f16,0xbf353e9e,0xbe20bf73,
0xbf4f0000,0xbe9ebf73,0x3f803f16,0xbe9e3f16,0xbf16bf80,0x3f733e9e,0x3f4f,0xbf73bf4f,0xbf350000,0xbf35bf80,0x3f350000,0x3f353f80,0xbf35bf80,0x3f350000,0x3f353f80,0xbf350000,
0x3e9ebf4f,0x3e9e3f80,0xbf4fbf4f,0x3f803e9e,0x3f733f16,0xbf730000,0x3f16bf16,0x3f73,0xbf64bf4f,0x3f640000,0xbe203f4f,0xbf35bf73,0x3ee8bf16,0x3ee83f80,0xbf7dbf16,0x3f35be9e,
0xbf163e9e,0xbf16bf80,0x3f733e9e,0x3f4f,0xbf4fbf73,0x3f4f0000,0x3e9e3f73,0xbf80bf16,0x3f353f80,0xbf350000,0xbf35bf80,0x3f350000,0xbf350000,0xbf35bf80,0x3f350000,0x3f353f80,
0x3f733f16,0xbf730000,0x3f16bf16,0x3f73,0xbe9e3f4f,0xbe9ebf80,0x3f4f3f4f,0xbf80be9e,0x3ee8bf16,0x3ee83f80,0xbf7dbf16,0x3f35be9e,0x3f643f4f,0xbf640000,0x3e20bf4f,0x3f353f73,
0xbf4fbf73,0x3f4f0000,0x3e9e3f73,0xbf80bf16,0x3f16be9e,0x3f163f80,0xbf73be9e,0xbf4f,0xbf350000,0xbf35bf80,0x3f350000,0x3f353f80,0xbf35bf80,0x3f350000,0x3f353f80,0xbf350000,
0xbf4f3e9e,0x3e9ebf4f,0x3e9e3f80,0xbf4fbf4f,0xbf16bf73,0x3f733f16,0xbf730000,0x3f16bf16,0x3f7d3e9e,0xbee83f16,0xbee8bf80,0x3f7d3f16,0x3e203f73,0xbf64bf4f,0x3f640000,0xbe203f4f,
0xbf73bf4f,0x3f16be9e,0x3f163f80,0xbf73be9e,0x3e9ebf16,0x3f4f3f73,0xbf4f0000,0xbe9ebf73,0x3f353f80,0xbf350000,0xbf35bf80,0x3f350000,0xbf350000,0xbf35bf80,0x3f350000,0x3f353f80,
0xbf16bf73,0x3f733f16,0xbf730000,0x3f16bf16,0x3f4fbe9e,0xbe9e3f4f,0xbe9ebf80,0x3f4f3f4f,0x3e203f73,0xbf64bf4f,0x3f640000,0xbe203f4f,0xbf7dbe9e,0x3ee8bf16,0x3ee83f80,0xbf7dbf16,
0x3e9ebf16,0x3f4f3f73,0xbf4f0000,0xbe9ebf73,0x3f733f4f,0xbf163e9e,0xbf16bf80,0x3f733e9e,0xbf350000,0xbf35bf80,0x3f350000,0x3f353f80,0xbf35bf80,0x3f350000,0x3f353f80,0xbf350000,
0x3f803e9e,0xbf4f3e9e,0x3e9ebf4f,0x3e9e3f80,0x3f73,0xbf16bf73,0x3f733f16,0xbf730000,0xbf353e9e,0xbe20bf73,0x3f643f4f,0xbf640000,0xbf35bf73,0x3f7d3e9e,0xbee83f16,0xbee8bf80,
0xbf4f,0x3f733f4f,0xbf163e9e,0xbf16bf80,0x3f803f16,0xbe9e3f16,0xbf4fbf73,0x3f4f0000,0x3f353f80,0xbf350000,0xbf35bf80,0x3f350000,0xbf350000,0xbf35bf80,0x3f350000,0x3f353f80,
0x3f73,0xbf16bf73,0x3f733f16,0xbf730000,0xbf80be9e,0x3f4fbe9e,0xbe9e3f4f,0xbe9ebf80,0xbf35bf73,0x3f7d3e9e,0xbee83f16,0xbee8bf80,0x3f35be9e,0x3e203f73,0xbf64bf4f,0x3f640000,
0x3f803f16,0xbe9e3f16,0xbf4fbf73,0x3f4f0000,0x3f4f,0xbf73bf4f,0x3f16be9e,0x3f163f80,0xbf350000,0xbf35bf80,0x3f350000,0x3f353f80,0xbf35bf80,0x3f350000,0x3f353f80,0xbf350000,
0xbf4fbf4f,0x3f803e9e,0xbf4f3e9e,0x3e9ebf4f,0x3f16bf16,0x3f73,0xbf16bf73,0x3f733f16,0x3e20bf4f,0x3f353f73,0xbf7dbe9e,0x3ee8bf16,0x3f7d3f16,0xbf353e9e,0xbe20bf73,0x3f643f4f,
0x3f733e9e,0x3f4f,0xbf73bf4f,0x3f16be9e,0x3e9e3f73,0xbf80bf16,0x3e9ebf16,0x3f4f3f73,0x3f353f80,0xbf350000,0xbf35bf80,0x3f350000,0xbf350000,0xbf35bf80,0x3f350000,0x3f353f80,
0x3f16bf16,0x3f73,0xbf16bf73,0x3f733f16,0x3f4f3f4f,0xbf80be9e,0x3f4fbe9e,0xbe9e3f4f,0x3f7d3f16,0xbf353e9e,0xbe20bf73,0x3f643f4f,0xbe203f4f,0xbf35bf73,0x3f7d3e9e,0xbee83f16,
0x3e9e3f73,0xbf80bf16,0x3e9ebf16,0x3f4f3f73,0xbf73be9e,0xbf4f,0x3f733f4f,0xbf163e9e,0xbf350000,0xbf35bf80,0x3f350000,0x3f353f80,0xbf35bf80,0x3f350000,0x3f353f80,0xbf350000,
0x3f4f3f80,0xbe9e3e9e,0xbf80bf4f,0xbe9ebf4f,0xbf160000,0xbf73bf73,0xbf16,0x3f733f16,0x3f643f80,0x3e203f16,0xbf35be9e,0xbf7dbf73,0xbee80000,0xbf7dbf4f,0xbf35bf73,0x3e20be9e,
0x3f733f80,0x3f163f4f,0x3e9e,0xbf16be9e,0xbe9e0000,0xbf4fbf16,0xbf80bf73,0xbf4fbf73,0x3f7d3f80,0x3f643f73,0x3f353f4f,0x3ee83f16,0xbe200000,0xbee8be9e,0xbf35bf16,0xbf64bf4f,
0xbf160000,0xbf73bf73,0xbf16,0x3f733f16,0xbf4fbf80,0x3e9ebe9e,0x3f803f4f,0x3e9e3f4f,0xbee80000,0xbf7dbf4f,0xbf35bf73,0x3e20be9e,0xbf64bf80,0xbe20bf16,0x3f353e9e,0x3f7d3f73,
0xbe9e0000,0xbf4fbf16,0xbf80bf73,0xbf4fbf73,0xbf73bf80,0xbf16bf4f,0xbe9e,0x3f163e9e,0xbe200000,0xbee8be9e,0xbf35bf16,0xbf64bf4f,0xbf7dbf80,0xbf64bf73,0xbf35bf4f,0xbee8bf16,
0x3f4f3e9e,0x3f4f3f80,0xbe9e3e9e,0xbf80bf4f,0x3f163f73,0xbf160000,0xbf73bf73,0xbf16,0xbee8bf4f,0x3ee80000,0x3f7d3f4f,0x3f353f73,0x3f643f16,0x3f643f80,0x3e203f16,0xbf35be9e,
0xbf73bf4f,0xbf73bf80,0xbf16bf4f,0xbe9e,0xbe9ebf16,0x3e9e0000,0x3f4f3f16,0x3f803f73,0x3e203e9e,0xbe200000,0xbee8be9e,0xbf35bf16,0xbf7dbf73,0xbf7dbf80,0xbf64bf73,0xbf35bf4f,
0x3f163f73,0xbf160000,0xbf73bf73,0xbf16,0xbf4fbe9e,0xbf4fbf80,0x3e9ebe9e,0x3f803f4f,0x3f643f16,0x3f643f80,0x3e203f16,0xbf35be9e,0x3ee83f4f,0xbee80000,0xbf7dbf4f,0xbf35bf73,
0xbe9ebf16,0x3e9e0000,0x3f4f3f16,0x3f803f73,0x3f733f4f,0x3f733f80,0x3f163f4f,0x3e9e,0xbf7dbf73,0xbf7dbf80,0xbf64bf73,0xbf35bf4f,0xbe20be9e,0x3e200000,0x3ee83e9e,0x3f353f16,
0xbe9ebf4f,0x3f4f3e9e,0x3f4f3f80,0xbe9e3e9e,0x3f733f16,0x3f163f73,0xbf160000,0xbf73bf73,0xbe203e9e,0xbf64bf16,0xbf64bf80,0xbe20bf16,0xbf7dbf73,0xbee8bf4f,0x3ee80000,0x3f7d3f4f,
0x3f163e9e,0x3f733f4f,0x3f733f80,0x3f163f4f,0x3f4f3f73,0x3e9e3f16,0xbe9e0000,0xbf4fbf16,0xbf64bf4f,0xbf7dbf73,0xbf7dbf80,0xbf64bf73,0xbee8bf16,0xbe20be9e,0x3e200000,0x3ee83e9e,
0x3f733f16,0x3f163f73,0xbf160000,0xbf73bf73,0x3e9e3f4f,0xbf4fbe9e,0xbf4fbf80,0x3e9ebe9e,0xbf7dbf73,0xbee8bf4f,0x3ee80000,0x3f7d3f4f,0x3e20be9e,0x3f643f16,0x3f643f80,0x3e203f16,
0x3f4f3f73,0x3e9e3f16,0xbe9e0000,0xbf4fbf16,0xbf16be9e,0xbf73bf4f,0xbf73bf80,0xbf16bf4f,0xbee8bf16,0xbe20be9e,0x3e200000,0x3ee83e9e,0x3f643f4f,0x3f7d3f73,0x3f7d3f80,0x3f643f73,
0xbf80bf4f,0xbe9ebf4f,0x3f4f3e9e,0x3f4f3f80,0xbf16,0x3f733f16,0x3f163f73,0xbf160000,0x3f353e9e,0x3f7d3f73,0x3ee83f4f,0xbee80000,0x3f353f73,0xbe203e9e,0xbf64bf16,0xbf64bf80,
0x3e9e,0xbf16be9e,0xbf73bf4f,0xbf73bf80,0xbf80bf73,0xbf4fbf73,0xbe9ebf16,0x3e9e0000,0xbf35bf4f,0xbee8bf16,0xbe20be9e,0x3e200000,0x3f353f16,0x3f643f4f,0x3f7d3f73,0x3f7d3f80,
0xbf16,0x3f733f16,0x3f163f73,0xbf160000,0x3f803f4f,0x3e9e3f4f,0xbf4fbe9e,0xbf4fbf80,0x3f353f73,0xbe203e9e,0xbf64bf16,0xbf64bf80,0xbf35be9e,0xbf7dbf73,0xbee8bf4f,0x3ee80000,
0xbf80bf73,0xbf4fbf73,0xbe9ebf16,0x3e9e0000,0xbe9e,0x3f163e9e,0x3f733f4f,0x3f733f80,0x3f353f16,0x3f643f4f,0x3f7d3f73,0x3f7d3f80,0x3f353f4f,0x3ee83f16,0x3e203e9e,0xbe200000,
0xbe9e3e9e,0xbf80bf4f,0xbe9ebf4f,0x3f4f3e9e,0xbf73bf73,0xbf16,0x3f733f16,0x3f163f73,0xbf7dbf4f,0xbf35bf73,0x3e20be9e,0x3f643f16,0xbe20bf16,0x3f353e9e,0x3f7d3f73,0x3ee83f4f,
0xbf16bf4f,0xbe9e,0x3f163e9e,0x3f733f4f,0x3f4f3f16,0x3f803f73,0x3f4f3f73,0x3e9e3f16,0x3ee83e9e,0x3f353f16,0x3f643f4f,0x3f7d3f73,0x3f643f73,0x3f353f4f,0x3ee83f16,0x3e203e9e,
0xbf73bf73,0xbf16,0x3f733f16,0x3f163f73,0x3e9ebe9e,0x3f803f4f,0x3e9e3f4f,0xbf4fbe9e,0xbe20bf16,0x3f353e9e,0x3f7d3f73,0x3ee83f4f,0x3f7d3f4f,0x3f353f73,0xbe203e9e,0xbf64bf16,
0x3f4f3f16,0x3f803f73,0x3f4f3f73,0x3e9e3f16,0x3f163f4f,0x3e9e,0xbf16be9e,0xbf73bf4f,0x3f643f73,0x3f353f4f,0x3ee83f16,0x3e203e9e,0xbee8be9e,0xbf35bf16,0xbf64bf4f,0xbf7dbf73,
0x3f800000,0,0x3f800000,0,0x3f800000,0,0x3f7cd925,0x3e20305b,0x3f800000,0,0x3f737871,0x3e9e377a,0x3f800000,0,0x3f641901,0x3ee87171,
0x3f800000,0,0x3f800000,0,0x3f7ff35e,0x3ca0d6d6,0x3f7ff35e,0x3ca0d6d6,0x3f7fcd79,0x3d20cee7,0x3f7fcd79,0x3d20cee7,0x3f7f8e56,0x3d712283,0x3f7f8e56,0x3d712283,
0x3f800000,0,0x3f800000,0,0x3f7fcd79,0x3d20cee7,0x3f7fcd79,0x3d20cee7,0x3f7f35f9,0x3da0af2a,0x3f7f35f9,0x3da0af2a,0x3f7e39bc,0x3df0b772,0x3f7e39bc,0x3df0b772,
0x3f800000,0,0x3f800000,0,0x3f7f8e56,0x3d712283,0x3f7f8e56,0x3d712283,0x3f7e39bc,0x3df0b772,0x3f7e39bc,0x3df0b772,0x3f7c0361,0x3e3403f1,0x3f7c0361,0x3e3403f1,
0x3f800000,0,0x3f800000,0,0x3f7f35f9,0x3da0af2a,0x3f7f35f9,0x3da0af2a,0x3f7cd925,0x3e20305b,0x3f7cd925,0x3e20305b,0x3f78ed3c,0x3e6f0c4d,0x3f78ed3c,0x3e6f0c4d,
0x3f800000,0,0x3f800000,0,0x3f7ec46d,0x3dc8bd36,0x3f7ec46d,0x3dc8bd36,0x3f7b14be,0x3e47c5c2,0x3f7b14be,0x3e47c5c2,0x3f74fa0b,0x3e94a031,0x3f74fa0b,0x3e94a031,
0x3f800000,0,0x3f800000,0,0x3f7e39bc,0x3df0b772,0x3f7e39bc,0x3df0b772,0x3f78ed3c,0x3e6f0c4d,0x3f78ed3c,0x3e6f0c4d,0x3f702d4f,0x3eb13641,0x3f702d4f,0x3eb13641,
0x3f800000,0,0x3f800000,0,0x3f7d95f4,0x3e0c4cf7,0x3f7d95f4,0x3e0c4cf7,0x3f766377,0x3e8afa3e,0x3f766377,0x3e8afa3e,0x3f6a8b4b,0x3ecd2ef3,0x3f6a8b4b,0x3ecd2ef3,
0x3f800000,0,0x3f7f35f9,0x3da0af2a,0x3f800000,0,0x3f78ed3c,0x3e6f0c4d,0x3f800000,0,0x3f6c835e,0x3ec3ef15,0x3f800000,0,0x3f5a46a0,0x3f05c277,
0x3f7ffcd7,0x3c20d8d2,0x3f7ffcd7,0x3c20d8d2,0x3f7fe394,0x3cf13d4c,0x3f7fe394,0x3cf13d4c,0x3f7fb10f,0x3d48fb30,0x3f7fb10f,0x3d48fb30,0x3f7f654e,0x3d8ca1f2,0x3f7f654e,0x3d8ca1f2,
0x3f7ff35e,0x3ca0d6d6,0x3f7ff35e,0x3ca0d6d6,0x3f7f8e56,0x3d712283,0x3f7f8e56,0x3d712283,0x3f7ec46d,0x3dc8bd36,0x3f7ec46d,0x3dc8bd36,0x3f7d95f4,0x3e0c4cf7,0x3f7d95f4,0x3e0c4cf7,
0x3f7fe394,0x3cf13d4c,0x3f7fe394,0x3cf13d4c,0x3f7f0059,0x3db4b86a,0x3f7f0059,0x3db4b86a,0x3f7d3aac,0x3e164083,0x3f7d3aac,0x3e164083,0x3f7a9421,0x3e519f65,0x3f7a9421,0x3e519f65,
0x3f7fcd79,0x3d20cee7,0x3f7fcd79,0x3d20cee7,0x3f7e39bc,0x3df0b772,0x3f7e39bc,0x3df0b772,0x3f7b14be,0x3e47c5c2,0x3f7b14be,0x3e47c5c2,0x3f766377,0x3e8afa3e,0x3f766377,0x3e8afa3e,
0x3f7fb10f,0x3d48fb30,0x3f7fb10f,0x3d48fb30,0x3f7d3aac,0x3e164083,0x3f7d3aac,0x3e164083,0x3f7853f8,0x3e78cfcc,0x3f7853f8,0x3e78cfcc,0x3f710908,0x3eac7cd4,0x3f710908,0x3eac7cd4,
0x3f7f8e56,0x3d712283,0x3f7f8e56,0x3d712283,0x3f7c0361,0x3e3403f1,0x3f7c0361,0x3e3403f1,0x3f74fa0b,0x3e94a031,0x3f74fa0b,0x3e94a031,0x3f6a8b4b,0x3ecd2ef3,0x3f6a8b4b,0x3ecd2ef3,
0x3f7f654e,0x3d8ca1f2,0x3f7f654e,0x3d8ca1f2,0x3f7a9421,0x3e519f65,0x3f7a9421,0x3e519f65,0x3f710908,0x3eac7cd4,0x3f710908,0x3eac7cd4,0x3f62f219,0x3eece91a,0x3f62f219,0x3eece91a,
0x3f800000,0,0x3f4f1bbd,0x3f167918,0x3f800000,0,0x3f3504f3,0x3f3504f3,0x3f800000,0,0x3f167918,0x3f4f1bbd,0x3f800000,0,0x3ee87171,0x3f641901,
0x3f7f35f9,0x3da0af2a,0x3f7f35f9,0x3da0af2a,0x3f7ec46d,0x3dc8bd36,0x3f7ec46d,0x3dc8bd36,0x3f7e39bc,0x3df0b772,0x3f7e39bc,0x3df0b772,0x3f7d95f4,0x3e0c4cf7,0x3f7d95f4,0x3e0c4cf7,
0x3f7cd925,0x3e20305b,0x3f7cd925,0x3e20305b,0x3f7b14be,0x3e47c5c2,0x3f7b14be,0x3e47c5c2,0x3f78ed3c,0x3e6f0c4d,0x3f78ed3c,0x3e6f0c4d,0x3f766377,0x3e8afa3e,0x3f766377,0x3e8afa3e,
0x3f78ed3c,0x3e6f0c4d,0x3f78ed3c,0x3e6f0c4d,0x3f74fa0b,0x3e94a031,0x3f74fa0b,0x3e94a031,0x3f702d4f,0x3eb13641,0x3f702d4f,0x3eb13641,0x3f6a8b4b,0x3ecd2ef3,0x3f6a8b4b,0x3ecd2ef3,
0x3f737871,0x3e9e377a,0x3f737871,0x3e9e377a,0x3f6c835e,0x3ec3ef15,0x3f6c835e,0x3ec3ef15,0x3f641901,0x3ee87171,0x3f641901,0x3ee87171,0x3f5a46a0,0x3f05c277,0x3f5a46a0,0x3f05c277,
0x3f6c835e,0x3ec3ef15,0x3f6c835e,0x3ec3ef15,0x3f61c598,0x3ef15aea,0x3f61c598,0x3ef15aea,0x3f54db31,0x3f0e39da,0x3f54db31,0x3f0e39da,0x3f45e403,0x3f226799,0x3f45e403,0x3f226799,
0x3f641901,0x3ee87171,0x3f641901,0x3ee87171,0x3f54db31,0x3f0e39da,0x3f54db31,0x3f0e39da,0x3f42a9f7,0x3f26423a,0x3f42a9f7,0x3f26423a,0x3f2dc5e3,0x3f3bfc8f,0x3f2dc5e3,0x3f3bfc8f,
0x3f5a46a0,0x3f05c277,0x3f5a46a0,0x3f05c277,0x3f45e403,0x3f226799,0x3f45e403,0x3f226799,0x3f2dc5e3,0x3f3bfc8f,0x3f2dc5e3,0x3f3bfc8f,0x3f1260b2,0x3f5205d4,0x3f1260b2,0x3f5205d4,
0x3f800000,0,0x3f42a9f7,0x3f26423a,0x3f800000,0,0x3f26423a,0x3f42a9f7,0x3f800000,0,0x3f05c277,0x3f5a46a0,0x3f800000,0,0x3ec3ef15,0x3f6c835e,
0x3f7f0059,0x3db4b86a,0x3f7f0059,0x3db4b86a,0x3f7e8238,0x3ddcbd0d,0x3f7e8238,0x3ddcbd0d,0x3f7deafa,0x3e0255f4,0x3f7deafa,0x3e0255f4,0x3f7d3aac,0x3e164083,0x3f7d3aac,0x3e164083,
0x3f7c0361,0x3e3403f1,0x3f7c0361,0x3e3403f1,0x3f7a0d54,0x3e5b73dc,0x3f7a0d54,0x3e5b73dc,0x3f77b493,0x3e814693,0x3f77b493,0x3e814693,0x3f74fa0b,0x3e94a031,0x3f74fa0b,0x3e94a031,
0x3f770f11,0x3e862210,0x3f770f11,0x3e862210,0x3f72ae9e,0x3ea2fd52,0x3f72ae9e,0x3ea2fd52,0x3f6d76aa,0x3ebf47d7,0x3f6d76aa,0x3ebf47d7,0x3f676bd8,0x3edae880,0x3f676bd8,0x3edae880,
0x3f702d4f,0x3eb13641,0x3f702d4f,0x3eb13641,0x3f687c12,0x3ed65a92,0x3f687c12,0x3ed65a92,0x3f5f5be6,0x3efa2c90,0x3f5f5be6,0x3efa2c90,0x3f54db31,0x3f0e39da,0x3f54db31,0x3f0e39da,
0x3f676bd8,0x3edae880,0x3f676bd8,0x3edae880,0x3f5b941a,0x3f039c3d,0x3f5b941a,0x3f039c3d,0x3f4d9f02,0x3f187fc0,0x3f4d9f02,0x3f187fc0,0x3f3daef9,0x3f2beb4a,0x3f3daef9,0x3f2beb4a,
0x3f5cdc29,0x3f0172c3,0x3f5cdc29,0x3f0172c3,0x3f4c1d35,0x3f1a82a4,0x3f4c1d35,0x3f1a82a4,0x3f3889dc,0x3f316e2c,0x3f3889dc,0x3f316e2c,0x3f226799,0x3f45e403,0x3f226799,0x3f45e403,
0x3f50935b,0x3f146eba,0x3f50935b,0x3f146eba,0x3f3a4582,0x3f2f9c32,0x3f3a4582,0x3f2f9c32,0x3f207440,0x3f4779bc,0x3f207440,0x3f4779bc,0x3f039c3d,0x3f5b941a,0x3f039c3d,0x3f5b941a,
0x3f800000,0,0x3e9e377a,0x3f737871,0x3f800000,0,0x3e20305b,0x3f7cd925,0x3f800000,0,0,0x3f800000,0x3f800000,0,0xbe20305b,0x3f7cd925,
0x3f7cd925,0x3e20305b,0x3f7cd925,0x3e20305b,0x3f7c0361,0x3e3403f1,0x3f7c0361,0x3e3403f1,0x3f7b14be,0x3e47c5c2,0x3f7b14be,0x3e47c5c2,0x3f7a0d54,0x3e5b73dc,0x3f7a0d54,0x3e5b73dc,
0x3f737871,0x3e9e377a,0x3f737871,0x3e9e377a,0x3f702d4f,0x3eb13641,0x3f702d4f,0x3eb13641,0x3f6c835e,0x3ec3ef15,0x3f6c835e,0x3ec3ef15,0x3f687c12,0x3ed65a92,0x3f687c12,0x3ed65a92,
0x3f641901,0x3ee87171,0x3f641901,0x3ee87171,0x3f5cdc29,0x3f0172c3,0x3f5cdc29,0x3f0172c3,0x3f54db31,0x3f0e39da,0x3f54db31,0x3f0e39da,0x3f4c1d35,0x3f1a82a4,0x3f4c1d35,0x3f1a82a4,
0x3f4f1bbd,0x3f167918,0x3f4f1bbd,0x3f167918,0x3f42a9f7,0x3f26423a,0x3f42a9f7,0x3f26423a,0x3f3504f3,0x3f3504f3,0x3f3504f3,0x3f3504f3,0x3f26423a,0x3f42a9f7,0x3f26423a,0x3f42a9f7,
0x3f3504f3,0x3f3504f3,0x3f3504f3,0x3f3504f3,0x3f226799,0x3f45e403,0x3f226799,0x3f45e403,0x3f0e39da,0x3f54db31,0x3f0e39da,0x3f54db31,0x3ef15aea,0x3f61c598,0x3ef15aea,0x3f61c598,
0x3f167918,0x3f4f1bbd,0x3f167918,0x3f4f1bbd,0x3efa2c90,0x3f5f5be6,0x3efa2c90,0x3f5f5be6,0x3ec3ef15,0x3f6c835e,0x3ec3ef15,0x3f6c835e,0x3e8afa3e,0x3f766377,0x3e8afa3e,0x3f766377,
0x3ee87171,0x3f641901,0x3ee87171,0x3f641901,0x3ea7bf25,0x3f71decf,0x3ea7bf25,0x3f71decf,0x3e47c5c2,0x3f7b14be,0x3e47c5c2,0x3f7b14be,0x3d712283,0x3f7f8e56,0x3d712283,0x3f7f8e56,
0x3f800000,0,0x3e6f0c4d,0x3f78ed3c,0x3f800000,0,0x3da0af2a,0x3f7f35f9,0x3f800000,0,0xbda0af2a,0x3f7f35f9,0x3f800000,0,0xbe6f0c4d,0x3f78ed3c,
0x3f7c7160,0x3e2a1c3f,0x3f7c7160,0x3e2a1c3f,0x3f7b8f2a,0x3e3de731,0x3f7b8f2a,0x3e3de731,0x3f7a9421,0x3e519f65,0x3f7a9421,0x3e519f65,0x3f79805c,0x3e6542e9,0x3f79805c,0x3e6542e9,
0x3f71decf,0x3ea7bf25,0x3f71decf,0x3ea7bf25,0x3f6e641a,0x3eba9be1,0x3f6e641a,0x3eba9be1,0x3f6a8b4b,0x3ecd2ef3,0x3f6a8b4b,0x3ecd2ef3,0x3f6655e7,0x3edf7108,0x3f6655e7,0x3edf7108,
0x3f609384,0x3ef5c6c5,0x3f609384,0x3ef5c6c5,0x3f58f3c4,0x3f07e565,0x3f58f3c4,0x3f07e565,0x3f50935b,0x3f146eba,0x3f50935b,0x3f146eba,0x3f4779bc,0x3f207440,0x3f4779bc,0x3f207440,
0x3f490a88,0x3f1e7cf1,0x3f490a88,0x3f1e7cf1,0x3f3bfc8f,0x3f2dc5e3,0x3f3bfc8f,0x3f2dc5e3,0x3f2dc5e3,0x3f3bfc8f,0x3f2dc5e3,0x3f3bfc8f,0x3f1e7cf1,0x3f490a88,0x3f1e7cf1,0x3f490a88,
0x3f2beb4a,0x3f3daef9,0x3f2beb4a,0x3f3daef9,0x3f187fc0,0x3f4d9f02,0x3f187fc0,0x3f4d9f02,0x3f039c3d,0x3f5b941a,0x3f039c3d,0x3f5b941a,0x3edae880,0x3f676bd8,0x3edae880,0x3f676bd8,
0x3f0a04f8,0x3f579b8c,0x3f0a04f8,0x3f579b8c,0x3edf7108,0x3f6655e7,0x3edf7108,0x3f6655e7,0x3ea7bf25,0x3f71decf,0x3ea7bf25,0x3f71decf,0x3e5b73dc,0x3f7a0d54,0x3e5b73dc,0x3f7a0d54,
0x3ec8917e,0x3f6b8a3d,0x3ec8917e,0x3f6b8a3d,0x3e862210,0x3f770f11,0x3e862210,0x3f770f11,0x3e0255f4,0x3f7deafa,0x3e0255f4,0x3f7deafa,0xbc20d8d2,0x3f7ffcd7,0xbc20d8d2,0x3f7ffcd7,
0x3f800000,0,0xbe9e377a,0x3f737871,0x3f800000,0,0xbee87171,0x3f641901,0x3f800000,0,0xbf167918,0x3f4f1bbd,0x3f800000,0,0xbf3504f3,0x3f3504f3,
0x3f78ed3c,0x3e6f0c4d,0x3f78ed3c,0x3e6f0c4d,0x3f77b493,0x3e814693,0x3f77b493,0x3e814693,0x3f766377,0x3e8afa3e,0x3f766377,0x3e8afa3e,0x3f74fa0b,0x3e94a031,0x3f74fa0b,0x3e94a031,
0x3f641901,0x3ee87171,0x3f641901,0x3ee87171,0x3f5f5be6,0x3efa2c90,0x3f5f5be6,0x3efa2c90,0x3f5a46a0,0x3f05c277,0x3f5a46a0,0x3f05c277,0x3f54db31,0x3f0e39da,0x3f54db31,0x3f0e39da,
0x3f42a9f7,0x3f26423a,0x3f42a9f7,0x3f26423a,0x3f3889dc,0x3f316e2c,0x3f3889dc,0x3f316e2c,0x3f2dc5e3,0x3f3bfc8f,0x3f2dc5e3,0x3f3bfc8f,0x3f226799,0x3f45e403,0x3f226799,0x3f45e403,
0x3f167918,0x3f4f1bbd,0x3f167918,0x3f4f1bbd,0x3f05c277,0x3f5a46a0,0x3f05c277,0x3f5a46a0,0x3ee87171,0x3f641901,0x3ee87171,0x3f641901,0x3ec3ef15,0x3f6c835e,0x3ec3ef15,0x3f6c835e,
0x3ec3ef15,0x3f6c835e,0x3ec3ef15,0x3f6c835e,0x3e94a031,0x3f74fa0b,0x3e94a031,0x3f74fa0b,0x3e47c5c2,0x3f7b14be,0x3e47c5c2,0x3f7b14be,0x3dc8bd36,0x3f7ec46d,0x3dc8bd36,0x3f7ec46d,
0x3e20305b,0x3f7cd925,0x3e20305b,0x3f7cd925,0x3d20cee7,0x3f7fcd79,0x3d20cee7,0x3f7fcd79,0xbda0af2a,0x3f7f35f9,0xbda0af2a,0x3f7f35f9,0xbe47c5c2,0x3f7b14be,0xbe47c5c2,0x3f7b14be,
0xbda0af2a,0x3f7f35f9,0xbda0af2a,0x3f7f35f9,0xbe5b73dc,0x3f7a0d54,0xbe5b73dc,0x3f7a0d54,0xbeb13641,0x3f702d4f,0xbeb13641,0x3f702d4f,0xbef15aea,0x3f61c598,0xbef15aea,0x3f61c598,
0x3f800000,0,0xbec3ef15,0x3f6c835e,0x3f800000,0,0xbf05c277,0x3f5a46a0,0x3f800000,0,0xbf26423a,0x3f42a9f7,0x3f800000,0,0xbf42a9f7,0x3f26423a,
0x3f7853f8,0x3e78cfcc,0x3f7853f8,0x3e78cfcc,0x3f770f11,0x3e862210,0x3f770f11,0x3e862210,0x3f75b1c9,0x3e8fcefe,0x3f75b1c9,0x3e8fcefe,0x3f743c41,0x3e996dba,0x3f743c41,0x3e996dba,
0x3f61c598,0x3ef15aea,0x3f61c598,0x3ef15aea,0x3f5cdc29,0x3f0172c3,0x3f5cdc29,0x3f0172c3,0x3f579b8c,0x3f0a04f8,0x3f579b8c,0x3f0a04f8,0x3f5205d4,0x3f1260b2,0x3f5205d4,0x3f1260b2,
0x3f3daef9,0x3f2beb4a,0x3f3daef9,0x3f2beb4a,0x3f333bc6,0x3f36c9a9,0x3f333bc6,0x3f36c9a9,0x3f28296a,0x3f4105b8,0x3f28296a,0x3f4105b8,0x3f1c81b9,0x3f4a965e,0x3f1c81b9,0x3f4a965e,
0x3f0e39da,0x3f54db31,0x3f0e39da,0x3f54db31,0x3efa2c90,0x3f5f5be6,0x3efa2c90,0x3f5f5be6,0x3ed65a92,0x3f687c12,0x3ed65a92,0x3f687c12,0x3eb13641,0x3f702d4f,0x3eb13641,0x3f702d4f,
0x3eac7cd4,0x3f710908,0x3eac7cd4,0x3f710908,0x3e78cfcc,0x3f7853f8,0x3e78cfcc,0x3f7853f8,0x3e164083,0x3f7d3aac,0x3e164083,0x3f7d3aac,0x3d48fb30,0x3f7fb10f,0x3d48fb30,0x3f7fb10f,
0x3dc8bd36,0x3f7ec46d,0x3dc8bd36,0x3f7ec46d,0xbca0d6d6,0x3f7ff35e,0xbca0d6d6,0x3f7ff35e,0xbe0c4cf7,0x3f7d95f4,0xbe0c4cf7,0x3f7d95f4,0xbe814693,0x3f77b493,0xbe814693,0x3f77b493,
0xbe164083,0x3f7d3aac,0xbe164083,0x3f7d3aac,0xbe8fcefe,0x3f75b1c9,0xbe8fcefe,0x3f75b1c9,0xbed1c759,0x3f698690,0xbed1c759,0x3f698690,0xbf07e565,0x3f58f3c4,0xbf07e565,0x3f58f3c4,
0x3f800000,0,0xbf4f1bbd,0x3f167918,0x3f800000,0,0xbf641901,0x3ee87171,0x3f800000,0,0xbf737871,0x3e9e377a,0x3f800000,0,0xbf7cd925,0x3e20305b,
0x3f737871,0x3e9e377a,0x3f737871,0x3e9e377a,0x3f71decf,0x3ea7bf25,0x3f71decf,0x3ea7bf25,0x3f702d4f,0x3eb13641,0x3f702d4f,0x3eb13641,0x3f6e641a,0x3eba9be1,0x3f6e641a,0x3eba9be1,
0x3f4f1bbd,0x3f167918,0x3f4f1bbd,0x3f167918,0x3f490a88,0x3f1e7cf1,0x3f490a88,0x3f1e7cf1,0x3f42a9f7,0x3f26423a,0x3f42a9f7,0x3f26423a,0x3f3bfc8f,0x3f2dc5e3,0x3f3bfc8f,0x3f2dc5e3,
0x3f167918,0x3f4f1bbd,0x3f167918,0x3f4f1bbd,0x3f0a04f8,0x3f579b8c,0x3f0a04f8,0x3f579b8c,0x3efa2c90,0x3f5f5be6,0x3efa2c90,0x3f5f5be6,0x3edf7108,0x3f6655e7,0x3edf7108,0x3f6655e7,
0x3e9e377a,0x3f737871,0x3e9e377a,0x3f737871,0x3e6f0c4d,0x3f78ed3c,0x3e6f0c4d,0x3f78ed3c,0x3e20305b,0x3f7cd925,0x3e20305b,0x3f7cd925,0x3da0af2a,0x3f7f35f9,0x3da0af2a,0x3f7f35f9,
0,0x3f800000,0,0x3f800000,0xbdc8bd36,0x3f7ec46d,0xbdc8bd36,0x3f7ec46d,0xbe47c5c2,0x3f7b14be,0xbe47c5c2,0x3f7b14be,0xbe94a031,0x3f74fa0b,0xbe94a031,0x3f74fa0b,
0xbe9e377a,0x3f737871,0xbe9e377a,0x3f737871,0xbed65a92,0x3f687c12,0xbed65a92,0x3f687c12,0xbf05c277,0x3f5a46a0,0xbf05c277,0x3f5a46a0,0xbf1e7cf1,0x3f490a88,0xbf1e7cf1,0x3f490a88,
0xbf167918,0x3f4f1bbd,0xbf167918,0x3f4f1bbd,0xbf316e2c,0x3f3889dc,0xbf316e2c,0x3f3889dc,0xbf490a88,0x3f1e7cf1,0xbf490a88,0x3f1e7cf1,0xbf5cdc29,0x3f0172c3,0xbf5cdc29,0x3f0172c3,
0x3f800000,0,0xbf5a46a0,0x3f05c277,0x3f800000,0,0xbf6c835e,0x3ec3ef15,0x3f800000,0,0xbf78ed3c,0x3e6f0c4d,0x3f800000,0,0xbf7f35f9,0x3da0af2a,
0x3f72ae9e,0x3ea2fd52,0x3f72ae9e,0x3ea2fd52,0x3f710908,0x3eac7cd4,0x3f710908,0x3eac7cd4,0x3f6f4ba8,0x3eb5eb4f,0x3f6f4ba8,0x3eb5eb4f,0x3f6d76aa,0x3ebf47d7,0x3f6d76aa,0x3ebf47d7,
0x3f4c1d35,0x3f1a82a4,0x3f4c1d35,0x3f1a82a4,0x3f45e403,0x3f226799,0x3f45e403,0x3f226799,0x3f3f5cb5,0x3f2a0c73,0x3f3f5cb5,0x3f2a0c73,0x3f3889dc,0x3f316e2c,0x3f3889dc,0x3f316e2c,
0x3f104f0e,0x3f53731f,0x3f104f0e,0x3f53731f,0x3f039c3d,0x3f5b941a,0x3f039c3d,0x3f5b941a,0x3eece91a,0x3f62f219,0x3eece91a,0x3f62f219,0x3ed1c759,0x3f698690,0x3ed1c759,0x3f698690,
0x3e8afa3e,0x3f766377,0x3e8afa3e,0x3f766377,0x3e47c5c2,0x3f7b14be,0x3e47c5c2,0x3f7b14be,0x3df0b772,0x3f7e39bc,0x3df0b772,0x3f7e39bc,0x3d20cee7,0x3f7fcd79,0x3d20cee7,0x3f7fcd79,
0xbd48fb30,0x3f7fb10f,0xbd48fb30,0x3f7fb10f,0xbe164083,0x3f7d3aac,0xbe164083,0x3f7d3aac,0xbe78cfcc,0x3f7853f8,0xbe78cfcc,0x3f7853f8,0xbeac7cd4,0x3f710908,0xbeac7cd4,0x3f710908,
0xbeba9be1,0x3f6e641a,0xbeba9be1,0x3f6e641a,0xbef15aea,0x3f61c598,0xbef15aea,0x3f61c598,0xbf1260b2,0x3f5205d4,0xbf1260b2,0x3f5205d4,0xbf2a0c73,0x3f3f5cb5,0xbf2a0c73,0x3f3f5cb5,
0xbf2456f1,0x3f444969,0xbf2456f1,0x3f444969,0xbf3daef9,0x3f2beb4a,0xbf3daef9,0x3f2beb4a,0xbf53731f,0x3f104f0e,0xbf53731f,0x3f104f0e,0xbf653a48,0x3ee3f40d,0xbf653a48,0x3ee3f40d,
0x3f803f00,0x3f6d3f00,0x3f00,0xbec4bf00,0x3f803f80,0x3ec43f35,0,0xbf6dbf35,0x3f803f80,0xbec40000,0,0xbf6dbf80,0x3f803f80,0xbf6dbf35,0,0xbec4bf35,
0x3f353f00,0x3ec43f00,0xbf353f00,0xbf6dbf00,0xbf350000,0xbf6dbf35,0xbf35bf80,0x3ec4bf35,0xbf35bf80,0x3f6d0000,0x3f350000,0x3ec43f80,0x3f350000,0xbec43f35,0x3f353f80,0xbf6dbf35,
0x3f00,0xbec43f00,0xbf803f00,0xbf6dbf00,0xbf80,0x3f6dbf35,0x3f800000,0x3ec43f35,0x3f80,0xbf6d0000,0xbf800000,0x3ec4bf80,0xbf80,0x3ec43f35,0x3f800000,0xbf6d3f35,
0xbf353f00,0xbf6d3f00,0xbf353f00,0xbec4bf00,0x3f350000,0xbec43f35,0xbf353f80,0xbf6d3f35,0x3f35bf80,0x3ec40000,0x3f350000,0xbf6d3f80,0xbf350000,0x3f6dbf35,0x3f35bf80,0xbec43f35,
0xbf803f00,0xbf6d3f00,0x3f00,0x3ec4bf00,0xbf803f80,0xbec43f35,0,0x3f6dbf35,0xbf803f80,0x3ec40000,0,0x3f6dbf80,0xbf803f80,0x3f6dbf35,0,0x3ec4bf35,
0xbf353f00,0xbec43f00,0x3f353f00,0x3f6dbf00,0x3f350000,0x3f6dbf35,0x3f35bf80,0xbec4bf35,0x3f35bf80,0xbf6d0000,0xbf350000,0xbec43f80,0xbf350000,0x3ec43f35,0xbf353f80,0x3f6dbf35,
0x3f00,0x3ec43f00,0x3f803f00,0x3f6dbf00,0xbf80,0xbf6dbf35,0xbf800000,0xbec43f35,0x3f80,0x3f6d0000,0x3f800000,0xbec4bf80,0xbf80,0xbec43f35,0xbf800000,0x3f6d3f35,
0x3f353f00,0x3f6d3f00,0x3f353f00,0x3ec4bf00,0xbf350000,0x3ec43f35,0x3f353f80,0x3f6d3f35,0xbf35bf80,0xbec40000,0xbf350000,0x3f6d3f80,0x3f350000,0xbf6dbf35,0xbf35bf80,0x3ec43f35,
0x3f80,0x3f800000,0x3f80,0x3f800000,0x3f80,0x3f800000,0x3f80,0x3f800000,0x3f80,0x3f800000,0x3f80,0x3f800000,0x3f80,0x3f800000,0x3f80,0x3f800000,
0x3f80,0x3f800000,0xbf800000,0x3f80,0xbec43f6d,0x3f6d3ec4,0xbf6dbec4,0xbec43f6d,0xbf353f35,0x3f353f35,0xbf35bf35,0xbf353f35,0xbf6d3ec4,0x3ec43f6d,0xbec4bf6d,0xbf6d3ec4,
0x3f80,0x3f800000,0xbf80,0xbf800000,0xbf353f35,0x3f353f35,0x3f35bf35,0xbf35bf35,0xbf800000,0x3f80,0x3f800000,0xbf80,0xbf35bf35,0xbf353f35,0x3f353f35,0x3f35bf35,
0x3f80,0x3f800000,0x3f800000,0xbf80,0xbf6d3ec4,0x3ec43f6d,0x3ec43f6d,0x3f6dbec4,0xbf35bf35,0xbf353f35,0xbf353f35,0x3f353f35,0x3ec4bf6d,0xbf6dbec4,0xbf6dbec4,0xbec43f6d,
0x3f80,0x3f800000,0x3f80,0x3f800000,0xbf800000,0x3f80,0xbf800000,0x3f80,0xbf80,0xbf800000,0xbf80,0xbf800000,0x3f800000,0xbf80,0x3f800000,0xbf80,
0x3f80,0x3f800000,0xbf800000,0x3f80,0xbf6dbec4,0xbec43f6d,0x3ec4bf6d,0xbf6dbec4,0x3f35bf35,0xbf35bf35,0x3f353f35,0x3f35bf35,0x3ec43f6d,0x3f6dbec4,0xbf6d3ec4,0x3ec43f6d,
0x3f80,0x3f800000,0xbf80,0xbf800000,0xbf35bf35,0xbf353f35,0x3f353f35,0x3f35bf35,0x3f800000,0xbf80,0xbf800000,0x3f80,0xbf353f35,0x3f353f35,0x3f35bf35,0xbf35bf35,
0x3f80,0x3f800000,0x3f800000,0xbf80,0xbec4bf6d,0xbf6d3ec4,0xbf6d3ec4,0x3ec43f6d,0x3f353f35,0x3f35bf35,0x3f35bf35,0xbf35bf35,0xbf6dbec4,0xbec43f6d,0xbec43f6d,0x3f6d3ec4,
0x3f80,0x3f800000,0x3f80,0x3f800000,0x3f80,0x3f800000,0x3f80,0x3f800000,0x3f80,0x3f800000,0x3f80,0x3f800000,0x3f80,0x3f800000,0x3f80,0x3f800000,
0xbf80,0xbf800000,0x3f800000,0xbf80,0x3ec4bf6d,0xbf6dbec4,0x3f6d3ec4,0x3ec4bf6d,0x3f35bf35,0xbf35bf35,0x3f353f35,0x3f35bf35,0x3f6dbec4,0xbec4bf6d,0x3ec43f6d,0x3f6dbec4,
0x3f80,0x3f800000,0xbf80,0xbf800000,0xbf353f35,0x3f353f35,0x3f35bf35,0xbf35bf35,0xbf800000,0x3f80,0x3f800000,0xbf80,0xbf35bf35,0xbf353f35,0x3f353f35,0x3f35bf35,
0xbf80,0xbf800000,0xbf800000,0x3f80,0x3f6dbec4,0xbec4bf6d,0xbec4bf6d,0xbf6d3ec4,0x3f353f35,0x3f35bf35,0x3f35bf35,0xbf35bf35,0xbec43f6d,0x3f6d3ec4,0x3f6d3ec4,0x3ec4bf6d,
0x3f80,0x3f800000,0x3f80,0x3f800000,0xbf800000,0x3f80,0xbf800000,0x3f80,0xbf80,0xbf800000,0xbf80,0xbf800000,0x3f800000,0xbf80,0x3f800000,0xbf80,
0xbf80,0xbf800000,0x3f800000,0xbf80,0x3f6d3ec4,0x3ec4bf6d,0xbec43f6d,0x3f6d3ec4,0xbf353f35,0x3f353f35,0xbf35bf35,0xbf353f35,0xbec4bf6d,0xbf6d3ec4,0x3f6dbec4,0xbec4bf6d,
0x3f80,0x3f800000,0xbf80,0xbf800000,0xbf35bf35,0xbf353f35,0x3f353f35,0x3f35bf35,0x3f800000,0xbf80,0xbf800000,0x3f80,0xbf353f35,0x3f353f35,0x3f35bf35,0xbf35bf35,
0xbf80,0xbf800000,0xbf800000,0x3f80,0x3ec43f6d,0x3f6dbec4,0x3f6dbec4,0xbec4bf6d,0xbf35bf35,0xbf353f35,0xbf353f35,0x3f353f35,0x3f6d3ec4,0x3ec4bf6d,0x3ec4bf6d,0xbf6dbec4,
0x3f80,0x3f800000,0x3f80,0x3f800000,0xbf80,0xbf800000,0xbf80,0xbf800000,0x3f80,0x3f800000,0x3f80,0x3f800000,0xbf80,0xbf800000,0xbf80,0xbf800000,
0x3f80,0x3f800000,0xbf800000,0x3f80,0x3ec4bf6d,0xbf6dbec4,0x3f6d3ec4,0x3ec4bf6d,0xbf353f35,0x3f353f35,0xbf35bf35,0xbf353f35,0x3f6dbec4,0xbec4bf6d,0x3ec43f6d,0x3f6dbec4,
0x3f80,0x3f800000,0xbf80,0xbf800000,0x3f35bf35,0xbf35bf35,0xbf353f35,0x3f353f35,0xbf800000,0x3f80,0x3f800000,0xbf80,0x3f353f35,0x3f35bf35,0xbf35bf35,0xbf353f35,
0x3f80,0x3f800000,0x3f800000,0xbf80,0x3f6dbec4,0xbec4bf6d,0xbec4bf6d,0xbf6d3ec4,0xbf35bf35,0xbf353f35,0xbf353f35,0x3f353f35,0xbec43f6d,0x3f6d3ec4,0x3f6d3ec4,0x3ec4bf6d,
0x3f80,0x3f800000,0x3f80,0x3f800000,0x3f800000,0xbf80,0x3f800000,0xbf80,0xbf80,0xbf800000,0xbf80,0xbf800000,0xbf800000,0x3f80,0xbf800000,0x3f80,
0x3f80,0x3f800000,0xbf800000,0x3f80,0x3f6d3ec4,0x3ec4bf6d,0xbec43f6d,0x3f6d3ec4,0x3f35bf35,0xbf35bf35,0x3f353f35,0x3f35bf35,0xbec4bf6d,0xbf6d3ec4,0x3f6dbec4,0xbec4bf6d,
0x3f80,0x3f800000,0xbf80,0xbf800000,0x3f353f35,0x3f35bf35,0xbf35bf35,0xbf353f35,0x3f800000,0xbf80,0xbf800000,0x3f80,0x3f35bf35,0xbf35bf35,0xbf353f35,0x3f353f35,
0x3f80,0x3f800000,0x3f800000,0xbf80,0x3ec43f6d,0x3f6dbec4,0x3f6dbec4,0xbec4bf6d,0x3f353f35,0x3f35bf35,0x3f35bf35,0xbf35bf35,0x3f6d3ec4,0x3ec4bf6d,0x3ec4bf6d,0xbf6dbec4,
0x3f80,0x3f800000,0x3f80,0x3f800000,0xbf80,0xbf800000,0xbf80,0xbf800000,0x3f80,0x3f800000,0x3f80,0x3f800000,0xbf80,0xbf800000,0xbf80,0xbf800000,
0xbf80,0xbf800000,0x3f800000,0xbf80,0xbec43f6d,0x3f6d3ec4,0xbf6dbec4,0xbec43f6d,0x3f35bf35,0xbf35bf35,0x3f353f35,0x3f35bf35,0xbf6d3ec4,0x3ec43f6d,0xbec4bf6d,0xbf6d3ec4,
0x3f80,0x3f800000,0xbf80,0xbf800000,0x3f35bf35,0xbf35bf35,0xbf353f35,0x3f353f35,0xbf800000,0x3f80,0x3f800000,0xbf80,0x3f353f35,0x3f35bf35,0xbf35bf35,0xbf353f35,
0xbf80,0xbf800000,0xbf800000,0x3f80,0xbf6d3ec4,0x3ec43f6d,0x3ec43f6d,0x3f6dbec4,0x3f353f35,0x3f35bf35,0x3f35bf35,0xbf35bf35,0x3ec4bf6d,0xbf6dbec4,0xbf6dbec4,0xbec43f6d,
0x3f80,0x3f800000,0x3f80,0x3f800000,0x3f800000,0xbf80,0x3f800000,0xbf80,0xbf80,0xbf800000,0xbf80,0xbf800000,0xbf800000,0x3f80,0xbf800000,0x3f80,
0xbf80,0xbf800000,0x3f800000,0xbf80,0xbf6dbec4,0xbec43f6d,0x3ec4bf6d,0xbf6dbec4,0xbf353f35,0x3f353f35,0xbf35bf35,0xbf353f35,0x3ec43f6d,0x3f6dbec4,0xbf6d3ec4,0x3ec43f6d,
0x3f80,0x3f800000,0xbf80,0xbf800000,0x3f353f35,0x3f35bf35,0xbf35bf35,0xbf353f35,0x3f800000,0xbf80,0xbf800000,0x3f80,0x3f35bf35,0xbf35bf35,0xbf353f35,0x3f353f35,
0xbf80,0xbf800000,0xbf800000,0x3f80,0xbec4bf6d,0xbf6d3ec4,0xbf6d3ec4,0x3ec43f6d,0xbf35bf35,0xbf353f35,0xbf353f35,0x3f353f35,0xbf6dbec4,0xbec43f6d,0xbec43f6d,0x3f6d3ec4,
0x3f803f80,0xbf803f80,0x3f803f80,0xbf803f80,0x3f803f80,0xbf803f80,0x3f803f80,0xbf803f80,0x3f803f80,0xbf803f80,0x3f803f80,0xbf803f80,0x3f803f80,0xbf803f80,0x3f803f80,0xbf803f80,
0x3f6d3f80,0xbec40000,0xbf6dbf80,0x3ec40000,0x3ec43f35,0xbf6dbf35,0xbec4bf35,0x3f6d3f35,0xbec40000,0xbf6dbf80,0x3ec40000,0x3f6d3f80,0xbf6dbf35,0xbec4bf35,0x3f6d3f35,0x3ec43f35,
0x3f353f80,0xbf350000,0x3f353f80,0xbf350000,0xbf350000,0xbf35bf80,0xbf350000,0xbf35bf80,0xbf35bf80,0x3f350000,0xbf35bf80,0x3f350000,0x3f350000,0x3f353f80,0x3f350000,0x3f353f80,
0x3ec43f80,0xbf6d0000,0xbec4bf80,0x3f6d0000,0xbf6dbf35,0x3ec4bf35,0x3f6d3f35,0xbec43f35,0x3f6d0000,0x3ec43f80,0xbf6d0000,0xbec4bf80,0xbec43f35,0xbf6dbf35,0x3ec4bf35,0x3f6d3f35,
0x3f80,0xbf800000,0x3f80,0xbf800000,0xbf80,0x3f800000,0xbf80,0x3f800000,0x3f80,0xbf800000,0x3f80,0xbf800000,0xbf80,0x3f800000,0xbf80,0x3f800000,
0xbec43f80,0xbf6d0000,0x3ec4bf80,0x3f6d0000,0x3f6dbf35,0x3ec43f35,0xbf6d3f35,0xbec4bf35,0xbf6d0000,0x3ec4bf80,0x3f6d0000,0xbec43f80,0x3ec43f35,0xbf6d3f35,0xbec4bf35,0x3f6dbf35,
0xbf353f80,0xbf350000,0xbf353f80,0xbf350000,0x3f350000,0xbf353f80,0x3f350000,0xbf353f80,0x3f35bf80,0x3f350000,0x3f35bf80,0x3f350000,0xbf350000,0x3f35bf80,0xbf350000,0x3f35bf80,
0xbf6d3f80,0xbec40000,0x3f6dbf80,0x3ec40000,0xbec43f35,0xbf6d3f35,0x3ec4bf35,0x3f6dbf35,0x3ec40000,0xbf6d3f80,0xbec40000,0x3f6dbf80,0x3f6dbf35,0xbec43f35,0xbf6d3f35,0x3ec4bf35,
0x3f803f80,0,0x3f803f80,0,0x3f803f80,0,0x3f803f80,0,0x3f803f80,0,0x3f803f80,0,0x3f803f80,0,0x3f803f80,0,
0x3f6d3f80,0xbec40000,0xbf6dbf80,0x3ec40000,0x3ec43f35,0xbf6dbf35,0xbec4bf35,0x3f6d3f35,0xbec40000,0xbf6dbf80,0x3ec40000,0x3f6d3f80,0xbf6dbf35,0xbec4bf35,0x3f6d3f35,0x3ec43f35,
0x3f353f80,0xbf350000,0x3f353f80,0xbf350000,0xbf350000,0xbf35bf80,0xbf350000,0xbf35bf80,0xbf35bf80,0x3f350000,0xbf35bf80,0x3f350000,0x3f350000,0x3f353f80,0x3f350000,0x3f353f80,
0x3ec43f80,0xbf6d0000,0xbec4bf80,0x3f6d0000,0xbf6dbf35,0x3ec4bf35,0x3f6d3f35,0xbec43f35,0x3f6d0000,0x3ec43f80,0xbf6d0000,0xbec4bf80,0xbec43f35,0xbf6dbf35,0x3ec4bf35,0x3f6d3f35,
0x3f80,0xbf800000,0x3f80,0xbf800000,0xbf80,0x3f800000,0xbf80,0x3f800000,0x3f80,0xbf800000,0x3f80,0xbf800000,0xbf80,0x3f800000,0xbf80,0x3f800000,
0xbec43f80,0xbf6d0000,0x3ec4bf80,0x3f6d0000,0x3f6dbf35,0x3ec43f35,0xbf6d3f35,0xbec4bf35,0xbf6d0000,0x3ec4bf80,0x3f6d0000,0xbec43f80,0x3ec43f35,0xbf6d3f35,0xbec4bf35,0x3f6dbf35,
0xbf353f80,0xbf350000,0xbf353f80,0xbf350000,0x3f350000,0xbf353f80,0x3f350000,0xbf353f80,0x3f35bf80,0x3f350000,0x3f35bf80,0x3f350000,0xbf350000,0x3f35bf80,0xbf350000,0x3f35bf80,
0xbf6d3f80,0xbec40000,0x3f6dbf80,0x3ec40000,0xbec43f35,0xbf6d3f35,0x3ec4bf35,0x3f6dbf35,0x3ec40000,0xbf6d3f80,0xbec40000,0x3f6dbf80,0x3f6dbf35,0xbec43f35,0xbf6d3f35,0x3ec4bf35,
0,0x3f803f80,0,0x3f803f80,0,0x3f803f80,0,0x3f803f80,0,0x3f803f80,0,0x3f803f80,0,0x3f803f80,0,0x3f803f80,
0x3ec40000,0x3f6d3f80,0xbec40000,0xbf6dbf80,0x3f6d3f35,0x3ec43f35,0xbf6dbf35,0xbec4bf35,0x3f6d3f80,0xbec40000,0xbf6dbf80,0x3ec40000,0x3ec43f35,0xbf6dbf35,0xbec4bf35,0x3f6d3f35,
0x3f350000,0x3f353f80,0x3f350000,0x3f353f80,0x3f353f80,0xbf350000,0x3f353f80,0xbf350000,0xbf350000,0xbf35bf80,0xbf350000,0xbf35bf80,0xbf35bf80,0x3f350000,0xbf35bf80,0x3f350000,
0x3f6d0000,0x3ec43f80,0xbf6d0000,0xbec4bf80,0xbec43f35,0xbf6dbf35,0x3ec4bf35,0x3f6d3f35,0xbec4bf80,0x3f6d0000,0x3ec43f80,0xbf6d0000,0x3f6d3f35,0xbec43f35,0xbf6dbf35,0x3ec4bf35,
0x3f800000,0x3f80,0x3f800000,0x3f80,0xbf800000,0xbf80,0xbf800000,0xbf80,0x3f800000,0x3f80,0x3f800000,0x3f80,0xbf800000,0xbf80,0xbf800000,0xbf80,
0x3f6d0000,0xbec43f80,0xbf6d0000,0x3ec4bf80,0xbec4bf35,0x3f6dbf35,0x3ec43f35,0xbf6d3f35,0xbec43f80,0xbf6d0000,0x3ec4bf80,0x3f6d0000,0x3f6dbf35,0x3ec43f35,0xbf6d3f35,0xbec4bf35,
0x3f350000,0xbf353f80,0x3f350000,0xbf353f80,0x3f35bf80,0x3f350000,0x3f35bf80,0x3f350000,0xbf350000,0x3f35bf80,0xbf350000,0x3f35bf80,0xbf353f80,0xbf350000,0xbf353f80,0xbf350000,
0x3ec40000,0xbf6d3f80,0xbec40000,0x3f6dbf80,0x3f6dbf35,0xbec43f35,0xbf6d3f35,0x3ec4bf35,0x3f6dbf80,0x3ec40000,0xbf6d3f80,0xbec40000,0x3ec4bf35,0x3f6dbf35,0xbec43f35,0xbf6d3f35,
0xbf803f80,0,0xbf803f80,0,0xbf803f80,0,0xbf803f80,0,0xbf803f80,0,0xbf803f80,0,0xbf803f80,0,0xbf803f80,0,
0x3f6d3f80,0xbec40000,0xbf6dbf80,0x3ec40000,0x3ec43f35,0xbf6dbf35,0xbec4bf35,0x3f6d3f35,0xbec40000,0xbf6dbf80,0x3ec40000,0x3f6d3f80,0xbf6dbf35,0xbec4bf35,0x3f6d3f35,0x3ec43f35,
0x3f353f80,0xbf350000,0x3f353f80,0xbf350000,0xbf350000,0xbf35bf80,0xbf350000,0xbf35bf80,0xbf35bf80,0x3f350000,0xbf35bf80,0x3f350000,0x3f350000,0x3f353f80,0x3f350000,0x3f353f80,
0x3ec43f80,0xbf6d0000,0xbec4bf80,0x3f6d0000,0xbf6dbf35,0x3ec4bf35,0x3f6d3f35,0xbec43f35,0x3f6d0000,0x3ec43f80,0xbf6d0000,0xbec4bf80,0xbec43f35,0xbf6dbf35,0x3ec4bf35,0x3f6d3f35,
0x3f80,0xbf800000,0x3f80,0xbf800000,0xbf80,0x3f800000,0xbf80,0x3f800000,0x3f80,0xbf800000,0x3f80,0xbf800000,0xbf80,0x3f800000,0xbf80,0x3f800000,
0xbec43f80,0xbf6d0000,0x3ec4bf80,0x3f6d0000,0x3f6dbf35,0x3ec43f35,0xbf6d3f35,0xbec4bf35,0xbf6d0000,0x3ec4bf80,0x3f6d0000,0xbec43f80,0x3ec43f35,0xbf6d3f35,0xbec4bf35,0x3f6dbf35,
0xbf353f80,0xbf350000,0xbf353f80,0xbf350000,0x3f350000,0xbf353f80,0x3f350000,0xbf353f80,0x3f35bf80,0x3f350000,0x3f35bf80,0x3f350000,0xbf350000,0x3f35bf80,0xbf350000,0x3f35bf80,
0xbf6d3f80,0xbec40000,0x3f6dbf80,0x3ec40000,0xbec43f35,0xbf6d3f35,0x3ec4bf35,0x3f6dbf35,0x3ec40000,0xbf6d3f80,0xbec40000,0x3f6dbf80,0x3f6dbf35,0xbec43f35,0xbf6d3f35,0x3ec4bf35,
0,0xbf803f80,0,0xbf803f80,0,0xbf803f80,0,0xbf803f80,0,0xbf803f80,0,0xbf803f80,0,0xbf803f80,0,0xbf803f80,
0xbec40000,0xbf6dbf80,0x3ec40000,0x3f6d3f80,0xbf6dbf35,0xbec4bf35,0x3f6d3f35,0x3ec43f35,0xbf6dbf80,0x3ec40000,0x3f6d3f80,0xbec40000,0xbec4bf35,0x3f6d3f35,0x3ec43f35,0xbf6dbf35,
0xbf350000,0xbf35bf80,0xbf350000,0xbf35bf80,0xbf35bf80,0x3f350000,0xbf35bf80,0x3f350000,0x3f350000,0x3f353f80,0x3f350000,0x3f353f80,0x3f353f80,0xbf350000,0x3f353f80,0xbf350000,
0xbf6d0000,0xbec4bf80,0x3f6d0000,0x3ec43f80,0x3ec4bf35,0x3f6d3f35,0xbec43f35,0xbf6dbf35,0x3ec43f80,0xbf6d0000,0xbec4bf80,0x3f6d0000,0xbf6dbf35,0x3ec4bf35,0x3f6d3f35,0xbec43f35,
0xbf800000,0xbf80,0xbf800000,0xbf80,0x3f800000,0x3f80,0x3f800000,0x3f80,0xbf800000,0xbf80,0xbf800000,0xbf80,0x3f800000,0x3f80,0x3f800000,0x3f80,
0xbf6d0000,0x3ec4bf80,0x3f6d0000,0xbec43f80,0x3ec43f35,0xbf6d3f35,0xbec4bf35,0x3f6dbf35,0x3ec4bf80,0x3f6d0000,0xbec43f80,0xbf6d0000,0xbf6d3f35,0xbec4bf35,0x3f6dbf35,0x3ec43f35,
0xbf350000,0x3f35bf80,0xbf350000,0x3f35bf80,0xbf353f80,0xbf350000,0xbf353f80,0xbf350000,0x3f350000,0xbf353f80,0x3f350000,0xbf353f80,0x3f35bf80,0x3f350000,0x3f35bf80,0x3f350000,
0xbec40000,0x3f6dbf80,0x3ec40000,0xbf6d3f80,0xbf6d3f35,0x3ec4bf35,0x3f6dbf35,0xbec43f35,0xbf6d3f80,0xbec40000,0x3f6dbf80,0x3ec40000,0xbec43f35,0xbf6d3f35,0x3ec4bf35,0x3f6dbf35,
0x3f003f00,0,0x3f003f00,0,0x3f003f00,0,0x3f003f00,0,0x3f003f00,0,0x3f003f00,0,0x3f003f00,0,0x3f003f00,0,
0x3f6d3f80,0xbec40000,0xbf6dbf80,0x3ec40000,0x3ec43f35,0xbf6dbf35,0xbec4bf35,0x3f6d3f35,0xbec40000,0xbf6dbf80,0x3ec40000,0x3f6d3f80,0xbf6dbf35,0xbec4bf35,0x3f6d3f35,0x3ec43f35,
0x3f353f80,0xbf350000,0x3f353f80,0xbf350000,0xbf350000,0xbf35bf80,0xbf350000,0xbf35bf80,0xbf35bf80,0x3f350000,0xbf35bf80,0x3f350000,0x3f350000,0x3f353f80,0x3f350000,0x3f353f80,
0x3ec43f80,0xbf6d0000,0xbec4bf80,0x3f6d0000,0xbf6dbf35,0x3ec4bf35,0x3f6d3f35,0xbec43f35,0x3f6d0000,0x3ec43f80,0xbf6d0000,0xbec4bf80,0xbec43f35,0xbf6dbf35,0x3ec4bf35,0x3f6d3f35,
0x3f80,0xbf800000,0x3f80,0xbf800000,0xbf80,0x3f800000,0xbf80,0x3f800000,0x3f80,0xbf800000,0x3f80,0xbf800000,0xbf80,0x3f800000,0xbf80,0x3f800000,
0xbec43f80,0xbf6d0000,0x3ec4bf80,0x3f6d0000,0x3f6dbf35,0x3ec43f35,0xbf6d3f35,0xbec4bf35,0xbf6d0000,0x3ec4bf80,0x3f6d0000,0xbec43f80,0x3ec43f35,0xbf6d3f35,0xbec4bf35,0x3f6dbf35,
0xbf353f80,0xbf350000,0xbf353f80,0xbf350000,0x3f350000,0xbf353f80,0x3f350000,0xbf353f80,0x3f35bf80,0x3f350000,0x3f35bf80,0x3f350000,0xbf350000,0x3f35bf80,0xbf350000,0x3f35bf80,
0xbf6d3f80,0xbec40000,0x3f6dbf80,0x3ec40000,0xbec43f35,0xbf6d3f35,0x3ec4bf35,0x3f6dbf35,0x3ec40000,0xbf6d3f80,0xbec40000,0x3f6dbf80,0x3f6dbf35,0xbec43f35,0xbf6d3f35,0x3ec4bf35,
0,0x3f003f00,0,0x3f003f00,0,0x3f003f00,0,0x3f003f00,0,0x3f003f00,0,0x3f003f00,0,0x3f003f00,0,0x3f003f00,
0,0,0,0,0,0,0,0,0,0,0,0,0,0,0,0,
0,0,0,0,0,0,0,0,0,0,0,0,0,0,0,0,
0,0,0,0,0,0,0,0,0,0,0,0,0,0,0,0,
0,0,0,0,0,0,0,0,0,0,0,0,0,0,0,0,
0,0,0,0,0,0,0,0,0,0,0,0,0,0,0,0,
0,0,0,0,0,0,0,0,0,0,0,0,0,0,0,0,
0,0,0,0,0,0,0,0,0,0,0,0,0,0,0,0,
0xbf003f00,0,0xbf003f00,0,0xbf003f00,0,0xbf003f00,0,0xbf003f00,0,0xbf003f00,0,0xbf003f00,0,0xbf003f00,0,
0,0,0,0,0,0,0,0,0,0,0,0,0,0,0,0,
0,0,0,0,0,0,0,0,0,0,0,0,0,0,0,0,
0,0,0,0,0,0,0,0,0,0,0,0,0,0,0,0,
0,0,0,0,0,0,0,0,0,0,0,0,0,0,0,0,
0,0,0,0,0,0,0,0,0,0,0,0,0,0,0,0,
0,0,0,0,0,0,0,0,0,0,0,0,0,0,0,0,
0,0,0,0,0,0,0,0,0,0,0,0,0,0,0,0,
0,0xbf003f00,0,0xbf003f00,0,0xbf003f00,0,0xbf003f00,0,0xbf003f00,0,0xbf003f00,0,0xbf003f00,0,0xbf003f00,
0x3f6d3f80,0xbec40000,0xbf6dbf80,0x3ec40000,0x3ec43f35,0xbf6dbf35,0xbec4bf35,0x3f6d3f35,0xbec40000,0xbf6dbf80,0x3ec40000,0x3f6d3f80,0xbf6dbf35,0xbec4bf35,0x3f6d3f35,0x3ec43f35,
0x3f353f80,0xbf350000,0x3f353f80,0xbf350000,0xbf350000,0xbf35bf80,0xbf350000,0xbf35bf80,0xbf35bf80,0x3f350000,0xbf35bf80,0x3f350000,0x3f350000,0x3f353f80,0x3f350000,0x3f353f80,
0x3ec43f80,0xbf6d0000,0xbec4bf80,0x3f6d0000,0xbf6dbf35,0x3ec4bf35,0x3f6d3f35,0xbec43f35,0x3f6d0000,0x3ec43f80,0xbf6d0000,0xbec4bf80,0xbec43f35,0xbf6dbf35,0x3ec4bf35,0x3f6d3f35,
0x3f80,0xbf800000,0x3f80,0xbf800000,0xbf80,0x3f800000,0xbf80,0x3f800000,0x3f80,0xbf800000,0x3f80,0xbf800000,0xbf80,0x3f800000,0xbf80,0x3f800000,
0xbec43f80,0xbf6d0000,0x3ec4bf80,0x3f6d0000,0x3f6dbf35,0x3ec43f35,0xbf6d3f35,0xbec4bf35,0xbf6d0000,0x3ec4bf80,0x3f6d0000,0xbec43f80,0x3ec43f35,0xbf6d3f35,0xbec4bf35,0x3f6dbf35,
0xbf353f80,0xbf350000,0xbf353f80,0xbf350000,0x3f350000,0xbf353f80,0x3f350000,0xbf353f80,0x3f35bf80,0x3f350000,0x3f35bf80,0x3f350000,0xbf350000,0x3f35bf80,0xbf350000,0x3f35bf80,
0xbf6d3f80,0xbec40000,0x3f6dbf80,0x3ec40000,0xbec43f35,0xbf6d3f35,0x3ec4bf35,0x3f6dbf35,0x3ec40000,0xbf6d3f80,0xbec40000,0x3f6dbf80,0x3f6dbf35,0xbec43f35,0xbf6d3f35,0x3ec4bf35,
0x3f80,0x3f80,0x3f80,0x3f80,0x3f80,0xbf80,0x3f80,0xbf80,0x3f80,0x3f80,0x3f80,0x3f80,0x3f80,0xbf80,0x3f80,0xbf80,
0x3f80,0x3f80,0x3f800000,0x3f800000,0x3ec43f6d,0xbec4bf6d,0x3f6dbec4,0xbf6d3ec4,0x3f353f35,0x3f353f35,0x3f35bf35,0x3f35bf35,0x3f6d3ec4,0xbf6dbec4,0x3ec4bf6d,0xbec43f6d,
0x3f80,0x3f80,0xbf80,0xbf80,0x3f353f35,0xbf35bf35,0xbf35bf35,0x3f353f35,0x3f800000,0x3f800000,0xbf800000,0xbf800000,0x3f35bf35,0xbf353f35,0xbf353f35,0x3f35bf35,
0x3f80,0x3f80,0xbf800000,0xbf800000,0x3f6d3ec4,0xbf6dbec4,0xbec43f6d,0x3ec4bf6d,0x3f35bf35,0x3f35bf35,0x3f353f35,0x3f353f35,0xbec4bf6d,0x3ec43f6d,0x3f6dbec4,0xbf6d3ec4,
0x3f80,0x3f80,0x3f80,0x3f80,0x3f800000,0xbf800000,0x3f800000,0xbf800000,0xbf80,0xbf80,0xbf80,0xbf80,0xbf800000,0x3f800000,0xbf800000,0x3f800000,
0x3f80,0x3f80,0x3f800000,0x3f800000,0x3f6dbec4,0xbf6d3ec4,0xbec4bf6d,0x3ec43f6d,0xbf35bf35,0xbf35bf35,0xbf353f35,0xbf353f35,0xbec43f6d,0x3ec4bf6d,0x3f6d3ec4,0xbf6dbec4,
0x3f80,0x3f80,0xbf80,0xbf80,0x3f35bf35,0xbf353f35,0xbf353f35,0x3f35bf35,0xbf800000,0xbf800000,0x3f800000,0x3f800000,0x3f353f35,0xbf35bf35,0xbf35bf35,0x3f353f35,
0x3f80,0x3f80,0xbf800000,0xbf800000,0x3ec4bf6d,0xbec43f6d,0x3f6d3ec4,0xbf6dbec4,0xbf353f35,0xbf353f35,0xbf35bf35,0xbf35bf35,0x3f6dbec4,0xbf6d3ec4,0x3ec43f6d,0xbec4bf6d,
0x3f80,0x3f80,0x3f80,0x3f80,0x3f80,0xbf80,0x3f80,0xbf80,0x3f80,0x3f80,0x3f80,0x3f80,0x3f80,0xbf80,0x3f80,0xbf80,
0xbf80,0xbf80,0xbf800000,0xbf800000,0xbec4bf6d,0x3ec43f6d,0xbf6d3ec4,0x3f6dbec4,0xbf35bf35,0xbf35bf35,0xbf353f35,0xbf353f35,0xbf6dbec4,0x3f6d3ec4,0xbec43f6d,0x3ec4bf6d,
0x3f80,0x3f80,0xbf80,0xbf80,0x3f353f35,0xbf35bf35,0xbf35bf35,0x3f353f35,0x3f800000,0x3f800000,0xbf800000,0xbf800000,0x3f35bf35,0xbf353f35,0xbf353f35,0x3f35bf35,
0xbf80,0xbf80,0x3f800000,0x3f800000,0xbf6dbec4,0x3f6d3ec4,0x3ec4bf6d,0xbec43f6d,0xbf353f35,0xbf353f35,0xbf35bf35,0xbf35bf35,0x3ec43f6d,0xbec4bf6d,0xbf6d3ec4,0x3f6dbec4,
0x3f80,0x3f80,0x3f80,0x3f80,0x3f800000,0xbf800000,0x3f800000,0xbf800000,0xbf80,0xbf80,0xbf80,0xbf80,0xbf800000,0x3f800000,0xbf800000,0x3f800000,
0xbf80,0xbf80,0xbf800000,0xbf800000,0xbf6d3ec4,0x3f6dbec4,0x3ec43f6d,0xbec4bf6d,0x3f353f35,0x3f353f35,0x3f35bf35,0x3f35bf35,0x3ec4bf6d,0xbec43f6d,0xbf6dbec4,0x3f6d3ec4,
0x3f80,0x3f80,0xbf80,0xbf80,0x3f35bf35,0xbf353f35,0xbf353f35,0x3f35bf35,0xbf800000,0xbf800000,0x3f800000,0x3f800000,0x3f353f35,0xbf35bf35,0xbf35bf35,0x3f353f35,
0xbf80,0xbf80,0x3f800000,0x3f800000,0xbec43f6d,0x3ec4bf6d,0xbf6dbec4,0x3f6d3ec4,0x3f35bf35,0x3f35bf35,0x3f353f35,0x3f353f35,0xbf6d3ec4,0x3f6dbec4,0xbec4bf6d,0x3ec43f6d,
0x3f800000,0x3f800000,0x3f800000,0x3f800000,0x3f800000,0xbf800000,0x3f800000,0xbf800000,0x3f800000,0x3f800000,0x3f800000,0x3f800000,0x3f800000,0xbf800000,0x3f800000,0xbf800000,
0x3f800000,0x3f800000,0xbf80,0xbf80,0x3f6dbec4,0xbf6d3ec4,0xbec4bf6d,0x3ec43f6d,0x3f35bf35,0x3f35bf35,0xbf35bf35,0xbf35bf35,0x3ec4bf6d,0xbec43f6d,0xbf6dbec4,0x3f6d3ec4,
0x3f800000,0x3f800000,0xbf800000,0xbf800000,0x3f35bf35,0xbf353f35,0xbf353f35,0x3f35bf35,0xbf80,0xbf80,0x3f80,0x3f80,0xbf35bf35,0x3f353f35,0x3f353f35,0xbf35bf35,
0x3f800000,0x3f800000,0x3f80,0x3f80,0x3ec4bf6d,0xbec43f6d,0x3f6d3ec4,0xbf6dbec4,0xbf35bf35,0xbf35bf35,0x3f35bf35,0x3f35bf35,0xbf6d3ec4,0x3f6dbec4,0xbec4bf6d,0x3ec43f6d,
0x3f800000,0x3f800000,0x3f800000,0x3f800000,0xbf80,0x3f80,0xbf80,0x3f80,0xbf800000,0xbf800000,0xbf800000,0xbf800000,0x3f80,0xbf80,0x3f80,0xbf80,
0x3f800000,0x3f800000,0xbf80,0xbf80,0xbec4bf6d,0x3ec43f6d,0xbf6d3ec4,0x3f6dbec4,0xbf353f35,0xbf353f35,0x3f353f35,0x3f353f35,0x3f6d3ec4,0xbf6dbec4,0x3ec4bf6d,0xbec43f6d,
0x3f800000,0x3f800000,0xbf800000,0xbf800000,0xbf35bf35,0x3f353f35,0x3f353f35,0xbf35bf35,0x3f80,0x3f80,0xbf80,0xbf80,0x3f35bf35,0xbf353f35,0xbf353f35,0x3f35bf35,
0x3f800000,0x3f800000,0x3f80,0x3f80,0xbf6dbec4,0x3f6d3ec4,0x3ec4bf6d,0xbec43f6d,0x3f353f35,0x3f353f35,0xbf353f35,0xbf353f35,0xbec4bf6d,0x3ec43f6d,0x3f6dbec4,0xbf6d3ec4,
0x3f800000,0x3f800000,0x3f800000,0x3f800000,0x3f800000,0xbf800000,0x3f800000,0xbf800000,0x3f800000,0x3f800000,0x3f800000,0x3f800000,0x3f800000,0xbf800000,0x3f800000,0xbf800000,
0xbf800000,0xbf800000,0x3f80,0x3f80,0xbf6d3ec4,0x3f6dbec4,0x3ec43f6d,0xbec4bf6d,0xbf353f35,0xbf353f35,0x3f353f35,0x3f353f35,0xbec43f6d,0x3ec4bf6d,0x3f6d3ec4,0xbf6dbec4,
0x3f800000,0x3f800000,0xbf800000,0xbf800000,0x3f35bf35,0xbf353f35,0xbf353f35,0x3f35bf35,0xbf80,0xbf80,0x3f80,0x3f80,0xbf35bf35,0x3f353f35,0x3f353f35,0xbf35bf35,
0xbf800000,0xbf800000,0xbf80,0xbf80,0xbec43f6d,0x3ec4bf6d,0xbf6dbec4,0x3f6d3ec4,0x3f353f35,0x3f353f35,0xbf353f35,0xbf353f35,0x3f6dbec4,0xbf6d3ec4,0x3ec43f6d,0xbec4bf6d,
0x3f800000,0x3f800000,0x3f800000,0x3f800000,0xbf80,0x3f80,0xbf80,0x3f80,0xbf800000,0xbf800000,0xbf800000,0xbf800000,0x3f80,0xbf80,0x3f80,0xbf80,
0xbf800000,0xbf800000,0x3f80,0x3f80,0x3ec43f6d,0xbec4bf6d,0x3f6dbec4,0xbf6d3ec4,0x3f35bf35,0x3f35bf35,0xbf35bf35,0xbf35bf35,0xbf6dbec4,0x3f6d3ec4,0xbec43f6d,0x3ec4bf6d,
0x3f800000,0x3f800000,0xbf800000,0xbf800000,0xbf35bf35,0x3f353f35,0x3f353f35,0xbf35bf35,0x3f80,0x3f80,0xbf80,0xbf80,0x3f35bf35,0xbf353f35,0xbf353f35,0x3f35bf35,
0xbf800000,0xbf800000,0xbf80,0xbf80,0x3f6d3ec4,0xbf6dbec4,0xbec43f6d,0x3ec4bf6d,0xbf35bf35,0xbf35bf35,0x3f35bf35,0x3f35bf35,0x3ec43f6d,0xbec4bf6d,0xbf6d3ec4,0x3f6dbec4,
0x3f803f80,0xbf803f80,0x3f803f80,0xbf803f80,0x3f803f80,0xbf803f80,0x3f803f80,0xbf803f80,0x3f803f80,0xbf803f80,0x3f803f80,0xbf803f80,0x3f803f80,0xbf803f80,0x3f803f80,0xbf803f80,
0x3f6d3f80,0xbf6d3f80,0xbf6dbf80,0x3f6dbf80,0x3ec43f35,0xbec43f35,0xbec4bf35,0x3ec4bf35,0xbec40000,0x3ec40000,0x3ec40000,0xbec40000,0xbf6dbf35,0x3f6dbf35,0x3f6d3f35,0xbf6d3f35,
0x3f353f80,0xbf353f80,0x3f353f80,0xbf353f80,0xbf350000,0x3f350000,0xbf350000,0x3f350000,0xbf35bf80,0x3f35bf80,0xbf35bf80,0x3f35bf80,0x3f350000,0xbf350000,0x3f350000,0xbf350000,
0x3ec43f80,0xbec43f80,0xbec4bf80,0x3ec4bf80,0xbf6dbf35,0x3f6dbf35,0x3f6d3f35,0xbf6d3f35,0x3f6d0000,0xbf6d0000,0xbf6d0000,0x3f6d0000,0xbec43f35,0x3ec43f35,0x3ec4bf35,0xbec4bf35,
0x3f80,0x3f80,0x3f80,0x3f80,0xbf80,0xbf80,0xbf80,0xbf80,0x3f80,0x3f80,0x3f80,0x3f80,0xbf80,0xbf80,0xbf80,0xbf80,
0xbec43f80,0x3ec43f80,0x3ec4bf80,0xbec4bf80,0x3f6dbf35,0xbf6dbf35,0xbf6d3f35,0x3f6d3f35,0xbf6d0000,0x3f6d0000,0x3f6d0000,0xbf6d0000,0x3ec43f35,0xbec43f35,0xbec4bf35,0x3ec4bf35,
0xbf353f80,0x3f353f80,0xbf353f80,0x3f353f80,0x3f350000,0xbf350000,0x3f350000,0xbf350000,0x3f35bf80,0xbf35bf80,0x3f35bf80,0xbf35bf80,0xbf350000,0x3f350000,0xbf350000,0x3f350000,
0xbf6d3f80,0x3f6d3f80,0x3f6dbf80,0xbf6dbf80,0xbec43f35,0x3ec43f35,0x3ec4bf35,0xbec4bf35,0x3ec40000,0xbec40000,0xbec40000,0x3ec40000,0x3f6dbf35,0xbf6dbf35,0xbf6d3f35,0x3f6d3f35,
0,0,0,0,0,0,0,0,0,0,0,0,0,0,0,0,
0x3ec40000,0xbec40000,0xbec40000,0x3ec40000,0x3f6d3f35,0xbf6d3f35,0xbf6dbf35,0x3f6dbf35,0x3f6d3f80,0xbf6d3f80,0xbf6dbf80,0x3f6dbf80,0x3ec43f35,0xbec43f35,0xbec4bf35,0x3ec4bf35,
0x3f350000,0xbf350000,0x3f350000,0xbf350000,0x3f353f80,0xbf353f80,0x3f353f80,0xbf353f80,0xbf350000,0x3f350000,0xbf350000,0x3f350000,0xbf35bf80,0x3f35bf80,0xbf35bf80,0x3f35bf80,
0x3f6d0000,0xbf6d0000,0xbf6d0000,0x3f6d0000,0xbec43f35,0x3ec43f35,0x3ec4bf35,0xbec4bf35,0xbec4bf80,0x3ec4bf80,0x3ec43f80,0xbec43f80,0x3f6d3f35,0xbf6d3f35,0xbf6dbf35,0x3f6dbf35,
0x3f800000,0xbf800000,0x3f800000,0xbf800000,0xbf800000,0x3f800000,0xbf800000,0x3f800000,0x3f800000,0xbf800000,0x3f800000,0xbf800000,0xbf800000,0x3f800000,0xbf800000,0x3f800000,
0x3f6d0000,0xbf6d0000,0xbf6d0000,0x3f6d0000,0xbec4bf35,0x3ec4bf35,0x3ec43f35,0xbec43f35,0xbec43f80,0x3ec43f80,0x3ec4bf80,0xbec4bf80,0x3f6dbf35,0xbf6dbf35,0xbf6d3f35,0x3f6d3f35,
0x3f350000,0xbf350000,0x3f350000,0xbf350000,0x3f35bf80,0xbf35bf80,0x3f35bf80,0xbf35bf80,0xbf350000,0x3f350000,0xbf350000,0x3f350000,0xbf353f80,0x3f353f80,0xbf353f80,0x3f353f80,
0x3ec40000,0xbec40000,0xbec40000,0x3ec40000,0x3f6dbf35,0xbf6dbf35,0xbf6d3f35,0x3f6d3f35,0x3f6dbf80,0xbf6dbf80,0xbf6d3f80,0x3f6d3f80,0x3ec4bf35,0xbec4bf35,0xbec43f35,0x3ec43f35,
0,0,0,0,0,0,0,0,0,0,0,0,0,0,0,0,
0xbec40000,0x3ec40000,0x3ec40000,0xbec40000,0xbf6dbf35,0x3f6dbf35,0x3f6d3f35,0xbf6d3f35,0xbf6dbf80,0x3f6dbf80,0x3f6d3f80,0xbf6d3f80,0xbec4bf35,0x3ec4bf35,0x3ec43f35,0xbec43f35,
0xbf350000,0x3f350000,0xbf350000,0x3f350000,0xbf35bf80,0x3f35bf80,0xbf35bf80,0x3f35bf80,0x3f350000,0xbf350000,0x3f350000,0xbf350000,0x3f353f80,0xbf353f80,0x3f353f80,0xbf353f80,
0xbf6d0000,0x3f6d0000,0x3f6d0000,0xbf6d0000,0x3ec4bf35,0xbec4bf35,0xbec43f35,0x3ec43f35,0x3ec43f80,0xbec43f80,0xbec4bf80,0x3ec4bf80,0xbf6dbf35,0x3f6dbf35,0x3f6d3f35,0xbf6d3f35,
0xbf800000,0x3f800000,0xbf800000,0x3f800000,0x3f800000,0xbf800000,0x3f800000,0xbf800000,0xbf800000,0x3f800000,0xbf800000,0x3f800000,0x3f800000,0xbf800000,0x3f800000,0xbf800000,
0xbf6d0000,0x3f6d0000,0x3f6d0000,0xbf6d0000,0x3ec43f35,0xbec43f35,0xbec4bf35,0x3ec4bf35,0x3ec4bf80,0xbec4bf80,0xbec43f80,0x3ec43f80,0xbf6d3f35,0x3f6d3f35,0x3f6dbf35,0xbf6dbf35,
0xbf350000,0x3f350000,0xbf350000,0x3f350000,0xbf353f80,0x3f353f80,0xbf353f80,0x3f353f80,0x3f350000,0xbf350000,0x3f350000,0xbf350000,0x3f35bf80,0xbf35bf80,0x3f35bf80,0xbf35bf80,
0xbec40000,0x3ec40000,0x3ec40000,0xbec40000,0xbf6d3f35,0x3f6d3f35,0x3f6dbf35,0xbf6dbf35,0xbf6d3f80,0x3f6d3f80,0x3f6dbf80,0xbf6dbf80,0xbec43f35,0x3ec43f35,0x3ec4bf35,0xbec4bf35,
0x3f800000,0x3f800000,0x3f800000,0x3f6c835e,0x3f800000,0x3f800000,0x3f3504f3,0x3ec3ef15,0x3f800000,0x3f800000,0,0xbec3ef15,0x3f800000,0x3f800000,0xbf3504f3,0xbf6c835e,
0x3f800000,0x3f7fb10f,0x3f800000,0x3f676bd8,0x3f7ec46d,0x3f7d3aac,0x3f226799,0x3e78cfcc,0x3f7b14be,0x3f7853f8,0xbe47c5c2,0xbf187fc0,0x3f74fa0b,0x3f710908,0xbf61c598,0xbf7fb10f,
0x3f800000,0x3f7ec46d,0x3f800000,0x3f61c598,0x3f7b14be,0x3f74fa0b,0x3f0e39da,0x3dc8bd36,0x3f6c835e,0x3f61c598,0xbec3ef15,0xbf45e403,0x3f54db31,0x3f45e403,0xbf7b14be,0xbf74fa0b,
0x3f800000,0x3f7d3aac,0x3f800000,0x3f5b941a,0x3f74fa0b,0x3f676bd8,0x3ef15aea,0xbd48fb30,0x3f54db31,0x3f3daef9,0xbf0e39da,0xbf676bd8,0x3f226799,0x3f039c3d,0xbf7ec46d,0xbf4d9f02,
0x3f800000,0x3f7b14be,0x3f800000,0x3f54db31,0x3f6c835e,0x3f54db31,0x3ec3ef15,0xbe47c5c2,0x3f3504f3,0x3f0e39da,0xbf3504f3,0xbf7b14be,0x3ec3ef15,0x3e47c5c2,0xbf6c835e,0xbf0e39da,
0x3f800000,0x3f7853f8,0x3f800000,0x3f4d9f02,0x3f61c598,0x3f3daef9,0x3e94a031,0xbeac7cd4,0x3f0e39da,0x3eac7cd4,0xbf54db31,0xbf7fb10f,0x3dc8bd36,0xbe164083,0xbf45e403,0xbe78cfcc,
0x3f800000,0x3f74fa0b,0x3f800000,0x3f45e403,0x3f54db31,0x3f226799,0x3e47c5c2,0xbef15aea,0x3ec3ef15,0x3dc8bd36,0xbf6c835e,0xbf74fa0b,0xbe47c5c2,0xbef15aea,0xbf0e39da,0x3dc8bd36,
0x3f800000,0x3f710908,0x3f800000,0x3f3daef9,0x3f45e403,0x3f039c3d,0x3dc8bd36,0xbf187fc0,0x3e47c5c2,0xbe164083,0xbf7b14be,0xbf5b941a,0xbef15aea,0xbf3daef9,0xbe94a031,0x3edae880,
0,0,0,0x3ec3ef15,0,0,0x3f3504f3,0x3f6c835e,0,0,0x3f800000,0x3f6c835e,0,0,0x3f3504f3,0x3ec3ef15,
0,0x3d48fb30,0,0x3edae880,0x3dc8bd36,0x3e164083,0x3f45e403,0x3f7853f8,0x3e47c5c2,0x3e78cfcc,0x3f7b14be,0x3f4d9f02,0x3e94a031,0x3eac7cd4,0x3ef15aea,0x3d48fb30,
0,0x3dc8bd36,0,0x3ef15aea,0x3e47c5c2,0x3e94a031,0x3f54db31,0x3f7ec46d,0x3ec3ef15,0x3ef15aea,0x3f6c835e,0x3f226799,0x3f0e39da,0x3f226799,0x3e47c5c2,0xbe94a031,
0,0x3e164083,0,0x3f039c3d,0x3e94a031,0x3edae880,0x3f61c598,0x3f7fb10f,0x3f0e39da,0x3f2beb4a,0x3f54db31,0x3edae880,0x3f45e403,0x3f5b941a,0xbdc8bd36,0xbf187fc0,
0,0x3e47c5c2,0,0x3f0e39da,0x3ec3ef15,0x3f0e39da,0x3f6c835e,0x3f7b14be,0x3f3504f3,0x3f54db31,0x3f3504f3,0x3e47c5c2,0x3f6c835e,0x3f7b14be,0xbec3ef15,0xbf54db31,
0,0x3e78cfcc,0,0x3f187fc0,0x3ef15aea,0x3f2beb4a,0x3f74fa0b,0x3f710908,0x3f54db31,0x3f710908,0x3f0e39da,0xbd48fb30,0x3f7ec46d,0x3f7d3aac,0xbf226799,0xbf7853f8,
0,0x3e94a031,0,0x3f226799,0x3f0e39da,0x3f45e403,0x3f7b14be,0x3f61c598,0x3f6c835e,0x3f7ec46d,0x3ec3ef15,0xbe94a031,0x3f7b14be,0x3f61c598,0xbf54db31,0xbf7ec46d,
0,0x3eac7cd4,0,0x3f2beb4a,0x3f226799,0x3f5b941a,0x3f7ec46d,0x3f4d9f02,0x3f7b14be,0x3f7d3aac,0x3e47c5c2,0xbf039c3d,0x3f61c598,0x3f2beb4a,0xbf74fa0b,0xbf676bd8,
0x35cccccd,0x35cccccd,0x35cccccd,0x35cccccd,0x35cccccd,0x35cccccd,0x35cccccd,0x35cccccd,0x35cccccd,0x35cccccd,0x35cccccd,0x35cccccd,0x35cccccd,0x35cccccd,0x35cccccd,0x35cccccd,
0x35cccccd,0x35cc8da6,0x35bd35e5,0x35b92313,0x35cbd057,0x35ca9556,0x35b49e13,0x35afa9af,0x35c8dd65,0x35c6a993,0x35aa48f4,0x35a47f35,0x35c3fb3c,0x35c0d407,0x359e5003,0x3597bf2e,
0x35cccccd,0x35cbd057,0x3590d0c3,0x3581ec7b,0x35c8dd65,0x35c3fb3c,0x35638fc3,0x35411588,0x35bd35e5,0x35b49e13,0x351cbf44,0x34edcd1c,0x35aa48f4,0x359e5003,0x349fd168,0x3420975e,
0x35cccccd,0x35ca9556,0x351cbf44,0x34c70ca3,0x35c3fb3c,0x35b92313,0x3420975e,0xb3a0c8f3,0x35aa48f4,0x3597bf2e,0xb49fd168,0xb509fd76,0x3581ec7b,0x35529394,0xb5411588,0xb573ff99,
0x35cccccd,0x35c8dd65,0,0xb49fd168,0x35bd35e5,0x35aa48f4,0xb51cbf44,0xb5638fc3,0x3590d0c3,0x35638fc3,0xb590d0c3,0xb5aa48f4,0x351cbf44,0x349fd168,0xb5bd35e5,0xb5c8dd65,
0x35cccccd,0x35c6a993,0xb51cbf44,0xb573ff99,0x35b49e13,0x3597bf2e,0xb59e5003,0xb5b92313,0x35638fc3,0x3509fd76,0xb5c8dd65,0xb5cc8da6,0x3420975e,0xb4706739,0xb5c3fb3c,0xb5afa9af,
0x35cccccd,0x35c3fb3c,0xb590d0c3,0xb5b49e13,0x35aa48f4,0x3581ec7b,0xb5c8dd65,0xb5cbd057,0x351cbf44,0x3420975e,0xb5bd35e5,0xb59e5003,0xb49fd168,0xb5411588,0xb5638fc3,0xb4edcd1c,
0x35cccccd,0x35c0d407,0xb5bd35e5,0xb5cc8da6,0x359e5003,0x35529394,0xb5c3fb3c,0xb5a47f35,0x349fd168,0xb4706739,0xb5638fc3,0xb4c70ca3,0xb5411588,0xb597bf2e,0x3420975e,0x352f2067,
0,0,0,0,0,0,0,0,0,0,0,0,0,0,0,0,
0,0x33a0c8f3,0x351cbf44,0x352f2067,0x3420975e,0x34706739,0x35411588,0x35529394,0x349fd168,0x34c70ca3,0x35638fc3,0x3573ff99,0x34edcd1c,0x3509fd76,0x3581ec7b,0x35898908,
0,0x3420975e,0x3590d0c3,0x359e5003,0x349fd168,0x34edcd1c,0x35aa48f4,0x35b49e13,0x351cbf44,0x35411588,0x35bd35e5,0x35c3fb3c,0x35638fc3,0x3581ec7b,0x35c8dd65,0x35cbd057,
0,0x34706739,0x35bd35e5,0x35c6a993,0x34edcd1c,0x352f2067,0x35cbd057,0x35cc8da6,0x35638fc3,0x35898908,0x35c8dd65,0x35c0d407,0x359e5003,0x35afa9af,0x35b49e13,0x35a47f35,
0,0x349fd168,0x35cccccd,0x35c8dd65,0x351cbf44,0x35638fc3,0x35bd35e5,0x35aa48f4,0x3590d0c3,0x35aa48f4,0x3590d0c3,0x35638fc3,0x35bd35e5,0x35c8dd65,0x351cbf44,0x349fd168,
0,0x34c70ca3,0x35bd35e5,0x35a47f35,0x35411588,0x35898908,0x3581ec7b,0x352f2067,0x35aa48f4,0x35c0d407,0x349fd168,0xb3a0c8f3,0x35cbd057,0x35ca9556,0xb4edcd1c,0xb5529394,
0,0x34edcd1c,0x3590d0c3,0x35411588,0x35638fc3,0x359e5003,0x349fd168,0xb420975e,0x35bd35e5,0x35cbd057,0xb51cbf44,0xb581ec7b,0x35c8dd65,0x35b49e13,0xb5aa48f4,0xb5c3fb3c,
0,0x3509fd76,0x351cbf44,0x33a0c8f3,0x3581ec7b,0x35afa9af,0xb4edcd1c,0xb573ff99,0x35c8dd65,0x35ca9556,0xb5aa48f4,0xb5c6a993,0x35b49e13,0x35898908,0xb5cbd057,0xb5b92313,
0x3f803f80,0,0,0x3f803f80,0x3f803f80,0,0,0x3f803f80,0x3f803f80,0,0,0x3f803f80,0x3f803f80,0,0,0x3f803f80,
0x3f353f80,0x3f350000,0xbf350000,0x3f353f80,0xbf350000,0x3f353f80,0xbf35bf80,0xbf350000,0xbf35bf80,0xbf350000,0x3f350000,0xbf35bf80,0x3f350000,0xbf35bf80,0x3f353f80,0x3f350000,
0x3f80,0x3f800000,0xbf800000,0x3f80,0xbf80,0xbf800000,0x3f800000,0xbf80,0x3f80,0x3f800000,0xbf800000,0x3f80,0xbf80,0xbf800000,0x3f800000,0xbf80,
0xbf353f80,0x3f350000,0xbf350000,0xbf353f80,0x3f350000,0x3f35bf80,0xbf353f80,0x3f350000,0x3f35bf80,0xbf350000,0x3f350000,0x3f35bf80,0xbf350000,0xbf353f80,0x3f35bf80,0xbf350000,
0xbf803f80,0,0,0xbf803f80,0xbf803f80,0,0,0xbf803f80,0xbf803f80,0,0,0xbf803f80,0xbf803f80,0,0,0xbf803f80,
0xbf353f80,0xbf350000,0x3f350000,0xbf353f80,0x3f350000,0xbf353f80,0x3f35bf80,0x3f350000,0x3f35bf80,0x3f350000,0xbf350000,0x3f35bf80,0xbf350000,0x3f35bf80,0xbf353f80,0xbf350000,
0x3f80,0xbf800000,0x3f800000,0x3f80,0xbf80,0x3f800000,0xbf800000,0xbf80,0x3f80,0xbf800000,0x3f800000,0x3f80,0xbf80,0x3f800000,0xbf800000,0xbf80,
0x3f353f80,0xbf350000,0x3f350000,0x3f353f80,0xbf350000,0xbf35bf80,0x3f353f80,0xbf350000,0xbf35bf80,0x3f350000,0xbf350000,0xbf35bf80,0x3f350000,0x3f353f80,0xbf35bf80,0x3f350000,
0x3f80,0x3f80,0x3dc93f7f,0x3dc93f7f,0x3cc93f80,0xbcc9bf80,0x3dfb3f7e,0xbdfbbf7e,0x3d493f80,0x3d493f80,0x3e163f7d,0x3e163f7d,0x3d973f7f,0xbd97bf7f,0x3e2f3f7c,0xbe2fbf7c,
0x3f80,0x3f80,0x3f7fbdc9,0x3f7fbdc9,0x3ecf3f6a,0xbecfbf6a,0x3f5fbefc,0xbf5f3efc,0x3f3e3f2c,0x3f3e3f2c,0x3f18bf4e,0x3f18bf4e,0x3f733ea1,0xbf73bea1,0x3e60bf7a,0xbe603f7a,
0x3f80,0x3f80,0xbdc9bf7f,0xbdc9bf7f,0x3f393f31,0xbf39bf31,0xbf4abf1d,0x3f4a3f1d,0x3f80bd49,0x3f80bd49,0xbf7d3e16,0xbf7d3e16,0x3f27bf42,0xbf273f42,0xbf133f51,0x3f13bf51,
0x3f80,0x3f80,0xbf7f3dc9,0xbf7f3dc9,0x3f6f3eb8,0xbf6fbeb8,0xbe893f77,0x3e89bf77,0x3f2cbf3e,0x3f2cbf3e,0x3f4e3f18,0x3f4e3f18,0xbee6bf65,0x3ee63f65,0x3f58bf09,0xbf583f09,
0x3f80,0x3f80,0x3dc93f7f,0x3dc93f7f,0x3f80bcc9,0xbf803cc9,0x3f7ebdfb,0xbf7e3dfb,0xbd49bf80,0xbd49bf80,0xbe16bf7d,0xbe16bf7d,0xbf7f3d97,0x3f7fbd97,0xbf7c3e2f,0x3f7cbe2f,
0x3f80,0x3f80,0x3f7fbdc9,0x3f7fbdc9,0x3f6abecf,0xbf6a3ecf,0xbefcbf5f,0x3efc3f5f,0xbf3ebf2c,0xbf3ebf2c,0xbf183f4e,0xbf183f4e,0xbea13f73,0x3ea1bf73,0x3f7a3e60,0xbf7abe60,
0x3f80,0x3f80,0xbdc9bf7f,0xbdc9bf7f,0x3f31bf39,0xbf313f39,0xbf1d3f4a,0x3f1dbf4a,0xbf803d49,0xbf803d49,0x3f7dbe16,0x3f7dbe16,0x3f423f27,0xbf42bf27,0xbf51bf13,0x3f513f13,
0x3f80,0x3f80,0xbf7f3dc9,0xbf7f3dc9,0x3eb8bf6f,0xbeb83f6f,0x3f773e89,0xbf77be89,0xbf2c3f3e,0xbf2c3f3e,0xbf4ebf18,0xbf4ebf18,0x3f65bee6,0xbf653ee6,0x3f093f58,0xbf09bf58,
0x3e483f7b,0x3e483f7b,0x3e953f75,0x3e953f75,0x3e603f7a,0xbe60bf7a,0x3ea13f73,0xbea1bf73,0x3e793f78,0x3e793f78,0x3eac3f71,0x3eac3f71,0x3e893f77,0xbe89bf77,0x3eb83f6f,0xbeb8bf6f,
0xbe48bf7b,0xbe48bf7b,0xbf753e95,0xbf753e95,0xbf13bf51,0x3f133f51,0xbf423f27,0x3f42bf27,0xbf5cbf04,0xbf5cbf04,0xbedb3f67,0xbedb3f67,0xbf7ebdfb,0x3f7e3dfb,0xbcc93f80,0x3cc9bf80,
0x3e483f7b,0x3e483f7b,0xbe95bf75,0xbe95bf75,0x3f583f09,0xbf58bf09,0xbf65bee6,0x3f653ee6,0x3f78be79,0x3f78be79,0xbf713eac,0xbf713eac,0x3efcbf5f,0xbefc3f5f,0xbecf3f6a,0x3ecfbf6a,
0xbe48bf7b,0xbe48bf7b,0x3f75be95,0x3f75be95,0xbf7cbe2f,0x3f7c3e2f,0x3d97bf7f,0xbd973f7f,0xbf043f5c,0xbf043f5c,0xbf67bedb,0xbf67bedb,0x3f1d3f4a,0xbf1dbf4a,0xbf393f31,0x3f39bf31,
0x3e483f7b,0x3e483f7b,0x3e953f75,0x3e953f75,0x3f7abe60,0xbf7a3e60,0x3f73bea1,0xbf733ea1,0xbe79bf78,0xbe79bf78,0xbeacbf71,0xbeacbf71,0xbf773e89,0x3f77be89,0xbf6f3eb8,0x3f6fbeb8,
0xbe48bf7b,0xbe48bf7b,0xbf753e95,0xbf753e95,0xbf513f13,0x3f51bf13,0x3f273f42,0xbf27bf42,0x3f5c3f04,0x3f5c3f04,0x3edbbf67,0x3edbbf67,0x3dfbbf7e,0xbdfb3f7e,0xbf80bcc9,0x3f803cc9,
0x3e483f7b,0x3e483f7b,0xbe95bf75,0xbe95bf75,0x3f09bf58,0xbf093f58,0xbee63f65,0x3ee6bf65,0xbf783e79,0xbf783e79,0x3f71beac,0x3f71beac,0x3f5f3efc,0xbf5fbefc,0xbf6abecf,0x3f6a3ecf,
0xbe48bf7b,0xbe48bf7b,0x3f75be95,0x3f75be95,0xbe2f3f7c,0x3e2fbf7c,0xbf7fbd97,0x3f7f3d97,0x3f04bf5c,0x3f04bf5c,0x3f673edb,0x3f673edb,0xbf4a3f1d,0x3f4abf1d,0xbf31bf39,0x3f313f39,
0x3f800000,0x3f800000,0x3f7fbdc9,0x3f7fbdc9,0x3f80bcc9,0xbf803cc9,0x3f7ebdfb,0xbf7e3dfb,0x3f80bd49,0x3f80bd49,0x3f7dbe16,0x3f7dbe16,0x3f7fbd97,0xbf7f3d97,0x3f7cbe2f,0xbf7c3e2f,
0x3f800000,0x3f800000,0xbdc9bf7f,0xbdc9bf7f,0x3f6abecf,0xbf6a3ecf,0xbefcbf5f,0x3efc3f5f,0x3f2cbf3e,0x3f2cbf3e,0xbf4ebf18,0xbf4ebf18,0x3ea1bf73,0xbea13f73,0xbf7abe60,0x3f7a3e60,
0x3f800000,0x3f800000,0xbf7f3dc9,0xbf7f3dc9,0x3f31bf39,0xbf313f39,0xbf1d3f4a,0x3f1dbf4a,0xbd49bf80,0xbd49bf80,0x3e163f7d,0x3e163f7d,0xbf42bf27,0x3f423f27,0x3f513f13,0xbf51bf13,
0x3f800000,0x3f800000,0x3dc93f7f,0x3dc93f7f,0x3eb8bf6f,0xbeb83f6f,0x3f773e89,0xbf77be89,0xbf3ebf2c,0xbf3ebf2c,0x3f18bf4e,0x3f18bf4e,0xbf653ee6,0x3f65bee6,0xbf09bf58,0x3f093f58,
0x3f800000,0x3f800000,0x3f7fbdc9,0x3f7fbdc9,0xbcc9bf80,0x3cc93f80,0xbdfbbf7e,0x3dfb3f7e,0xbf803d49,0xbf803d49,0xbf7d3e16,0xbf7d3e16,0x3d973f7f,0xbd97bf7f,0x3e2f3f7c,0xbe2fbf7c,
0x3f800000,0x3f800000,0xbdc9bf7f,0xbdc9bf7f,0xbecfbf6a,0x3ecf3f6a,0xbf5f3efc,0x3f5fbefc,0xbf2c3f3e,0xbf2c3f3e,0x3f4e3f18,0x3f4e3f18,0x3f733ea1,0xbf73bea1,0x3e60bf7a,0xbe603f7a,
0x3f800000,0x3f800000,0xbf7f3dc9,0xbf7f3dc9,0xbf39bf31,0x3f393f31,0x3f4a3f1d,0xbf4abf1d,0x3d493f80,0x3d493f80,0xbe16bf7d,0xbe16bf7d,0x3f27bf42,0xbf273f42,0xbf133f51,0x3f13bf51,
0x3f800000,0x3f800000,0x3dc93f7f,0x3dc93f7f,0xbf6fbeb8,0x3f6f3eb8,0x3e89bf77,0xbe893f77,0x3f3e3f2c,0x3f3e3f2c,0xbf183f4e,0xbf183f4e,0xbee6bf65,0x3ee63f65,0x3f58bf09,0xbf583f09,
0x3f7bbe48,0x3f7bbe48,0x3f75be95,0x3f75be95,0x3f7abe60,0xbf7a3e60,0x3f73bea1,0xbf733ea1,0x3f78be79,0x3f78be79,0x3f71beac,0x3f71beac,0x3f77be89,0xbf773e89,0x3f6fbeb8,0xbf6f3eb8,
0xbf7b3e48,0xbf7b3e48,0x3e953f75,0x3e953f75,0xbf513f13,0x3f51bf13,0x3f273f42,0xbf27bf42,0xbf043f5c,0xbf043f5c,0x3f673edb,0x3f673edb,0xbdfb3f7e,0x3dfbbf7e,0x3f803cc9,0xbf80bcc9,
0x3f7bbe48,0x3f7bbe48,0xbf753e95,0xbf753e95,0x3f09bf58,0xbf093f58,0xbee63f65,0x3ee6bf65,0xbe79bf78,0xbe79bf78,0x3eac3f71,0x3eac3f71,0xbf5fbefc,0x3f5f3efc,0x3f6a3ecf,0xbf6abecf,
0xbf7b3e48,0xbf7b3e48,0xbe95bf75,0xbe95bf75,0xbe2f3f7c,0x3e2fbf7c,0xbf7fbd97,0x3f7f3d97,0x3f5c3f04,0x3f5c3f04,0xbedb3f67,0xbedb3f67,0x3f4abf1d,0xbf4a3f1d,0x3f313f39,0xbf31bf39,
0x3f7bbe48,0x3f7bbe48,0x3f75be95,0x3f75be95,0xbe60bf7a,0x3e603f7a,0xbea1bf73,0x3ea13f73,0xbf783e79,0xbf783e79,0xbf713eac,0xbf713eac,0x3e893f77,0xbe89bf77,0x3eb83f6f,0xbeb8bf6f,
0xbf7b3e48,0xbf7b3e48,0x3e953f75,0x3e953f75,0x3f133f51,0xbf13bf51,0x3f42bf27,0xbf423f27,0x3f04bf5c,0x3f04bf5c,0xbf67bedb,0xbf67bedb,0xbf7ebdfb,0x3f7e3dfb,0xbcc93f80,0x3cc9bf80,
0x3f7bbe48,0x3f7bbe48,0xbf753e95,0xbf753e95,0xbf58bf09,0x3f583f09,0x3f653ee6,0xbf65bee6,0x3e793f78,0x3e793f78,0xbeacbf71,0xbeacbf71,0x3efcbf5f,0xbefc3f5f,0xbecf3f6a,0x3ecfbf6a,
0xbf7b3e48,0xbf7b3e48,0xbe95bf75,0xbe95bf75,0x3f7c3e2f,0xbf7cbe2f,0xbd973f7f,0x3d97bf7f,0xbf5cbf04,0xbf5cbf04,0x3edbbf67,0x3edbbf67,0x3f1d3f4a,0xbf1dbf4a,0xbf393f31,0x3f39bf31,
0x3f803f80,0xbf7b3f7b,0x3f803f80,0xbf7b3f7b,0x3f803f80,0xbf7b3f7b,0x3f803f80,0xbf7b3f7b,0x3f803f80,0xbf7b3f7b,0x3f803f80,0xbf7b3f7b,0x3f803f80,0xbf7b3f7b,0x3f803f80,0xbf7b3f7b,
0x3f6a3f80,0xbf513f7a,0xbf6abf80,0x3f51bf7a,0x3eb83f31,0xbe2f3f09,0xbeb8bf31,0x3e2fbf09,0xbecfbcc9,0x3f13be60,0x3ecf3cc9,0xbf133e60,0xbf6fbf39,0x3f7cbf58,0x3f6f3f39,0xbf7c3f58,
0x3f2c3f80,0xbf043f78,0x3f2c3f80,0xbf043f78,0xbf3ebd49,0x3f5cbe79,0xbf3ebd49,0x3f5cbe79,0xbf2cbf80,0x3f04bf78,0xbf2cbf80,0x3f04bf78,0x3f3e3d49,0xbf5c3e79,0x3f3e3d49,0xbf5c3e79,
0x3ea13f7f,0xbdfb3f77,0xbea1bf7f,0x3dfbbf77,0xbf65bf42,0x3f4abf5f,0x3f653f42,0xbf4a3f5f,0x3f733d97,0xbf7e3e89,0xbf73bd97,0x3f7ebe89,0xbee63f27,0x3f1d3efc,0x3ee6bf27,0xbf1dbefc,
0xbdc93f7f,0x3e953f75,0xbdc93f7f,0x3e953f75,0x3dc9bf7f,0xbe95bf75,0x3dc9bf7f,0xbe95bf75,0xbdc93f7f,0x3e953f75,0xbdc93f7f,0x3e953f75,0x3dc9bf7f,0xbe95bf75,0x3dc9bf7f,0xbe95bf75,
0xbefc3f7e,0x3f273f73,0x3efcbf7e,0xbf27bf73,0x3f77bf1d,0xbf7fbee6,0xbf773f1d,0x3f7f3ee6,0xbf5fbdfb,0x3f42bea1,0x3f5f3dfb,0xbf423ea1,0x3e893f4a,0xbd973f65,0xbe89bf4a,0x3d97bf65,
0xbf4e3f7d,0x3f673f71,0xbf4e3f7d,0x3f673f71,0x3f183e16,0xbedb3eac,0x3f183e16,0xbedb3eac,0x3f4ebf7d,0xbf67bf71,0x3f4ebf7d,0xbf67bf71,0xbf18be16,0x3edbbeac,0xbf18be16,0x3edbbeac,
0xbf7a3f7c,0x3f803f6f,0x3f7abf7c,0xbf80bf6f,0xbf093f51,0x3f313f6a,0x3f09bf51,0xbf31bf6a,0x3e603e2f,0xbcc93eb8,0xbe60be2f,0x3cc9beb8,0x3f58bf13,0xbf39becf,0xbf583f13,0x3f393ecf,
0,0xbe483e48,0,0xbe483e48,0,0xbe483e48,0,0xbe483e48,0,0xbe483e48,0,0xbe483e48,0,0xbe483e48,0,0xbe483e48,
0x3ecf3cc9,0xbf133e60,0xbecfbcc9,0x3f13be60,0x3f6f3f39,0xbf7c3f58,0xbf6fbf39,0x3f7cbf58,0x3f6a3f80,0xbf513f7a,0xbf6abf80,0x3f51bf7a,0x3eb83f31,0xbe2f3f09,0xbeb8bf31,0x3e2fbf09,
0x3f3e3d49,0xbf5c3e79,0x3f3e3d49,0xbf5c3e79,0x3f2c3f80,0xbf043f78,0x3f2c3f80,0xbf043f78,0xbf3ebd49,0x3f5cbe79,0xbf3ebd49,0x3f5cbe79,0xbf2cbf80,0x3f04bf78,0xbf2cbf80,0x3f04bf78,
0x3f733d97,0xbf7e3e89,0xbf73bd97,0x3f7ebe89,0xbee63f27,0x3f1d3efc,0x3ee6bf27,0xbf1dbefc,0xbea1bf7f,0x3dfbbf77,0x3ea13f7f,0xbdfb3f77,0x3f653f42,0xbf4a3f5f,0xbf65bf42,0x3f4abf5f,
0x3f7f3dc9,0xbf753e95,0x3f7f3dc9,0xbf753e95,0xbf7fbdc9,0x3f75be95,0xbf7fbdc9,0x3f75be95,0x3f7f3dc9,0xbf753e95,0x3f7f3dc9,0xbf753e95,0xbf7fbdc9,0x3f75be95,0xbf7fbdc9,0x3f75be95,
0x3f5f3dfb,0xbf423ea1,0xbf5fbdfb,0x3f42bea1,0xbe89bf4a,0x3d97bf65,0x3e893f4a,0xbd973f65,0xbefc3f7e,0x3f273f73,0x3efcbf7e,0xbf27bf73,0x3f77bf1d,0xbf7fbee6,0xbf773f1d,0x3f7f3ee6,
0x3f183e16,0xbedb3eac,0x3f183e16,0xbedb3eac,0x3f4ebf7d,0xbf67bf71,0x3f4ebf7d,0xbf67bf71,0xbf18be16,0x3edbbeac,0xbf18be16,0x3edbbeac,0xbf4e3f7d,0x3f673f71,0xbf4e3f7d,0x3f673f71,
0x3e603e2f,0xbcc93eb8,0xbe60be2f,0x3cc9beb8,0x3f58bf13,0xbf39becf,0xbf583f13,0x3f393ecf,0x3f7abf7c,0xbf80bf6f,0xbf7a3f7c,0x3f803f6f,0x3f09bf51,0xbf31bf6a,0xbf093f51,0x3f313f6a,
0,0x3e48be48,0,0x3e48be48,0,0x3e48be48,0,0x3e48be48,0,0x3e48be48,0,0x3e48be48,0,0x3e48be48,0,0x3e48be48,
0xbecfbcc9,0x3f13be60,0x3ecf3cc9,0xbf133e60,0xbf6fbf39,0x3f7cbf58,0x3f6f3f39,0xbf7c3f58,0xbf6abf80,0x3f51bf7a,0x3f6a3f80,0xbf513f7a,0xbeb8bf31,0x3e2fbf09,0x3eb83f31,0xbe2f3f09,
0xbf3ebd49,0x3f5cbe79,0xbf3ebd49,0x3f5cbe79,0xbf2cbf80,0x3f04bf78,0xbf2cbf80,0x3f04bf78,0x3f3e3d49,0xbf5c3e79,0x3f3e3d49,0xbf5c3e79,0x3f2c3f80,0xbf043f78,0x3f2c3f80,0xbf043f78,
0xbf73bd97,0x3f7ebe89,0x3f733d97,0xbf7e3e89,0x3ee6bf27,0xbf1dbefc,0xbee63f27,0x3f1d3efc,0x3ea13f7f,0xbdfb3f77,0xbea1bf7f,0x3dfbbf77,0xbf65bf42,0x3f4abf5f,0x3f653f42,0xbf4a3f5f,
0xbf7fbdc9,0x3f75be95,0xbf7fbdc9,0x3f75be95,0x3f7f3dc9,0xbf753e95,0x3f7f3dc9,0xbf753e95,0xbf7fbdc9,0x3f75be95,0xbf7fbdc9,0x3f75be95,0x3f7f3dc9,0xbf753e95,0x3f7f3dc9,0xbf753e95,
0xbf5fbdfb,0x3f42bea1,0x3f5f3dfb,0xbf423ea1,0x3e893f4a,0xbd973f65,0xbe89bf4a,0x3d97bf65,0x3efcbf7e,0xbf27bf73,0xbefc3f7e,0x3f273f73,0xbf773f1d,0x3f7f3ee6,0x3f77bf1d,0xbf7fbee6,
0xbf18be16,0x3edbbeac,0xbf18be16,0x3edbbeac,0xbf4e3f7d,0x3f673f71,0xbf4e3f7d,0x3f673f71,0x3f183e16,0xbedb3eac,0x3f183e16,0xbedb3eac,0x3f4ebf7d,0xbf67bf71,0x3f4ebf7d,0xbf67bf71,
0xbe60be2f,0x3cc9beb8,0x3e603e2f,0xbcc93eb8,0xbf583f13,0x3f393ecf,0x3f58bf13,0xbf39becf,0xbf7a3f7c,0x3f803f6f,0x3f7abf7c,0xbf80bf6f,0xbf093f51,0x3f313f6a,0x3f09bf51,0xbf31bf6a,
0x3f800000,0x3f7fffb1,0x3f800000,0x3f6c3624,0x3f7ffec4,0x3f7ffd39,0x3f33e7bc,0x3ebf926f,0x3f7ffb11,0x3f7ff84a,0xbc490e90,0xbecb2aae,0x3f7ff4e6,0x3f7ff0e3,0xbf385216,0xbf6e8ff8,
0x3f800000,0x3f7fa6e3,0x3f800000,0x3f671599,0x3f7e9bc9,0x3f7cdf6c,0x3f212ff9,0x3e6fa8b2,0x3f7a7302,0x3f77583a,0xbe541501,0xbf1ba299,0x3f73913f,0x3f6f20b0,0xbf63f473,0xbf7fe705,
0x3f800000,0x3f7eb069,0x3f800000,0x3f61668a,0x3f7ac516,0x3f74484b,0x3f0cead0,0x3db5f8da,0x3f6b4b0c,0x3f5fe4e9,0xbec9b953,0xbf485bca,0x3f5233c6,0x3f425b89,0xbf7bf531,0xbf73530e,
0x3f800000,0x3f7d1cdd,0x3f800000,0x3f5b2c79,0x3f748422,0x3f666771,0x3eee9479,0xbd6ea038,0x3f531849,0x3f3b0629,0xbf10d3cd,0xbf6912ae,0x3f1ebc12,0x3efdbabb,0xbf7e4323,0xbf4a4c87,
0x3f800000,0x3f7aed37,0x3f800000,0x3f546b3b,0x3f6be858,0x3f5389c7,0x3ec1071e,0xbe5101f1,0x3f32c8c9,0x3f0af1b7,0xbf373a23,0xbf7bd14d,0x3ebb31a0,0x3e3228d4,0xbf6aab7b,0xbf099f4e,
0x3f800000,0x3f7822d1,0x3f800000,0x3f4d26fd,0x3f6106f2,0x3f3c17d9,0x3e919ddd,0xbeb0eacb,0x3f0b9a6b,0x3ea5129f,0xbf5695e5,0xbf7f7808,0x3da3308c,0xbe2bf804,0xbf42de29,0xbe636c83,
0x3f800000,0x3f74bf62,0x3f800000,0x3f456439,0x3f53fac3,0x3f209393,0x3e419b37,0xbef58035,0x3ebe1d4a,0x3da973ba,0xbf6db293,0xbf73ced9,0xbe5a3997,0xbefafef7,0xbf0a48ad,0x3df475c0,
0x3f800000,0x3f70c501,0x3f800000,0x3f3d27b8,0x3f44e3f5,0x3f019573,0x3dbc3ac3,0xbf1a6293,0x3e3b6ecf,0xbe25c58c,0xbf7baccd,0xbf5988ad,0xbef9a02d,0xbf4154e1,0xbe8b9507,0x3ee4cbfe,
0,0x3b490fc6,0,0x3ec5625c,0x3bc90f88,0x3c16cb58,0x3f36206c,0x3f6d67a1,0x3c490e90,0x3c7b514b,0x3f7ffb11,0x3f6afb8c,0x3c96c9b6,0x3cafea69,0x3f31a81d,0x3eb9bb1e,
0,0x3d55880e,0,0x3edc53c1,0x3dd53db9,0x3e1f917b,0x3f46e22a,0x3f78e3d6,0x3e541501,0x3e840270,0x3f7a7302,0x3f4b41fa,0x3e9d9e78,0x3eb6ccc3,0x3ee900b7,0x3ce22a7a,
0,0x3dcefdb7,0,0x3ef2bd43,0x3e4dee60,0x3e9920fe,0x3f55b993,0x3f7efcc9,0x3ec9b953,0x3ef840c8,0x3f6b4b0c,0x3f1f599f,0x3f121eb0,0x3f269de3,0x3e354098,0xbe9f1cdf,
0,0x3e195be0,0,0x3f044889,0x3e97a117,0x3edf28a9,0x3f628210,0x3f7f90b1,0x3f10d3cd,0x3f2ecef7,0x3f531849,0x3ed3c867,0x3f48d8b3,0x3f5e5aa6,0xbdee3876,0xbf1ce11f,
0,0x3e4ada4f,0,0x3f0ee0db,0x3ec6d529,0x3f102dd5,0x3f6d1c1d,0x3f7a9c59,0x3f373a23,0x3f570348,0x3f32c8c9,0x3e3857ec,0x3f6e46be,0x3f7c187a,0xbecc9b8b,0xbf57dc7f,
0,0x3e7bdba4,0,0x3f19210f,0x3ef41f07,0x3f2da859,0x3f756d97,0x3f703b37,0x3f5695e5,0x3f725470,0x3f0b9a6b,0xbd83db0a,0x3f7f2f9d,0x3f7c5d3a,0xbf26050a,0xbf799b43,
0,0x3e9620d2,0,0x3f2302d3,0x3f0f8784,0x3f476085,0x3f7b61fc,0x3f60a6cf,0x3f6db293,0x3f7f1f49,0x3ebe1d4a,0xbe9c1faf,0x3f7a1e84,0x3f5f20db,0xbf577026,0xbf7e2b72,
0,0x3eadf73c,0,0x3f2c800f,0x3f239da9,0x3f5cc7d1,0x3f7eea9d,0x3f4c3578,0x3f7baccd,0x3f7c9f8a,0x3e3b6ecf,0xbf06f686,0x3f5f8327,0x3f27ce61,0xbf764d97,0xbf650479,
0x35cccccd,0x35cccccd,0x35cccccd,0x35cccccd,0x35cccccd,0x35cccccd,0x35cccccd,0x35cccccd,0x35cccccd,0x35cccccd,0x35cccccd,0x35cccccd,0x35cccccd,0x35cccccd,0x35cccccd,0x35cccccd,
0x35cccc8e,0x35cc8582,0x35bcf81d,0x35b8de14,0x35cbc054,0x35ca7d7e,0x35b45208,0x35af56c7,0x35c8bdc6,0x35c68241,0x35a9ef63,0x35a41f31,0x35c3cc4e,0x35c09d9b,0x359de9c7,0x359752fa,
0x35cccbd0,0x35cbafd4,0x358fec97,0x3580f32d,0x35c89dab,0x35c39ce8,0x356177b4,0x353edd2d,0x35bcb9e0,0x35b4058e,0x351a6c18,0x34e8fc95,0x35a99568,0x359d832a,0x349ae293,0x34169569,
0x35ccca94,0x35ca4c56,0x351941f2,0x34bfba28,0x35c36d09,0x35b852c1,0x341193e2,0xb3bee693,0x35a93b06,0x3596797a,0xb4a734c1,0xb50d88a2,0x3580760f,0x354f5584,0xb5446691,0xb577041e,
0x35ccc8da,0x35c85c01,0xb2a0d873,0xb4a9aa67,0x35bc3c09,0x35a8e03a,0xb521610f,0xb567b948,0x358f0707,0x355f5d78,0xb59294e9,0xb5abab1e,0x3518176e,0x3495f23f,0xb5be2876,0xb5c9570a,
0x35ccc6a2,0x35c5e02f,0xb522888b,0xb5790428,0x35b31d87,0x35959e88,0xb5a0496e,0xb5ba7558,0x355e4f8b,0x35040ee5,0xb5c9743e,0xb5cc6006,0x34078fc8,0xb4849e0a,0xb5c30be1,0xb5ae06f1,
0x35ccc3eb,0x35c2da99,0xb59374de,0xb5b65d28,0x35a8296b,0x357df9b6,0xb5c990f4,0xb5cb68e9,0x3515c14d,0x34028d3d,0xb5bbbc62,0xb59be4ed,0xb4ae9479,0xb547b357,0xb55d4116,0xb4df54d8,
0x35ccc0b6,0x35bf4d5a,0xb5bed993,0xb5ccb8d1,0x359b7c6d,0x354afbc9,0xb5c2a8d8,0xb5a1d6d2,0x348e8710,0xb4899337,0xb55c3217,0xb4b5f068,0xb548cbf9,0xb59aaa4d,0x34439166,0x35370998,
0,0,0,0,0,0,0,0,0,0,0,0,0,0,0,0,
0x31a0d96b,0x33aad33e,0x351de84a,0x35304301,0x342597c6,0x34755fcc,0x35423103,0x3553a742,0x34a2483f,0x34c97c83,0x35649af8,0x357501b2,0x34f03484,0x350b2c30,0x358268a9,0x358a000c,
0x3220d93a,0x342a97c7,0x3591b389,0x359f1b54,0x34a4beb3,0x34f29b58,0x35aafadc,0x35b534da,0x351f10ee,0x35434c06,0x35bdb017,0x35c457ac,0x3565a5a1,0x3582e487,0x35c91b30,0x35cbeee4,
0x3271455a,0x347f4f2b,0x35bdec81,0x35c71cab,0x34f50196,0x353286ed,0x35cbfd6e,0x35cc73c1,0x3566afbb,0x358aed14,0x35c87d14,0x35c02f5f,0x359f806a,0x35b09fda,0x35b3b8a6,0x35a35df9,
0x32a0d873,0x34a9aa67,0x35ccc8da,0x35c85c01,0x3521610f,0x3567b948,0x35bc3c09,0x35a8e03a,0x359294e9,0x35abab1e,0x358f0707,0x355f5d78,0x35be2876,0x35c9570a,0x3518176e,0x3495f23f,
0x32c90dd6,0x34d3371a,0x35bbfc70,0x35a29b2e,0x35469a3a,0x358bd8c6,0x357ef5cc,0x35296d1f,0x35ac02a0,0x35c1dd26,0x3493798a,0xb3d2f811,0x35cc1907,0x35ca193c,0xb4f9cc4b,0xb557f0d6,
0x32f142bd,0x34fc30c0,0x358e2017,0x353a66f9,0x3569cab3,0x35a0ad5c,0x3491007a,0xb43e9392,0x35be9eff,0x35cc2618,0xb523afa2,0xb584d0d5,0x35c8186a,0x35b2cf52,0xb5ac59b8,0xb5c50adf,
0x330cbb87,0x35123d69,0x351495b2,0x3334eec8,0x35854b1c,0x35b1e21f,0xb4fe9498,0xb57b01cb,0x35c9ad2f,0x35c9e42e,0xb5acb065,0xb5c7af69,0x35b280af,0x35863eb4,0xb5cb55f5,0xb5b736c7,
0x3f803f80,0,0,0x3f803f80,0x3f803f80,0,0,0x3f803f80,0x3f803f80,0,0,0x3f803f80,0x3f803f80,0,0,0x3f803f80,
0x3f353f80,0x3f350000,0xbf350000,0x3f353f80,0xbf350000,0x3f353f80,0xbf35bf80,0xbf350000,0xbf35bf80,0xbf350000,0x3f350000,0xbf35bf80,0x3f350000,0xbf35bf80,0x3f353f80,0x3f350000,
0x3f80,0x3f800000,0xbf800000,0x3f80,0xbf80,0xbf800000,0x3f800000,0xbf80,0x3f80,0x3f800000,0xbf800000,0x3f80,0xbf80,0xbf800000,0x3f800000,0xbf80,
0xbf353f80,0x3f350000,0xbf350000,0xbf353f80,0x3f350000,0x3f35bf80,0xbf353f80,0x3f350000,0x3f35bf80,0xbf350000,0x3f350000,0x3f35bf80,0xbf350000,0xbf353f80,0x3f35bf80,0xbf350000,
0xbf803f80,0,0,0xbf803f80,0xbf803f80,0,0,0xbf803f80,0xbf803f80,0,0,0xbf803f80,0xbf803f80,0,0,0xbf803f80,
0xbf353f80,0xbf350000,0x3f350000,0xbf353f80,0x3f350000,0xbf353f80,0x3f35bf80,0x3f350000,0x3f35bf80,0x3f350000,0xbf350000,0x3f35bf80,0xbf350000,0x3f35bf80,0xbf353f80,0xbf350000,
0x3f80,0xbf800000,0x3f800000,0x3f80,0xbf80,0x3f800000,0xbf800000,0xbf80,0x3f80,0xbf800000,0x3f800000,0x3f80,0xbf80,0x3f800000,0xbf800000,0xbf80,
0x3f353f80,0xbf350000,0x3f350000,0x3f353f80,0xbf350000,0xbf35bf80,0x3f353f80,0xbf350000,0xbf35bf80,0x3f350000,0xbf350000,0xbf35bf80,0x3f350000,0x3f353f80,0xbf35bf80,0x3f350000,
0x3f80,0x3f80,0x3e483f7b,0x3e483f7b,0x3d493f80,0xbd49bf80,0x3e793f78,0xbe79bf78,0x3dc93f7f,0x3dc93f7f,0x3e953f75,0x3e953f75,0x3e163f7d,0xbe16bf7d,0x3eac3f71,0xbeacbf71,
0x3f80,0x3f80,0x3f7bbe48,0x3f7bbe48,0x3edb3f67,0xbedbbf67,0x3f4ebf18,0xbf4e3f18,0x3f463f22,0x3f463f22,0x3ef1bf62,0x3ef1bf62,0x3f783e79,0xbf78be79,0x3d49bf80,0xbd493f80,
0x3f80,0x3f80,0xbe48bf7b,0xbe48bf7b,0x3f3e3f2c,0xbf3ebf2c,0xbf5cbf04,0x3f5c3f04,0x3f7fbdc9,0x3f7fbdc9,0xbf753e95,0xbf753e95,0x3f18bf4e,0xbf183f4e,0xbedb3f67,0x3edbbf67,
0x3f80,0x3f80,0xbf7b3e48,0xbf7b3e48,0x3f713eac,0xbf71beac,0xbe163f7d,0x3e16bf7d,0x3f22bf46,0x3f22bf46,0x3f623ef1,0x3f623ef1,0xbf04bf5c,0x3f043f5c,0x3f3ebf2c,0xbf3e3f2c,
0x3f80,0x3f80,0x3e483f7b,0x3e483f7b,0x3f80bd49,0xbf803d49,0x3f78be79,0xbf783e79,0xbdc9bf7f,0xbdc9bf7f,0xbe95bf75,0xbe95bf75,0xbf7d3e16,0x3f7dbe16,0xbf713eac,0x3f71beac,
0x3f80,0x3f80,0x3f7bbe48,0x3f7bbe48,0x3f67bedb,0xbf673edb,0xbf18bf4e,0x3f183f4e,0xbf46bf22,0xbf46bf22,0xbef13f62,0xbef13f62,0xbe793f78,0x3e79bf78,0x3f803d49,0xbf80bd49,
0x3f80,0x3f80,0xbe48bf7b,0xbe48bf7b,0x3f2cbf3e,0xbf2c3f3e,0xbf043f5c,0x3f04bf5c,0xbf7f3dc9,0xbf7f3dc9,0x3f75be95,0x3f75be95,0x3f4e3f18,0xbf4ebf18,0xbf67bedb,0x3f673edb,
0x3f80,0x3f80,0xbf7b3e48,0xbf7b3e48,0x3eacbf71,0xbeac3f71,0x3f7d3e16,0xbf7dbe16,0xbf223f46,0xbf223f46,0xbf62bef1,0xbf62bef1,0x3f5cbf04,0xbf5c3f04,0x3f2c3f3e,0xbf2cbf3e,
0x3ec43f6d,0x3ec43f6d,0x3f0e3f55,0x3f0e3f55,0x3edb3f67,0xbedbbf67,0x3f183f4e,0xbf18bf4e,0x3ef13f62,0x3ef13f62,0x3f223f46,0x3f223f46,0x3f043f5c,0xbf04bf5c,0x3f2c3f3e,0xbf2cbf3e,
0xbec4bf6d,0xbec4bf6d,0xbf553f0e,0xbf553f0e,0xbf3ebf2c,0x3f3e3f2c,0xbf043f5c,0x3f04bf5c,0xbf75be95,0xbf75be95,0xbdc93f7f,0xbdc93f7f,0xbf7d3e16,0x3f7dbe16,0x3eac3f71,0xbeacbf71,
0x3ec43f6d,0x3ec43f6d,0xbf0ebf55,0xbf0ebf55,0x3f713eac,0xbf71beac,0xbf7dbe16,0x3f7d3e16,0x3f62bef1,0x3f62bef1,0xbf463f22,0xbf463f22,0x3e79bf78,0xbe793f78,0xbd493f80,0x3d49bf80,
0xbec4bf6d,0xbec4bf6d,0x3f55bf0e,0x3f55bf0e,0xbf803d49,0x3f80bd49,0xbe79bf78,0x3e793f78,0xbe953f75,0xbe953f75,0xbf7fbdc9,0xbf7fbdc9,0x3f4e3f18,0xbf4ebf18,0xbedb3f67,0x3edbbf67,
0x3ec43f6d,0x3ec43f6d,0x3f0e3f55,0x3f0e3f55,0x3f67bedb,0xbf673edb,0x3f4ebf18,0xbf4e3f18,0xbef1bf62,0xbef1bf62,0xbf22bf46,0xbf22bf46,0xbf5c3f04,0x3f5cbf04,0xbf3e3f2c,0x3f3ebf2c,
0xbec4bf6d,0xbec4bf6d,0xbf553f0e,0xbf553f0e,0xbf2c3f3e,0x3f2cbf3e,0x3f5c3f04,0xbf5cbf04,0x3f753e95,0x3f753e95,0x3dc9bf7f,0x3dc9bf7f,0xbe16bf7d,0x3e163f7d,0xbf713eac,0x3f71beac,
0x3ec43f6d,0x3ec43f6d,0xbf0ebf55,0xbf0ebf55,0x3eacbf71,0xbeac3f71,0xbe163f7d,0x3e16bf7d,0xbf623ef1,0xbf623ef1,0x3f46bf22,0x3f46bf22,0x3f783e79,0xbf78be79,0xbf80bd49,0x3f803d49,
0xbec4bf6d,0xbec4bf6d,0x3f55bf0e,0x3f55bf0e,0x3d493f80,0xbd49bf80,0xbf783e79,0x3f78be79,0x3e95bf75,0x3e95bf75,0x3f7f3dc9,0x3f7f3dc9,0xbf183f4e,0x3f18bf4e,0xbf67bedb,0x3f673edb,
0x3f800000,0x3f800000,0x3f7bbe48,0x3f7bbe48,0x3f80bd49,0xbf803d49,0x3f78be79,0xbf783e79,0x3f7fbdc9,0x3f7fbdc9,0x3f75be95,0x3f75be95,0x3f7dbe16,0xbf7d3e16,0x3f71beac,0xbf713eac,
0x3f800000,0x3f800000,0xbe48bf7b,0xbe48bf7b,0x3f67bedb,0xbf673edb,0xbf18bf4e,0x3f183f4e,0x3f22bf46,0x3f22bf46,0xbf62bef1,0xbf62bef1,0x3e79bf78,0xbe793f78,0xbf80bd49,0x3f803d49,
0x3f800000,0x3f800000,0xbf7b3e48,0xbf7b3e48,0x3f2cbf3e,0xbf2c3f3e,0xbf043f5c,0x3f04bf5c,0xbdc9bf7f,0xbdc9bf7f,0x3e953f75,0x3e953f75,0xbf4ebf18,0x3f4e3f18,0x3f673edb,0xbf67bedb,
0x3f800000,0x3f800000,0x3e483f7b,0x3e483f7b,0x3eacbf71,0xbeac3f71,0x3f7d3e16,0xbf7dbe16,0xbf46bf22,0xbf46bf22,0x3ef1bf62,0x3ef1bf62,0xbf5c3f04,0x3f5cbf04,0xbf2cbf3e,0x3f2c3f3e,
0x3f800000,0x3f800000,0x3f7bbe48,0x3f7bbe48,0xbd49bf80,0x3d493f80,0xbe79bf78,0x3e793f78,0xbf7f3dc9,0xbf7f3dc9,0xbf753e95,0xbf753e95,0x3e163f7d,0xbe16bf7d,0x3eac3f71,0xbeacbf71,
0x3f800000,0x3f800000,0xbe48bf7b,0xbe48bf7b,0xbedbbf67,0x3edb3f67,0xbf4e3f18,0x3f4ebf18,0xbf223f46,0xbf223f46,0x3f623ef1,0x3f623ef1,0x3f783e79,0xbf78be79,0x3d49bf80,0xbd493f80,
0x3f800000,0x3f800000,0xbf7b3e48,0xbf7b3e48,0xbf3ebf2c,0x3f3e3f2c,0x3f5c3f04,0xbf5cbf04,0x3dc93f7f,0x3dc93f7f,0xbe95bf75,0xbe95bf75,0x3f18bf4e,0xbf183f4e,0xbedb3f67,0x3edbbf67,
0x3f800000,0x3f800000,0x3e483f7b,0x3e483f7b,0xbf71beac,0x3f713eac,0x3e16bf7d,0xbe163f7d,0x3f463f22,0x3f463f22,0xbef13f62,0xbef13f62,0xbf04bf5c,0x3f043f5c,0x3f3ebf2c,0xbf3e3f2c,
0x3f6dbec4,0x3f6dbec4,0x3f55bf0e,0x3f55bf0e,0x3f67bedb,0xbf673edb,0x3f4ebf18,0xbf4e3f18,0x3f62bef1,0x3f62bef1,0x3f46bf22,0x3f46bf22,0x3f5cbf04,0xbf5c3f04,0x3f3ebf2c,0xbf3e3f2c,
0xbf6d3ec4,0xbf6d3ec4,0x3f0e3f55,0x3f0e3f55,0xbf2c3f3e,0x3f2cbf3e,0x3f5c3f04,0xbf5cbf04,0xbe953f75,0xbe953f75,0x3f7f3dc9,0x3f7f3dc9,0x3e163f7d,0xbe16bf7d,0x3f71beac,0xbf713eac,
0x3f6dbec4,0x3f6dbec4,0xbf553f0e,0xbf553f0e,0x3eacbf71,0xbeac3f71,0xbe163f7d,0x3e16bf7d,0xbef1bf62,0xbef1bf62,0x3f223f46,0x3f223f46,0xbf78be79,0x3f783e79,0x3f803d49,0xbf80bd49,
0xbf6d3ec4,0xbf6d3ec4,0xbf0ebf55,0xbf0ebf55,0x3d493f80,0xbd49bf80,0xbf783e79,0x3f78be79,0x3f753e95,0x3f753e95,0xbdc93f7f,0xbdc93f7f,0x3f18bf4e,0xbf183f4e,0x3f673edb,0xbf67bedb,
0x3f6dbec4,0x3f6dbec4,0x3f55bf0e,0x3f55bf0e,0xbedbbf67,0x3edb3f67,0xbf18bf4e,0x3f183f4e,0xbf623ef1,0xbf623ef1,0xbf463f22,0xbf463f22,0x3f043f5c,0xbf04bf5c,0x3f2c3f3e,0xbf2cbf3e,
0xbf6d3ec4,0xbf6d3ec4,0x3f0e3f55,0x3f0e3f55,0x3f3e3f2c,0xbf3ebf2c,0x3f04bf5c,0xbf043f5c,0x3e95bf75,0x3e95bf75,0xbf7fbdc9,0xbf7fbdc9,0xbf7d3e16,0x3f7dbe16,0x3eac3f71,0xbeacbf71,
0x3f6dbec4,0x3f6dbec4,0xbf553f0e,0xbf553f0e,0xbf71beac,0x3f713eac,0x3f7d3e16,0xbf7dbe16,0x3ef13f62,0x3ef13f62,0xbf22bf46,0xbf22bf46,0x3e79bf78,0xbe793f78,0xbd493f80,0x3d49bf80,
0xbf6d3ec4,0xbf6d3ec4,0xbf0ebf55,0xbf0ebf55,0x3f80bd49,0xbf803d49,0x3e793f78,0xbe79bf78,0xbf75be95,0xbf75be95,0x3dc9bf7f,0x3dc9bf7f,0x3f4e3f18,0xbf4ebf18,0xbedb3f67,0x3edbbf67,
0x3f803f80,0xbf6d3f6d,0x3f803f80,0xbf6d3f6d,0x3f803f80,0xbf6d3f6d,0x3f803f80,0xbf6d3f6d,0x3f803f80,0xbf6d3f6d,0x3f803f80,0xbf6d3f6d,0x3f803f80,0xbf6d3f6d,0x3f803f80,0xbf6d3f6d,
0x3f673f80,0xbf2c3f67,0xbf67bf80,0x3f2cbf67,0x3eac3f2c,0x3d493eac,0xbeacbf2c,0xbd49beac,0xbedbbd49,0x3f3ebedb,0x3edb3d49,0xbf3e3edb,0xbf71bf3e,0x3f80bf71,0x3f713f3e,0xbf803f71,
0x3f223f7f,0xbe953f62,0x3f223f7f,0xbe953f62,0xbf46bdc9,0x3f75bef1,0xbf46bdc9,0x3f75bef1,0xbf22bf7f,0x3e95bf62,0xbf22bf7f,0x3e95bf62,0x3f463dc9,0xbf753ef1,0x3f463dc9,0xbf753ef1,
0x3e793f7d,0x3e163f5c,0xbe79bf7d,0xbe16bf5c,0xbf5cbf4e,0x3f18bf78,0x3f5c3f4e,0xbf183f78,0x3f783e16,0xbf7d3f04,0xbf78be16,0x3f7dbf04,0xbf043f18,0x3f4e3e79,0x3f04bf18,0xbf4ebe79,
0xbe483f7b,0x3f0e3f55,0xbe483f7b,0x3f0e3f55,0x3e48bf7b,0xbf0ebf55,0x3e48bf7b,0xbf0ebf55,0xbe483f7b,0x3f0e3f55,0xbe483f7b,0x3f0e3f55,0x3e48bf7b,0xbf0ebf55,0x3e48bf7b,0xbf0ebf55,
0xbf183f78,0x3f5c3f4e,0x3f18bf78,0xbf5cbf4e,0x3f7dbf04,0xbf78be16,0xbf7d3f04,0x3f783e16,0xbf4ebe79,0x3f04bf18,0x3f4e3e79,0xbf043f18,0x3e163f5c,0x3e793f7d,0xbe16bf5c,0xbe79bf7d,
0xbf623f75,0x3f7f3f46,0xbf623f75,0x3f7f3f46,0x3ef13e95,0xbdc93f22,0x3ef13e95,0xbdc93f22,0x3f62bf75,0xbf7fbf46,0x3f62bf75,0xbf7fbf46,0xbef1be95,0x3dc9bf22,0xbef1be95,0x3dc9bf22,
0xbf803f71,0x3f713f3e,0x3f80bf71,0xbf71bf3e,0xbf2c3f67,0x3f673f80,0x3f2cbf67,0xbf67bf80,0x3d493eac,0x3eac3f2c,0xbd49beac,0xbeacbf2c,0x3f3ebedb,0xbedbbd49,0xbf3e3edb,0x3edb3d49,
0,0xbec43ec4,0,0xbec43ec4,0,0xbec43ec4,0,0xbec43ec4,0,0xbec43ec4,0,0xbec43ec4,0,0xbec43ec4,0,0xbec43ec4,
0x3edb3d49,0xbf3e3edb,0xbedbbd49,0x3f3ebedb,0x3f713f3e,0xbf803f71,0xbf71bf3e,0x3f80bf71,0x3f673f80,0xbf2c3f67,0xbf67bf80,0x3f2cbf67,0x3eac3f2c,0x3d493eac,0xbeacbf2c,0xbd49beac,
0x3f463dc9,0xbf753ef1,0x3f463dc9,0xbf753ef1,0x3f223f7f,0xbe953f62,0x3f223f7f,0xbe953f62,0xbf46bdc9,0x3f75bef1,0xbf46bdc9,0x3f75bef1,0xbf22bf7f,0x3e95bf62,0xbf22bf7f,0x3e95bf62,
0x3f783e16,0xbf7d3f04,0xbf78be16,0x3f7dbf04,0xbf043f18,0x3f4e3e79,0x3f04bf18,0xbf4ebe79,0xbe79bf7d,0xbe16bf5c,0x3e793f7d,0x3e163f5c,0x3f5c3f4e,0xbf183f78,0xbf5cbf4e,0x3f18bf78,
0x3f7b3e48,0xbf553f0e,0x3f7b3e48,0xbf553f0e,0xbf7bbe48,0x3f55bf0e,0xbf7bbe48,0x3f55bf0e,0x3f7b3e48,0xbf553f0e,0x3f7b3e48,0xbf553f0e,0xbf7bbe48,0x3f55bf0e,0xbf7bbe48,0x3f55bf0e,
0x3f4e3e79,0xbf043f18,0xbf4ebe79,0x3f04bf18,0xbe16bf5c,0xbe79bf7d,0x3e163f5c,0x3e793f7d,0xbf183f78,0x3f5c3f4e,0x3f18bf78,0xbf5cbf4e,0x3f7dbf04,0xbf78be16,0xbf7d3f04,0x3f783e16,
0x3ef13e95,0xbdc93f22,0x3ef13e95,0xbdc93f22,0x3f62bf75,0xbf7fbf46,0x3f62bf75,0xbf7fbf46,0xbef1be95,0x3dc9bf22,0xbef1be95,0x3dc9bf22,0xbf623f75,0x3f7f3f46,0xbf623f75,0x3f7f3f46,
0x3d493eac,0x3eac3f2c,0xbd49beac,0xbeacbf2c,0x3f3ebedb,0xbedbbd49,0xbf3e3edb,0x3edb3d49,0x3f80bf71,0xbf71bf3e,0xbf803f71,0x3f713f3e,0x3f2cbf67,0xbf67bf80,0xbf2c3f67,0x3f673f80,
0,0x3ec4bec4,0,0x3ec4bec4,0,0x3ec4bec4,0,0x3ec4bec4,0,0x3ec4bec4,0,0x3ec4bec4,0,0x3ec4bec4,0,0x3ec4bec4,
0xbedbbd49,0x3f3ebedb,0x3edb3d49,0xbf3e3edb,0xbf71bf3e,0x3f80bf71,0x3f713f3e,0xbf803f71,0xbf67bf80,0x3f2cbf67,0x3f673f80,0xbf2c3f67,0xbeacbf2c,0xbd49beac,0x3eac3f2c,0x3d493eac,
0xbf46bdc9,0x3f75bef1,0xbf46bdc9,0x3f75bef1,0xbf22bf7f,0x3e95bf62,0xbf22bf7f,0x3e95bf62,0x3f463dc9,0xbf753ef1,0x3f463dc9,0xbf753ef1,0x3f223f7f,0xbe953f62,0x3f223f7f,0xbe953f62,
0xbf78be16,0x3f7dbf04,0x3f783e16,0xbf7d3f04,0x3f04bf18,0xbf4ebe79,0xbf043f18,0x3f4e3e79,0x3e793f7d,0x3e163f5c,0xbe79bf7d,0xbe16bf5c,0xbf5cbf4e,0x3f18bf78,0x3f5c3f4e,0xbf183f78,
0xbf7bbe48,0x3f55bf0e,0xbf7bbe48,0x3f55bf0e,0x3f7b3e48,0xbf553f0e,0x3f7b3e48,0xbf553f0e,0xbf7bbe48,0x3f55bf0e,0xbf7bbe48,0x3f55bf0e,0x3f7b3e48,0xbf553f0e,0x3f7b3e48,0xbf553f0e,
0xbf4ebe79,0x3f04bf18,0x3f4e3e79,0xbf043f18,0x3e163f5c,0x3e793f7d,0xbe16bf5c,0xbe79bf7d,0x3f18bf78,0xbf5cbf4e,0xbf183f78,0x3f5c3f4e,0xbf7d3f04,0x3f783e16,0x3f7dbf04,0xbf78be16,
0xbef1be95,0x3dc9bf22,0xbef1be95,0x3dc9bf22,0xbf623f75,0x3f7f3f46,0xbf623f75,0x3f7f3f46,0x3ef13e95,0xbdc93f22,0x3ef13e95,0xbdc93f22,0x3f62bf75,0xbf7fbf46,0x3f62bf75,0xbf7fbf46,
0xbd49beac,0xbeacbf2c,0x3d493eac,0x3eac3f2c,0xbf3e3edb,0x3edb3d49,0x3f3ebedb,0xbedbbd49,0xbf803f71,0x3f713f3e,0x3f80bf71,0xbf71bf3e,0xbf2c3f67,0x3f673f80,0x3f2cbf67,0xbf67bf80,
0x3f800000,0x3f7ffec4,0x3f800000,0x3f6be858,0x3f7ffb11,0x3f7ff4e6,0x3f32c8c9,0x3ebb31a0,0x3f7fec43,0x3f7fe129,0xbcc90ab0,0xbed25a09,0x3f7fd397,0x3f7fc38f,0xbf3b8f3b,0xbf708066,
0x3f800000,0x3f7f9c18,0x3f800000,0x3f66becc,0x3f7e70b0,0x3f7c7eb0,0x3f1ff6cb,0x3e667c66,0x3f79c79d,0x3f764d97,0xbe605c13,0xbf1ebc12,0x3f721352,0x3f6d1c1d,0xbf660f88,0xbf7ffec4,
0x3f800000,0x3f7e9bc9,0x3f800000,0x3f6106f2,0x3f7a7302,0x3f73913f,0x3f0b9a6b,0x3da3308c,0x3f6a09a7,0x3f5df6be,0xbecf7bca,0xbf4ac77f,0x3f4f7a1f,0x3f3ebc1b,0xbf7cbfc9,0xbf718f57,
0x3f800000,0x3f7cfe73,0x3f800000,0x3f5ac450,0x3f740bdd,0x3f655e0b,0x3eebcbbb,0xbd8a200a,0x3f514d3d,0x3f385216,0xbf13682a,0xbf6aab7b,0x3f1b02c6,0x3ef41f07,0xbf7dabcc,0xbf46e22a,
0x3f800000,0x3f7ac516,0x3f800000,0x3f53fac3,0x3f6b4b0c,0x3f5233c6,0x3ebe1d4a,0xbe5a3997,0x3f3085bb,0x3f07a136,0xbf396842,0xbf7c7eb0,0x3eb263ef,0x3e1c76de,0xbf68bf3c,0xbf04f484,
0x3f800000,0x3f77f110,0x3f800000,0x3f4cae79,0x3f604621,0x3f3a7ca4,0x3e8e9a22,0xbeb554ec,0x3f08f59b,0x3e9d9e78,0xbf584853,0xbf7f2f9d,0x3d7b2b74,0xbe419b37,0xbf3fc767,0xbe4dee60,
0x3f800000,0x3f748422,0x3f800000,0x3f44e3f5,0x3f531849,0x3f1ebc12,0x3e3b6ecf,0xbef9a02d,0x3eb8442a,0x3d8a200a,0xbf6ed89e,0xbf7294f8,0xbe6c9a7f,0xbf0242b1,0xbf064b82,0x3e1008b7,
0x3f800000,0x3f708066,0x3f800000,0x3f3ca003,0x3f43e200,0x3eff17b2,0x3dafb680,0xbf1c420c,0x3e2f10a2,0xbe354098,0xbf7c3b28,0xbf577026,0xbf00e7e4,0xbf44e3f5,0xbe827dc0,0x3eee9479,
0,0x3bc90f88,0,0x3ec6d529,0x3c490e90,0x3c96c9b6,0x3f373a23,0x3f6e46be,0x3cc90ab0,0x3cfb49ba,0x3f7fec43,0x3f696591,0x3d16c32c,0x3d2fe007,0x3f2e3bde,0x3eaf713a,
0,0x3d621469,0,0x3eddbe79,0x3de1bc2e,0x3e28defc,0x3f47de65,0x3f796e4e,0x3e605c13,0x3e8b9507,0x3f79c79d,0x3f48d8b3,0x3ea68f12,0x3ec1071e,0x3ee0924f,0x3bc90f88,
0,0x3dd53db9,0,0x3ef41f07,0x3e541501,0x3e9d9e78,0x3f5695e5,0x3f7f2f9d,0x3ecf7bca,0x3eff17b2,0x3f6a09a7,0x3f1c420c,0x3f15f6d9,0x3f2ac082,0x3e22abb6,0xbea986c4,
0,0x3e1c76de,0,0x3f04f484,0x3e9aa086,0x3ee363fa,0x3f633c5a,0x3f7f6ac7,0x3f13682a,0x3f31a81d,0x3f514d3d,0x3ecc9b8b,0x3f4bbbf8,0x3f6106f2,0xbe09cf86,0xbf212ff9,
0,0x3e4dee60,0,0x3f0f8784,0x3ec9b953,0x3f121eb0,0x3f6db293,0x3f7a1e84,0x3f396842,0x3f591e6a,0x3f3085bb,0x3e28defc,0x3f6ff573,0x3f7cfe73,0xbed53641,0xbf5ac450,
0,0x3e7ee6e1,0,0x3f19c200,0x3ef6e0cb,0x3f2f61a5,0x3f75dec6,0x3f6f6830,0x3f584853,0x3f73913f,0x3f08f59b,0xbda3308c,0x3f7f84ab,0x3f7b61fc,0xbf299415,0xbf7ac516,
0,0x3e97a117,0,0x3f239da9,0x3f10d3cd,0x3f48d8b3,0x3f7baccd,0x3f5f8327,0x3f6ed89e,0x3f7f6ac7,0x3eb8442a,0xbea395c5,0x3f791298,0x3f5c61c7,0xbf59f26a,0xbf7d7474,
0,0x3eaf713a,0,0x3f2d1469,0x3f24d225,0x3f5df6be,0x3f7f0e58,0x3f4ac77f,0x3f7c3b28,0x3f7bf531,0x3e2f10a2,0xbf0a48ad,0x3f5d2d53,0x3f239da9,0xbf778bc5,0xbf628210,
0x35cccccd,0x35cccccd,0x35cccccd,0x35cccccd,0x35cccccd,0x35cccccd,0x35cccccd,0x35cccccd,0x35cccccd,0x35cccccd,0x35cccccd,0x35cccccd,0x35cccccd,0x35cccccd,0x35cccccd,0x35cccccd,
0x35cccbd0,0x35cc7ce0,0x35bcb9e0,0x35b898a3,0x35cbafd4,0x35ca6529,0x35b4058e,0x35af0373,0x35c89dab,0x35c65a74,0x35a99568,0x35a3bec8,0x35c39ce8,0x35c066b8,0x359d832a,0x3596e669,
0x35ccc8da,0x35cb8d5a,0x358f0707,0x357ff144,0x35c85c01,0x35c33cb1,0x355f5d78,0x353ca2fc,0x35bc3c09,0x35b36b4e,0x3518176e,0x34e429d0,0x35a8e03a,0x359cb4cd,0x3495f23f,0x340c9200,
0x35ccc3eb,0x35c9fef3,0x3515c14d,0x34b86384,0x35c2da99,0x35b77e6f,0x34028d3d,0xb3dd000f,0x35a8296b,0x35953084,0xb4ae9479,0xb51110bd,0x357df9b6,0x354c12f5,0xb547b357,0xb57a0347,
0x35ccbd02,0x35c7d2e4,0xb320d559,0xb4b37cdc,0x35bb3aec,0x35a770fe,0xb525fca2,0xb56bd9dd,0x358d37c9,0x355b2291,0xb5945368,0xb5ad06a9,0x351369bb,0x348c0d4f,0xb5bf13b1,0xb5c9c8ed,
0x35ccb421,0x35c50adf,0xb5284807,0xb57df9b6,0x35b19232,0x359374de,0xb5a23933,0xb5bbbc62,0x355901f0,0x34fc30c0,0xb5c9fef3,0xb5cc2618,0x33dd000f,0xb491007a,0xb5c210c7,0xb5ac59b8,
0x35cca946,0x35c1a90f,0xb5960c2f,0xb5b80c6c,0x35a5fb4c,0x3578046f,0xb5ca3307,0xb5caefd6,0x350eb659,0x33c8ef90,0xb5ba3296,0xb5996c52,0xb4bd4866,0xb54e3fd4,0xb556df37,0xb4d0c934,
0x35cc9c72,0x35bdb017,0xb5c066b8,0xb5cccbd0,0x3598967c,0x35434c06,0xb5c13f79,0xb59f1b54,0x347a57c9,0xb49ae293,0xb554ba6c,0xb4a4beb3,0xb5506ab5,0xb59d832a,0x34667457,0x353edd2d,
0,0,0,0,0,0,0,0,0,0,0,0,0,0,0,0,
0x3220d93a,0x33b4dd20,0x351f10ee,0x3531652e,0x342a97c7,0x347a57c9,0x35434c06,0x3554ba6c,0x34a4beb3,0x34cbebe7,0x3565a5a1,0x35760334,0x34f29b58,0x350c5a95,0x3582e487,0x358a76bb,
0x32a0d873,0x3434968b,0x359294e9,0x359fe51e,0x34a9aa67,0x34f7673d,0x35abab1e,0x35b5c9e1,0x3521610f,0x354580a2,0x35be2876,0x35c4b238,0x3567b948,0x3583db51,0x35c9570a,0x35cc0b7a,
0x32f142bd,0x348718ca,0x35be9eff,0x35c78b72,0x34fc30c0,0x3535e995,0x35cc2618,0x35cc556c,0x3569cab3,0x358c4e1d,0x35c8186a,0x35bf868d,0x35a0ad5c,0x35b19232,0x35b2cf52,0x35a23933,
0x3320d559,0x34b37cdc,0x35ccbd02,0x35c7d2e4,0x3525fca2,0x356bd9dd,0x35bb3aec,0x35a770fe,0x35945368,0x35ad06a9,0x358d37c9,0x355b2291,0x35bf13b1,0x35c9c8ed,0x351369bb,0x348c0d4f,
0x334907c8,0x34df54d8,0x35bab7a7,0x35a0ad5c,0x354c12f5,0x358e2017,0x357a0347,0x3523afa2,0x35adb1ef,0x35c2da99,0x348718ca,0xb4028d3d,0x35cc556c,0x35c990f4,0xb502de37,0xb55d4116,
0x33713846,0x35053f42,0x358b6318,0x3533a83f,0x356ff15b,0x35a2fcc6,0x348222f8,0xb45c7f3e,0x35bff78f,0x35cc6a23,0xb52a91ce,0xb587a9aa,0x35c74213,0x35b0f10f,0xb5ae5b88,0xb5c6096a,
0x338cb338,0x351a6c18,0x350c5a95,0x3220d93a,0x35889a01,0x35b4058e,0xb5079f03,0xb580f32d,0x35ca6529,0x35c91b30,0xb5af0373,0xb5c89dab,0x35b04e38,0x3582e487,0xb5cac390,0xb5b534da,
0x3f803f80,0,0,0x3f803f80,0x3f803f80,0,0,0x3f803f80,0x3f803f80,0,0,0x3f803f80,0x3f803f80,0,0,0x3f803f80,
0x3f353f80,0x3f350000,0xbf350000,0x3f353f80,0xbf350000,0x3f353f80,0xbf35bf80,0xbf350000,0xbf35bf80,0xbf350000,0x3f350000,0xbf35bf80,0x3f350000,0xbf35bf80,0x3f353f80,0x3f350000,
0x3f80,0x3f800000,0xbf800000,0x3f80,0xbf80,0xbf800000,0x3f800000,0xbf80,0x3f80,0x3f800000,0xbf800000,0x3f80,0xbf80,0xbf800000,0x3f800000,0xbf80,
0xbf353f80,0x3f350000,0xbf350000,0xbf353f80,0x3f350000,0x3f35bf80,0xbf353f80,0x3f350000,0x3f35bf80,0xbf350000,0x3f350000,0x3f35bf80,0xbf350000,0xbf353f80,0x3f35bf80,0xbf350000,
0xbf803f80,0,0,0xbf803f80,0xbf803f80,0,0,0xbf803f80,0xbf803f80,0,0,0xbf803f80,0xbf803f80,0,0,0xbf803f80,
0xbf353f80,0xbf350000,0x3f350000,0xbf353f80,0x3f350000,0xbf353f80,0x3f35bf80,0x3f350000,0x3f35bf80,0x3f350000,0xbf350000,0x3f35bf80,0xbf350000,0x3f35bf80,0xbf353f80,0xbf350000,
0x3f80,0xbf800000,0x3f800000,0x3f80,0xbf80,0x3f800000,0xbf800000,0xbf80,0x3f80,0xbf800000,0x3f800000,0x3f80,0xbf80,0x3f800000,0xbf800000,0xbf80,
0x3f353f80,0xbf350000,0x3f350000,0x3f353f80,0xbf350000,0xbf35bf80,0x3f353f80,0xbf350000,0xbf35bf80,0x3f350000,0xbf350000,0xbf35bf80,0x3f350000,0x3f353f80,0xbf35bf80,0x3f350000,
0x3f80,0x3f80,0x3e953f75,0x3e953f75,0x3d973f7f,0xbd97bf7f,0x3eb83f6f,0xbeb8bf6f,0x3e163f7d,0x3e163f7d,0x3edb3f67,0x3edb3f67,0x3e603f7a,0xbe60bf7a,0x3efc3f5f,0xbefcbf5f,
0x3f80,0x3f80,0x3f75be95,0x3f75be95,0x3ee63f65,0xbee6bf65,0x3f39bf31,0xbf393f31,0x3f4e3f18,0x3f4e3f18,0x3eacbf71,0x3eacbf71,0x3f7c3e2f,0xbf7cbe2f,0xbdfbbf7e,0x3dfb3f7e,
0x3f80,0x3f80,0xbe95bf75,0xbe95bf75,0x3f423f27,0xbf42bf27,0xbf6abecf,0x3f6a3ecf,0x3f7dbe16,0x3f7dbe16,0xbf673edb,0xbf673edb,0x3f09bf58,0xbf093f58,0xbe893f77,0x3e89bf77,
0x3f80,0x3f80,0xbf753e95,0xbf753e95,0x3f733ea1,0xbf73bea1,0xbcc93f80,0x3cc9bf80,0x3f18bf4e,0x3f18bf4e,0x3f713eac,0x3f713eac,0xbf13bf51,0x3f133f51,0x3f1dbf4a,0xbf1d3f4a,
0x3f80,0x3f80,0x3e953f75,0x3e953f75,0x3f7fbd97,0xbf7f3d97,0x3f6fbeb8,0xbf6f3eb8,0xbe16bf7d,0xbe16bf7d,0xbedbbf67,0xbedbbf67,0xbf7a3e60,0x3f7abe60,0xbf5f3efc,0x3f5fbefc,
0x3f80,0x3f80,0x3f75be95,0x3f75be95,0x3f65bee6,0xbf653ee6,0xbf31bf39,0x3f313f39,0xbf4ebf18,0xbf4ebf18,0xbeac3f71,0xbeac3f71,0xbe2f3f7c,0x3e2fbf7c,0x3f7ebdfb,0xbf7e3dfb,
0x3f80,0x3f80,0xbe95bf75,0xbe95bf75,0x3f27bf42,0xbf273f42,0xbecf3f6a,0x3ecfbf6a,0xbf7d3e16,0xbf7d3e16,0x3f67bedb,0x3f67bedb,0x3f583f09,0xbf58bf09,0xbf77be89,0x3f773e89,
0x3f80,0x3f80,0xbf753e95,0xbf753e95,0x3ea1bf73,0xbea13f73,0x3f803cc9,0xbf80bcc9,0xbf183f4e,0xbf183f4e,0xbf71beac,0xbf71beac,0x3f51bf13,0xbf513f13,0x3f4a3f1d,0xbf4abf1d,
0x3f0e3f55,0x3f0e3f55,0x3f463f22,0x3f463f22,0x3f1d3f4a,0xbf1dbf4a,0x3f513f13,0xbf51bf13,0x3f2c3f3e,0x3f2c3f3e,0x3f5c3f04,0x3f5c3f04,0x3f393f31,0xbf39bf31,0x3f653ee6,0xbf65bee6,
0xbf0ebf55,0xbf0ebf55,0xbf223f46,0xbf223f46,0xbf5fbefc,0x3f5f3efc,0xbe603f7a,0x3e60bf7a,0xbf80bd49,0xbf80bd49,0x3e793f78,0x3e793f78,0xbf6a3ecf,0x3f6abecf,0x3f273f42,0xbf27bf42,
0x3f0e3f55,0x3f0e3f55,0xbf46bf22,0xbf46bf22,0x3f7e3dfb,0xbf7ebdfb,0xbf7c3e2f,0x3f7cbe2f,0x3f3ebf2c,0x3f3ebf2c,0xbf043f5c,0xbf043f5c,0xbcc9bf80,0x3cc93f80,0x3ea13f73,0xbea1bf73,
0xbf0ebf55,0xbf0ebf55,0x3f22bf46,0x3f22bf46,0xbf773e89,0x3f77be89,0xbf09bf58,0x3f093f58,0xbd493f80,0xbd493f80,0xbf783e79,0xbf783e79,0x3f6f3eb8,0xbf6fbeb8,0xbd973f7f,0x3d97bf7f,
0x3f0e3f55,0x3f0e3f55,0x3f463f22,0x3f463f22,0x3f4abf1d,0xbf4a3f1d,0x3f13bf51,0xbf133f51,0xbf2cbf3e,0xbf2cbf3e,0xbf5cbf04,0xbf5cbf04,0xbf313f39,0x3f31bf39,0xbee63f65,0x3ee6bf65,
0xbf0ebf55,0xbf0ebf55,0xbf223f46,0xbf223f46,0xbefc3f5f,0x3efcbf5f,0x3f7a3e60,0xbf7abe60,0x3f803d49,0x3f803d49,0xbe79bf78,0xbe79bf78,0xbecfbf6a,0x3ecf3f6a,0xbf423f27,0x3f42bf27,
0x3f0e3f55,0x3f0e3f55,0xbf46bf22,0xbf46bf22,0x3dfbbf7e,0xbdfb3f7e,0x3e2f3f7c,0xbe2fbf7c,0xbf3e3f2c,0xbf3e3f2c,0x3f04bf5c,0x3f04bf5c,0x3f80bcc9,0xbf803cc9,0xbf733ea1,0x3f73bea1,
0xbf0ebf55,0xbf0ebf55,0x3f22bf46,0x3f22bf46,0x3e893f77,0xbe89bf77,0xbf583f09,0x3f58bf09,0x3d49bf80,0x3d49bf80,0x3f78be79,0x3f78be79,0xbeb83f6f,0x3eb8bf6f,0xbf7fbd97,0x3f7f3d97,
0x3f800000,0x3f800000,0x3f75be95,0x3f75be95,0x3f7fbd97,0xbf7f3d97,0x3f6fbeb8,0xbf6f3eb8,0x3f7dbe16,0x3f7dbe16,0x3f67bedb,0x3f67bedb,0x3f7abe60,0xbf7a3e60,0x3f5fbefc,0xbf5f3efc,
0x3f800000,0x3f800000,0xbe95bf75,0xbe95bf75,0x3f65bee6,0xbf653ee6,0xbf31bf39,0x3f313f39,0x3f18bf4e,0x3f18bf4e,0xbf71beac,0xbf71beac,0x3e2fbf7c,0xbe2f3f7c,0xbf7e3dfb,0x3f7ebdfb,
0x3f800000,0x3f800000,0xbf753e95,0xbf753e95,0x3f27bf42,0xbf273f42,0xbecf3f6a,0x3ecfbf6a,0xbe16bf7d,0xbe16bf7d,0x3edb3f67,0x3edb3f67,0xbf58bf09,0x3f583f09,0x3f773e89,0xbf77be89,
0x3f800000,0x3f800000,0x3e953f75,0x3e953f75,0x3ea1bf73,0xbea13f73,0x3f803cc9,0xbf80bcc9,0xbf4ebf18,0xbf4ebf18,0x3eacbf71,0x3eacbf71,0xbf513f13,0x3f51bf13,0xbf4abf1d,0x3f4a3f1d,
0x3f800000,0x3f800000,0x3f75be95,0x3f75be95,0xbd97bf7f,0x3d973f7f,0xbeb8bf6f,0x3eb83f6f,0xbf7d3e16,0xbf7d3e16,0xbf673edb,0xbf673edb,0x3e603f7a,0xbe60bf7a,0x3efc3f5f,0xbefcbf5f,
0x3f800000,0x3f800000,0xbe95bf75,0xbe95bf75,0xbee6bf65,0x3ee63f65,0xbf393f31,0x3f39bf31,0xbf183f4e,0xbf183f4e,0x3f713eac,0x3f713eac,0x3f7c3e2f,0xbf7cbe2f,0xbdfbbf7e,0x3dfb3f7e,
0x3f800000,0x3f800000,0xbf753e95,0xbf753e95,0xbf42bf27,0x3f423f27,0x3f6a3ecf,0xbf6abecf,0x3e163f7d,0x3e163f7d,0xbedbbf67,0xbedbbf67,0x3f09bf58,0xbf093f58,0xbe893f77,0x3e89bf77,
0x3f800000,0x3f800000,0x3e953f75,0x3e953f75,0xbf73bea1,0x3f733ea1,0x3cc9bf80,0xbcc93f80,0x3f4e3f18,0x3f4e3f18,0xbeac3f71,0xbeac3f71,0xbf13bf51,0x3f133f51,0x3f1dbf4a,0xbf1d3f4a,
0x3f55bf0e,0x3f55bf0e,0x3f22bf46,0x3f22bf46,0x3f4abf1d,0xbf4a3f1d,0x3f13bf51,0xbf133f51,0x3f3ebf2c,0x3f3ebf2c,0x3f04bf5c,0x3f04bf5c,0x3f31bf39,0xbf313f39,0x3ee6bf65,0xbee63f65,
0xbf553f0e,0xbf553f0e,0x3f463f22,0x3f463f22,0xbefc3f5f,0x3efcbf5f,0x3f7a3e60,0xbf7abe60,0xbd493f80,0xbd493f80,0x3f78be79,0x3f78be79,0x3ecf3f6a,0xbecfbf6a,0x3f42bf27,0xbf423f27,
0x3f55bf0e,0x3f55bf0e,0xbf223f46,0xbf223f46,0x3dfbbf7e,0xbdfb3f7e,0x3e2f3f7c,0xbe2fbf7c,0xbf2cbf3e,0xbf2cbf3e,0x3f5c3f04,0x3f5c3f04,0xbf803cc9,0x3f80bcc9,0x3f73bea1,0xbf733ea1,
0xbf553f0e,0xbf553f0e,0xbf46bf22,0xbf46bf22,0x3e893f77,0xbe89bf77,0xbf583f09,0x3f58bf09,0x3f803d49,0x3f803d49,0x3e793f78,0x3e793f78,0x3eb8bf6f,0xbeb83f6f,0x3f7f3d97,0xbf7fbd97,
0x3f55bf0e,0x3f55bf0e,0x3f22bf46,0x3f22bf46,0xbf1dbf4a,0x3f1d3f4a,0xbf51bf13,0x3f513f13,0xbf3e3f2c,0xbf3e3f2c,0xbf043f5c,0xbf043f5c,0x3f393f31,0xbf39bf31,0x3f653ee6,0xbf65bee6,
0xbf553f0e,0xbf553f0e,0x3f463f22,0x3f463f22,0x3f5f3efc,0xbf5fbefc,0x3e60bf7a,0xbe603f7a,0x3d49bf80,0x3d49bf80,0xbf783e79,0xbf783e79,0xbf6a3ecf,0x3f6abecf,0x3f273f42,0xbf27bf42,
0x3f55bf0e,0x3f55bf0e,0xbf223f46,0xbf223f46,0xbf7ebdfb,0x3f7e3dfb,0x3f7cbe2f,0xbf7c3e2f,0x3f2c3f3e,0x3f2c3f3e,0xbf5cbf04,0xbf5cbf04,0xbcc9bf80,0x3cc93f80,0x3ea13f73,0xbea1bf73,
0xbf553f0e,0xbf553f0e,0xbf46bf22,0xbf46bf22,0x3f77be89,0xbf773e89,0x3f093f58,0xbf09bf58,0xbf80bd49,0xbf80bd49,0xbe79bf78,0xbe79bf78,0x3f6f3eb8,0xbf6fbeb8,0xbd973f7f,0x3d97bf7f,
0x3f803f80,0xbf553f55,0x3f803f80,0xbf553f55,0x3f803f80,0xbf553f55,0x3f803f80,0xbf553f55,0x3f803f80,0xbf553f55,0x3f803f80,0xbf553f55,0x3f803f80,0xbf553f55,0x3f803f80,0xbf553f55,
0x3f653f7f,0xbefc3f4a,0xbf65bf7f,0x3efcbf4a,0x3ea13f27,0x3e893dfb,0xbea1bf27,0xbe89bdfb,0xbee6bd97,0x3f5fbf1d,0x3ee63d97,0xbf5f3f1d,0xbf73bf42,0x3f77bf7e,0x3f733f42,0xbf773f7e,
0x3f183f7d,0xbd493f3e,0x3f183f7d,0xbd493f3e,0xbf4ebe16,0x3f80bf2c,0xbf4ebe16,0x3f80bf2c,0xbf18bf7d,0x3d49bf3e,0xbf18bf7d,0x3d49bf3e,0x3f4e3e16,0xbf803f2c,0x3f4e3e16,0xbf803f2c,
0x3e2f3f7a,0x3ecf3f31,0xbe2fbf7a,0xbecfbf31,0xbf51bf58,0x3eb8bf80,0x3f513f58,0xbeb83f80,0x3f7c3e60,0xbf6a3f39,0xbf7cbe60,0x3f6abf39,0xbf133f09,0x3f6fbcc9,0x3f13bf09,0xbf6f3cc9,
0xbe953f75,0x3f463f22,0xbe953f75,0x3f463f22,0x3e95bf75,0xbf46bf22,0x3e95bf75,0xbf46bf22,0xbe953f75,0x3f463f22,0xbe953f75,0x3f463f22,0x3e95bf75,0xbf46bf22,0x3e95bf75,0xbf46bf22,
0xbf313f6f,0x3f7a3f13,0x3f31bf6f,0xbf7abf13,0x3f80becf,0xbf583e2f,0xbf803ecf,0x3f58be2f,0xbf39beb8,0x3e60bf51,0x3f393eb8,0xbe603f51,0x3cc93f6a,0x3f093f7c,0xbcc9bf6a,0xbf09bf7c,
0xbf713f67,0x3f783f04,0xbf713f67,0x3f783f04,0x3eac3edb,0x3e793f5c,0x3eac3edb,0x3e793f5c,0x3f71bf67,0xbf78bf04,0x3f71bf67,0xbf78bf04,0xbeacbedb,0xbe79bf5c,0xbeacbedb,0xbe79bf5c,
0xbf7e3f5f,0x3f423ee6,0x3f7ebf5f,0xbf42bee6,0xbf4a3f77,0x3f7f3f73,0x3f4abf77,0xbf7fbf73,0xbdfb3efc,0x3f273f65,0x3dfbbefc,0xbf27bf65,0x3f1dbe89,0xbd973ea1,0xbf1d3e89,0x3d97bea1,
0,0xbf0e3f0e,0,0xbf0e3f0e,0,0xbf0e3f0e,0,0xbf0e3f0e,0,0xbf0e3f0e,0,0xbf0e3f0e,0,0xbf0e3f0e,0,0xbf0e3f0e,
0x3ee63d97,0xbf5f3f1d,0xbee6bd97,0x3f5fbf1d,0x3f733f42,0xbf773f7e,0xbf73bf42,0x3f77bf7e,0x3f653f7f,0xbefc3f4a,0xbf65bf7f,0x3efcbf4a,0x3ea13f27,0x3e893dfb,0xbea1bf27,0xbe89bdfb,
0x3f4e3e16,0xbf803f2c,0x3f4e3e16,0xbf803f2c,0x3f183f7d,0xbd493f3e,0x3f183f7d,0xbd493f3e,0xbf4ebe16,0x3f80bf2c,0xbf4ebe16,0x3f80bf2c,0xbf18bf7d,0x3d49bf3e,0xbf18bf7d,0x3d49bf3e,
0x3f7c3e60,0xbf6a3f39,0xbf7cbe60,0x3f6abf39,0xbf133f09,0x3f6fbcc9,0x3f13bf09,0xbf6f3cc9,0xbe2fbf7a,0xbecfbf31,0x3e2f3f7a,0x3ecf3f31,0x3f513f58,0xbeb83f80,0xbf51bf58,0x3eb8bf80,
0x3f753e95,0xbf223f46,0x3f753e95,0xbf223f46,0xbf75be95,0x3f22bf46,0xbf75be95,0x3f22bf46,0x3f753e95,0xbf223f46,0x3f753e95,0xbf223f46,0xbf75be95,0x3f22bf46,0xbf75be95,0x3f22bf46,
0x3f393eb8,0xbe603f51,0xbf39beb8,0x3e60bf51,0xbcc9bf6a,0xbf09bf7c,0x3cc93f6a,0x3f093f7c,0xbf313f6f,0x3f7a3f13,0x3f31bf6f,0xbf7abf13,0x3f80becf,0xbf583e2f,0xbf803ecf,0x3f58be2f,
0x3eac3edb,0x3e793f5c,0x3eac3edb,0x3e793f5c,0x3f71bf67,0xbf78bf04,0x3f71bf67,0xbf78bf04,0xbeacbedb,0xbe79bf5c,0xbeacbedb,0xbe79bf5c,0xbf713f67,0x3f783f04,0xbf713f67,0x3f783f04,
0xbdfb3efc,0x3f273f65,0x3dfbbefc,0xbf27bf65,0x3f1dbe89,0xbd973ea1,0xbf1d3e89,0x3d97bea1,0x3f7ebf5f,0xbf42bee6,0xbf7e3f5f,0x3f423ee6,0x3f4abf77,0xbf7fbf73,0xbf4a3f77,0x3f7f3f73,
0,0x3f0ebf0e,0,0x3f0ebf0e,0,0x3f0ebf0e,0,0x3f0ebf0e,0,0x3f0ebf0e,0,0x3f0ebf0e,0,0x3f0ebf0e,0,0x3f0ebf0e,
0xbee6bd97,0x3f5fbf1d,0x3ee63d97,0xbf5f3f1d,0xbf73bf42,0x3f77bf7e,0x3f733f42,0xbf773f7e,0xbf65bf7f,0x3efcbf4a,0x3f653f7f,0xbefc3f4a,0xbea1bf27,0xbe89bdfb,0x3ea13f27,0x3e893dfb,
0xbf4ebe16,0x3f80bf2c,0xbf4ebe16,0x3f80bf2c,0xbf18bf7d,0x3d49bf3e,0xbf18bf7d,0x3d49bf3e,0x3f4e3e16,0xbf803f2c,0x3f4e3e16,0xbf803f2c,0x3f183f7d,0xbd493f3e,0x3f183f7d,0xbd493f3e,
0xbf7cbe60,0x3f6abf39,0x3f7c3e60,0xbf6a3f39,0x3f13bf09,0xbf6f3cc9,0xbf133f09,0x3f6fbcc9,0x3e2f3f7a,0x3ecf3f31,0xbe2fbf7a,0xbecfbf31,0xbf51bf58,0x3eb8bf80,0x3f513f58,0xbeb83f80,
0xbf75be95,0x3f22bf46,0xbf75be95,0x3f22bf46,0x3f753e95,0xbf223f46,0x3f753e95,0xbf223f46,0xbf75be95,0x3f22bf46,0xbf75be95,0x3f22bf46,0x3f753e95,0xbf223f46,0x3f753e95,0xbf223f46,
0xbf39beb8,0x3e60bf51,0x3f393eb8,0xbe603f51,0x3cc93f6a,0x3f093f7c,0xbcc9bf6a,0xbf09bf7c,0x3f31bf6f,0xbf7abf13,0xbf313f6f,0x3f7a3f13,0xbf803ecf,0x3f58be2f,0x3f80becf,0xbf583e2f,
0xbeacbedb,0xbe79bf5c,0xbeacbedb,0xbe79bf5c,0xbf713f67,0x3f783f04,0xbf713f67,0x3f783f04,0x3eac3edb,0x3e793f5c,0x3eac3edb,0x3e793f5c,0x3f71bf67,0xbf78bf04,0x3f71bf67,0xbf78bf04,
0x3dfbbefc,0xbf27bf65,0xbdfb3efc,0x3f273f65,0xbf1d3e89,0x3d97bea1,0x3f1dbe89,0xbd973ea1,0xbf7e3f5f,0x3f423ee6,0x3f7ebf5f,0xbf42bee6,0xbf4a3f77,0x3f7f3f73,0x3f4abf77,0xbf7fbf73,
0x3f800000,0x3f7ffd39,0x3f800000,0x3f6b99fb,0x3f7ff4e6,0x3f7fe705,0x3f31a81d,0x3eb6ccc3,0x3f7fd397,0x3f7fba9e,0xbd16c32c,0xbed97cb9,0x3f7f9c18,0x3f7f7808,0xbf3ebc1b,0xbf725470,
0x3f800000,0x3f7f90b1,0x3f800000,0x3f666771,0x3f7e4323,0x3f7c187a,0x3f1ebc12,0x3e5d4b1a,0x3f791298,0x3f75341d,0xbe6c9a7f,0xbf21cbfb,0x3f708066,0x3f6afb8c,0xbf6816a8,0xbf7ff84a,
0x3f800000,0x3f7e868b,0x3f800000,0x3f60a6cf,0x3f7a1e84,0x3f72d4eb,0x3f0a48ad,0x3d9064b4,0x3f68bf3c,0x3f5bfb34,0xbed53641,0xbf4d26fd,0x3f4cae79,0x3f3b0629,0xbf7d7474,0xbf6faf1b,
0x3f800000,0x3f7cdf6c,0x3f800000,0x3f5a5ba0,0x3f73913f,0x3f644fac,0x3ee900b7,0xbd9cecf9,0x3f4f7a1f,0x3f3592e7,0xbf15f6d9,0xbf6c3624,0x3f173c07,0x3eea6681,0xbf7cfe73,0xbf436051,
0x3f800000,0x3f7a9c59,0x3f800000,0x3f5389c7,0x3f6aab7b,0x3f50d937,0x3ebb31a0,0xbe636c83,0x3f2e3bde,0x3f044889,0xbf3b8f3b,0xbf7d1cdd,0x3ea986c4,0x3e06b26e,0xbf66becc,0xbf003a06,
0x3f800000,0x3f77beb7,0x3f800000,0x3f4c3578,0x3f5f8327,0x3f38dd65,0x3e8b9507,0xbeb9bb1e,0x3f064b82,0x3e9620d2,0xbf59f26a,0xbf7ed7d4,0x3d2fe007,0xbe57278f,0xbf3ca003,0xbe3857ec,
0x3f800000,0x3f74484b,0x3f800000,0x3f446337,0x3f5233c6,0x3f1ce11f,0x3e354098,0xbefdbabb,0x3eb263ef,0x3d55880e,0xbf6ff573,0xbf714c7a,0xbe7ee6e1,0xbf06f686,0xbf0242b1,0x3e25c58c,
0x3f800000,0x3f703b37,0x3f800000,0x3f3c17d9,0x3f42de29,0x3efafef7,0x3da3308c,0xbf1e1e22,0x3e22abb6,0xbe44b0b9,0xbf7cbfc9,0xbf554aa4,0xbf04f484,0xbf485bca,0xbe72b651,0x3ef840c8,
0,0x3c16cb58,0,0x3ec8477c,0x3c96c9b6,0x3ce22a7a,0x3f385216,0x3f6f20b0,0x3d16c32c,0x3d3c6dd5,0x3f7fd397,0x3f67c187,0x3d621469,0x3d83db0a,0x3f2ac082,0x3ea5129f,
0,0x3d6ea038,0,0x3edf28a9,0x3dee3876,0x3e3228d4,0x3f48d8b3,0x3f79f35e,0x3e6c9a7f,0x3e931f35,0x3f791298,0x3f466354,0x3eaf713a,0x3ecb2aae,0x3ed8106b,0xbc7b514b,
0,0x3ddb7d37,0,0x3ef58035,0x3e5a3997,0x3ea21887,0x3f577026,0x3f7f5ce9,0x3ed53641,0x3f02ef9f,0x3f68bf3c,0x3f19210f,0x3f19c200,0x3f2ecef7,0x3e1008b7,0xbeb3dca5,
0,0x3e1f917b,0,0x3f05a02c,0x3e9d9e78,0x3ee79a5d,0x3f63f473,0x3f7f3f54,0x3f15f6d9,0x3f34768f,0x3f4f7a1f,0x3ec5625c,0x3f4e8d90,0x3f6398ac,0xbe1c76de,0xbf256bcb,
0,0x3e5101f1,0,0x3f102dd5,0x3ecc9b8b,0x3f140c5f,0x3f6e46be,0x3f799b43,0x3f3b8f3b,0x3f5b2c79,0x3f2e3bde,0x3e195be0,0x3f718f57,0x3f7dc68c,0xbeddbe79,0xbf5d924d,
0,0x3e80f8c0,0,0x3f1a6293,0x3ef9a02d,0x3f311722,0x3f764d97,0x3f6e8ff8,0x3f59f26a,0x3f74bf62,0x3f064b82,0xbdc27c39,0x3f7fc38f,0x3f7a4910,0xbf2d1469,0xbf7bd14d,
0,0x3e9920fe,0,0x3f24381a,0x3f121eb0,0x3f4a4c87,0x3f7bf531,0x3f5e5aa6,0x3f6ff573,0x3f7fa6e3,0x3eb263ef,0xbeab0201,0x3f77f110,0x3f5988ad,0xbf5c61c7,0xbf7c9f8a,
0,0x3eb0eacb,0,0x3f2da859,0x3f26050a,0x3f5f20db,0x3f7f2f9d,0x3f495521,0x3f7cbfc9,0x3f7b3bab,0x3e22abb6,0xbf0d9281,0x3f5ac450,0x3f1f599f,0xbf78b47b,0xbf5fe4e9,
0x35cccccd,0x35cccccd,0x35cccccd,0x35cccccd,0x35cccccd,0x35cccccd,0x35cccccd,0x35cccccd,0x35cccccd,0x35cccccd,0x35cccccd,0x35cccccd,0x35cccccd,0x35cccccd,0x35cccccd,0x35cccccd,
0x35ccca94,0x35cc73c1,0x35bc7b2f,0x35b852c1,0x35cb9ed5,0x35ca4c56,0x35b3b8a6,0x35aeafb3,0x35c87d14,0x35c6322c,0x35a93b06,0x35a35df9,0x35c36d09,0x35c02f5f,0x359d1c2c,0x3596797a,
0x35ccc3eb,0x35cb68e9,0x358e2017,0x357df9b6,0x35c8186a,0x35c2da99,0x355d4116,0x353a66f9,0x35bbbc62,0x35b2cf52,0x3515c14d,0x34df54d8,0x35a8296b,0x359be4ed,0x3491007a,0x34028d3d,
0x35ccb8d1,0x35c9ad2f,0x35123d69,0x34b108e1,0x35c243ef,0x35b6a623,0x33e70786,0xb3fb14c1,0x35a7142c,0x3593e451,0xb4b5f068,0xb51495b2,0x357b01cb,0x3548cbf9,0xb54afbc9,0xb57cfd04,
0x35cca946,0x35c74213,0xb3713846,0xb4bd4866,0x35ba3296,0x35a5fb4c,0xb52a91ce,0xb56ff15b,0x358b6318,0x3556df37,0xb5960c2f,0xb5ae5b88,0x350eb659,0x348222f8,0xb5bff78f,0xb5ca3307,
0x35cc954b,0x35c429b0,0xb52dfd61,0xb5816ffc,0x35affc2a,0x35914253,0xb5a41f31,0xb5bcf81d,0x3553a742,0x34f03484,0xb5ca7d7e,0xb5cbdfdd,0x33aad33e,0xb49d5a2e,0xb5c109fb,0xb5aaa21d,
0x35cc7ce0,0x35c066b8,0xb598967c,0xb5b9abba,0x35a3bec8,0x3571f9a5,0xb5cac390,0xb5ca6529,0x35079f03,0x338cb338,0xb5b898a3,0xb596e669,0xb4cbebe7,0xb554ba6c,0xb5506ab5,0xb4c22b74,
0x35cc6006,0x35bbfc70,0xb5c1dd26,0xb5ccc6a2,0x35959e88,0x353b8534,0xb5bfbf49,0xb59c4d0e,0x345783e3,0xb4ac1fa5,0xb54d29a4,0xb493798a,0xb557f0d6,0xb5a0496e,0x34849e0a,0x35469a3a,
0,0,0,0,0,0,0,0,0,0,0,0,0,0,0,0,
0x3271455a,0x33bee693,0x35203930,0x353286ed,0x342f9760,0x347f4f2b,0x35446691,0x3555cd14,0x34a734c1,0x34ce5acd,0x3566afbb,0x3577041e,0x34f50196,0x350d88a2,0x35836014,0x358aed14,
0x32f142bd,0x343e9392,0x359374de,0x35a0ad5c,0x34ae9479,0x34fc30c0,0x35ac59b8,0x35b65d28,0x3523afa2,0x3547b357,0x35be9eff,0x35c50adf,0x3569cab3,0x3584d0d5,0x35c990f4,0x35cc2618,
0x3334eec8,0x348e8710,0x35bf4d5a,0x35c7f5e5,0x3501ad39,0x3539484b,0x35cc4a54,0x35cc32aa,0x356ce099,0x358dac1c,0x35c7af69,0x35bed993,0x35a1d6d2,0x35b280af,0x35b1e21f,0x35a110e7,
0x33713846,0x34bd4866,0x35cca946,0x35c74213,0x352a91ce,0x356ff15b,0x35ba3296,0x35a5fb4c,0x35960c2f,0x35ae5b88,0x358b6318,0x3556df37,0x35bff78f,0x35ca3307,0x350eb659,0x348222f8,
0x3396be44,0x34eb6521,0x35b9679f,0x359eb5dd,0x35517f65,0x35905ed9,0x357501b2,0x351de84a,0x35af56c7,0x35c3cc4e,0x34755fcc,0xb41b9694,0x35cc8582,0x35c8fc89,0xb508ce67,0xb5628401,
0x33b4dd20,0x350c5a95,0x35889a01,0x352cd9f0,0x35760334,0x35a53e0d,0x34667457,0xb47a57c9,0x35c13f79,0x35cc9c72,0xb531652e,0xb58a76bb,0x35c65a74,0x35af0373,0xb5b04e38,0xb5c6f6c8,
0x33d2f811,0x3522888b,0x35040ee5,0xb2c90dd6,0x358bd8c6,0x35b613bd,0xb50fe3b7,0xb584563c,0x35cb053d,0x35c83a73,0xb5b141d7,0xb5c9743e,0x35ae06f1,0x357ef5cc,0xb5ca193c,0xb5b31d87,
0x3f803f80,0,0,0x3f803f80,0x3f803f80,0,0,0x3f803f80,0x3f803f80,0,0,0x3f803f80,0x3f803f80,0,0,0x3f803f80,
0x3f353f80,0x3f350000,0xbf350000,0x3f353f80,0xbf350000,0x3f353f80,0xbf35bf80,0xbf350000,0xbf35bf80,0xbf350000,0x3f350000,0xbf35bf80,0x3f350000,0xbf35bf80,0x3f353f80,0x3f350000,
0x3f80,0x3f800000,0xbf800000,0x3f80,0xbf80,0xbf800000,0x3f800000,0xbf80,0x3f80,0x3f800000,0xbf800000,0x3f80,0xbf80,0xbf800000,0x3f800000,0xbf80,
0xbf353f80,0x3f350000,0xbf350000,0xbf353f80,0x3f350000,0x3f35bf80,0xbf353f80,0x3f350000,0x3f35bf80,0xbf350000,0x3f350000,0x3f35bf80,0xbf350000,0xbf353f80,0x3f35bf80,0xbf350000,
0xbf803f80,0,0,0xbf803f80,0xbf803f80,0,0,0xbf803f80,0xbf803f80,0,0,0xbf803f80,0xbf803f80,0,0,0xbf803f80,
0xbf353f80,0xbf350000,0x3f350000,0xbf353f80,0x3f350000,0xbf353f80,0x3f35bf80,0x3f350000,0x3f35bf80,0x3f350000,0xbf350000,0x3f35bf80,0xbf350000,0x3f35bf80,0xbf353f80,0xbf350000,
0x3f80,0xbf800000,0x3f800000,0x3f80,0xbf80,0x3f800000,0xbf800000,0xbf80,0x3f80,0xbf800000,0x3f800000,0x3f80,0xbf80,0x3f800000,0xbf800000,0xbf80,
0x3f353f80,0xbf350000,0x3f350000,0x3f353f80,0xbf350000,0xbf35bf80,0x3f353f80,0xbf350000,0xbf35bf80,0x3f350000,0xbf350000,0xbf35bf80,0x3f350000,0x3f353f80,0xbf35bf80,0x3f350000,
0x3f80,0x3f80,0x3ec43f6d,0x3ec43f6d,0x3dc93f7f,0xbdc9bf7f,0x3ef13f62,0xbef1bf62,0x3e483f7b,0x3e483f7b,0x3f0e3f55,0x3f0e3f55,0x3e953f75,0xbe95bf75,0x3f223f46,0xbf22bf46,
0x3f80,0x3f80,0x3f6dbec4,0x3f6dbec4,0x3ef13f62,0xbef1bf62,0x3f22bf46,0xbf223f46,0x3f553f0e,0x3f553f0e,0x3e48bf7b,0x3e48bf7b,0x3f7f3dc9,0xbf7fbdc9,0xbe95bf75,0x3e953f75,
0x3f80,0x3f80,0xbec4bf6d,0xbec4bf6d,0x3f463f22,0xbf46bf22,0xbf75be95,0x3f753e95,0x3f7bbe48,0x3f7bbe48,0xbf553f0e,0xbf553f0e,0x3ef1bf62,0xbef13f62,0xbdc93f7f,0x3dc9bf7f,
0x3f80,0x3f80,0xbf6d3ec4,0xbf6d3ec4,0x3f753e95,0xbf75be95,0x3dc93f7f,0xbdc9bf7f,0x3f0ebf55,0x3f0ebf55,0x3f7b3e48,0x3f7b3e48,0xbf22bf46,0x3f223f46,0x3ef1bf62,0xbef13f62,
0x3f80,0x3f80,0x3ec43f6d,0x3ec43f6d,0x3f7fbdc9,0xbf7f3dc9,0x3f62bef1,0xbf623ef1,0xbe48bf7b,0xbe48bf7b,0xbf0ebf55,0xbf0ebf55,0xbf753e95,0x3f75be95,0xbf463f22,0x3f46bf22,
0x3f80,0x3f80,0x3f6dbec4,0x3f6dbec4,0x3f62bef1,0xbf623ef1,0xbf46bf22,0x3f463f22,0xbf55bf0e,0xbf55bf0e,0xbe483f7b,0xbe483f7b,0xbdc93f7f,0x3dc9bf7f,0x3f75be95,0xbf753e95,
0x3f80,0x3f80,0xbec4bf6d,0xbec4bf6d,0x3f22bf46,0xbf223f46,0xbe953f75,0x3e95bf75,0xbf7b3e48,0xbf7b3e48,0x3f55bf0e,0x3f55bf0e,0x3f623ef1,0xbf62bef1,0xbf7fbdc9,0x3f7f3dc9,
0x3f80,0x3f80,0xbf6d3ec4,0xbf6d3ec4,0x3e95bf75,0xbe953f75,0x3f7fbdc9,0xbf7f3dc9,0xbf0e3f55,0xbf0e3f55,0xbf7bbe48,0xbf7bbe48,0x3f46bf22,0xbf463f22,0x3f623ef1,0xbf62bef1,
0x3f353f35,0x3f353f35,0x3f6d3ec4,0x3f6d3ec4,0x3f463f22,0xbf46bf22,0x3f753e95,0xbf75be95,0x3f553f0e,0x3f553f0e,0x3f7b3e48,0x3f7b3e48,0x3f623ef1,0xbf62bef1,0x3f7f3dc9,0xbf7fbdc9,
0xbf35bf35,0xbf35bf35,0xbec43f6d,0xbec43f6d,0xbf75be95,0x3f753e95,0x3dc93f7f,0xbdc9bf7f,0xbf7b3e48,0xbf7b3e48,0x3f0e3f55,0x3f0e3f55,0xbf463f22,0x3f46bf22,0x3f623ef1,0xbf62bef1,
0x3f353f35,0x3f353f35,0xbf6dbec4,0xbf6dbec4,0x3f7fbdc9,0xbf7f3dc9,0xbf623ef1,0x3f62bef1,0x3f0ebf55,0x3f0ebf55,0xbe483f7b,0xbe483f7b,0xbe95bf75,0x3e953f75,0x3f223f46,0xbf22bf46,
0xbf35bf35,0xbf35bf35,0x3ec4bf6d,0x3ec4bf6d,0xbf623ef1,0x3f62bef1,0xbf46bf22,0x3f463f22,0x3e483f7b,0x3e483f7b,0xbf553f0e,0xbf553f0e,0x3f7f3dc9,0xbf7fbdc9,0x3e953f75,0xbe95bf75,
0x3f353f35,0x3f353f35,0x3f6d3ec4,0x3f6d3ec4,0x3f22bf46,0xbf223f46,0x3e95bf75,0xbe953f75,0xbf55bf0e,0xbf55bf0e,0xbf7bbe48,0xbf7bbe48,0xbef13f62,0x3ef1bf62,0xbdc93f7f,0x3dc9bf7f,
0xbf35bf35,0xbf35bf35,0xbec43f6d,0xbec43f6d,0xbe953f75,0x3e95bf75,0x3f7fbdc9,0xbf7f3dc9,0x3f7bbe48,0x3f7bbe48,0xbf0ebf55,0xbf0ebf55,0xbf22bf46,0x3f223f46,0xbef13f62,0x3ef1bf62,
0x3f353f35,0x3f353f35,0xbf6dbec4,0xbf6dbec4,0xbdc9bf7f,0x3dc93f7f,0x3ef13f62,0xbef1bf62,0xbf0e3f55,0xbf0e3f55,0x3e48bf7b,0x3e48bf7b,0x3f75be95,0xbf753e95,0xbf463f22,0x3f46bf22,
0xbf35bf35,0xbf35bf35,0x3ec4bf6d,0x3ec4bf6d,0x3ef13f62,0xbef1bf62,0xbf223f46,0x3f22bf46,0xbe48bf7b,0xbe48bf7b,0x3f55bf0e,0x3f55bf0e,0xbdc93f7f,0x3dc9bf7f,0xbf753e95,0x3f75be95,
0x3f800000,0x3f800000,0x3f6dbec4,0x3f6dbec4,0x3f7fbdc9,0xbf7f3dc9,0x3f62bef1,0xbf623ef1,0x3f7bbe48,0x3f7bbe48,0x3f55bf0e,0x3f55bf0e,0x3f75be95,0xbf753e95,0x3f46bf22,0xbf463f22,
0x3f800000,0x3f800000,0xbec4bf6d,0xbec4bf6d,0x3f62bef1,0xbf623ef1,0xbf46bf22,0x3f463f22,0x3f0ebf55,0x3f0ebf55,0xbf7bbe48,0xbf7bbe48,0x3dc9bf7f,0xbdc93f7f,0xbf753e95,0x3f75be95,
0x3f800000,0x3f800000,0xbf6d3ec4,0xbf6d3ec4,0x3f22bf46,0xbf223f46,0xbe953f75,0x3e95bf75,0xbe48bf7b,0xbe48bf7b,0x3f0e3f55,0x3f0e3f55,0xbf62bef1,0x3f623ef1,0x3f7f3dc9,0xbf7fbdc9,
0x3f800000,0x3f800000,0x3ec43f6d,0x3ec43f6d,0x3e95bf75,0xbe953f75,0x3f7fbdc9,0xbf7f3dc9,0xbf55bf0e,0xbf55bf0e,0x3e48bf7b,0x3e48bf7b,0xbf463f22,0x3f46bf22,0xbf62bef1,0x3f623ef1,
0x3f800000,0x3f800000,0x3f6dbec4,0x3f6dbec4,0xbdc9bf7f,0x3dc93f7f,0xbef1bf62,0x3ef13f62,0xbf7b3e48,0xbf7b3e48,0xbf553f0e,0xbf553f0e,0x3e953f75,0xbe95bf75,0x3f223f46,0xbf22bf46,
0x3f800000,0x3f800000,0xbec4bf6d,0xbec4bf6d,0xbef1bf62,0x3ef13f62,0xbf223f46,0x3f22bf46,0xbf0e3f55,0xbf0e3f55,0x3f7b3e48,0x3f7b3e48,0x3f7f3dc9,0xbf7fbdc9,0xbe95bf75,0x3e953f75,
0x3f800000,0x3f800000,0xbf6d3ec4,0xbf6d3ec4,0xbf46bf22,0x3f463f22,0x3f753e95,0xbf75be95,0x3e483f7b,0x3e483f7b,0xbf0ebf55,0xbf0ebf55,0x3ef1bf62,0xbef13f62,0xbdc93f7f,0x3dc9bf7f,
0x3f800000,0x3f800000,0x3ec43f6d,0x3ec43f6d,0xbf75be95,0x3f753e95,0xbdc9bf7f,0x3dc93f7f,0x3f553f0e,0x3f553f0e,0xbe483f7b,0xbe483f7b,0xbf22bf46,0x3f223f46,0x3ef1bf62,0xbef13f62,
0x3f35bf35,0x3f35bf35,0x3ec4bf6d,0x3ec4bf6d,0x3f22bf46,0xbf223f46,0x3e95bf75,0xbe953f75,0x3f0ebf55,0x3f0ebf55,0x3e48bf7b,0x3e48bf7b,0x3ef1bf62,0xbef13f62,0x3dc9bf7f,0xbdc93f7f,
0xbf353f35,0xbf353f35,0x3f6d3ec4,0x3f6d3ec4,0xbe953f75,0x3e95bf75,0x3f7fbdc9,0xbf7f3dc9,0x3e483f7b,0x3e483f7b,0x3f55bf0e,0x3f55bf0e,0x3f223f46,0xbf22bf46,0x3ef1bf62,0xbef13f62,
0x3f35bf35,0x3f35bf35,0xbec43f6d,0xbec43f6d,0xbdc9bf7f,0x3dc93f7f,0x3ef13f62,0xbef1bf62,0xbf55bf0e,0xbf55bf0e,0x3f7b3e48,0x3f7b3e48,0xbf753e95,0x3f75be95,0x3f46bf22,0xbf463f22,
0xbf353f35,0xbf353f35,0xbf6dbec4,0xbf6dbec4,0x3ef13f62,0xbef1bf62,0xbf223f46,0x3f22bf46,0x3f7bbe48,0x3f7bbe48,0x3f0e3f55,0x3f0e3f55,0x3dc9bf7f,0xbdc93f7f,0x3f75be95,0xbf753e95,
0x3f35bf35,0x3f35bf35,0x3ec4bf6d,0x3ec4bf6d,0xbf46bf22,0x3f463f22,0xbf75be95,0x3f753e95,0xbf0e3f55,0xbf0e3f55,0xbe483f7b,0xbe483f7b,0x3f623ef1,0xbf62bef1,0x3f7f3dc9,0xbf7fbdc9,
0xbf353f35,0xbf353f35,0x3f6d3ec4,0x3f6d3ec4,0x3f753e95,0xbf75be95,0xbdc9bf7f,0x3dc93f7f,0xbe48bf7b,0xbe48bf7b,0xbf553f0e,0xbf553f0e,0xbf463f22,0x3f46bf22,0x3f623ef1,0xbf62bef1,
0x3f35bf35,0x3f35bf35,0xbec43f6d,0xbec43f6d,0xbf7f3dc9,0x3f7fbdc9,0x3f62bef1,0xbf623ef1,0x3f553f0e,0x3f553f0e,0xbf7bbe48,0xbf7bbe48,0xbe95bf75,0x3e953f75,0x3f223f46,0xbf22bf46,
0xbf353f35,0xbf353f35,0xbf6dbec4,0xbf6dbec4,0x3f62bef1,0xbf623ef1,0x3f463f22,0xbf46bf22,0xbf7b3e48,0xbf7b3e48,0xbf0ebf55,0xbf0ebf55,0x3f7f3dc9,0xbf7fbdc9,0x3e953f75,0xbe95bf75,
0x3f803f80,0xbf353f35,0x3f803f80,0xbf353f35,0x3f803f80,0xbf353f35,0x3f803f80,0xbf353f35,0x3f803f80,0xbf353f35,0x3f803f80,0xbf353f35,0x3f803f80,0xbf353f35,0x3f803f80,0xbf353f35,
0x3f623f7f,0xbe953f22,0xbf62bf7f,0x3e95bf22,0x3e953f22,0x3ef1bdc9,0xbe95bf22,0xbef13dc9,0xbef1bdc9,0x3f75bf46,0x3ef13dc9,0xbf753f46,0xbf75bf46,0x3f62bf7f,0x3f753f46,0xbf623f7f,
0x3f0e3f7b,0x3e483f0e,0x3f0e3f7b,0x3e483f0e,0xbf55be48,0x3f7bbf55,0xbf55be48,0x3f7bbf55,0xbf0ebf7b,0xbe48bf0e,0xbf0ebf7b,0xbe48bf0e,0x3f553e48,0xbf7b3f55,0x3f553e48,0xbf7b3f55,
0x3dc93f75,0x3f223ef1,0xbdc9bf75,0xbf22bef1,0xbf46bf62,0x3dc9bf75,0x3f463f62,0xbdc93f75,0x3f7f3e95,0xbf463f62,0xbf7fbe95,0x3f46bf62,0xbf223ef1,0x3f7fbe95,0x3f22bef1,0xbf7f3e95,
0xbec43f6d,0x3f6d3ec4,0xbec43f6d,0x3f6d3ec4,0x3ec4bf6d,0xbf6dbec4,0x3ec4bf6d,0xbf6dbec4,0xbec43f6d,0x3f6d3ec4,0xbec43f6d,0x3f6d3ec4,0x3ec4bf6d,0xbf6dbec4,0x3ec4bf6d,0xbf6dbec4,
0xbf463f62,0x3f7f3e95,0x3f46bf62,0xbf7fbe95,0x3f7fbe95,0xbf223ef1,0xbf7f3e95,0x3f22bef1,0xbf22bef1,0xbdc9bf75,0x3f223ef1,0x3dc93f75,0xbdc93f75,0x3f463f62,0x3dc9bf75,0xbf46bf62,
0xbf7b3f55,0x3f553e48,0xbf7b3f55,0x3f553e48,0x3e483f0e,0x3f0e3f7b,0x3e483f0e,0x3f0e3f7b,0x3f7bbf55,0xbf55be48,0x3f7bbf55,0xbf55be48,0xbe48bf0e,0xbf0ebf7b,0xbe48bf0e,0xbf0ebf7b,
0xbf753f46,0x3ef13dc9,0x3f75bf46,0xbef1bdc9,0xbf623f7f,0x3f753f46,0x3f62bf7f,0xbf75bf46,0xbe953f22,0x3f623f7f,0x3e95bf22,0xbf62bf7f,0x3ef1bdc9,0x3e953f22,0xbef13dc9,0xbe95bf22,
0,0xbf353f35,0,0xbf353f35,0,0xbf353f35,0,0xbf353f35,0,0xbf353f35,0,0xbf353f35,0,0xbf353f35,0,0xbf353f35,
0x3ef13dc9,0xbf753f46,0xbef1bdc9,0x3f75bf46,0x3f753f46,0xbf623f7f,0xbf75bf46,0x3f62bf7f,0x3f623f7f,0xbe953f22,0xbf62bf7f,0x3e95bf22,0x3e953f22,0x3ef1bdc9,0xbe95bf22,0xbef13dc9,
0x3f553e48,0xbf7b3f55,0x3f553e48,0xbf7b3f55,0x3f0e3f7b,0x3e483f0e,0x3f0e3f7b,0x3e483f0e,0xbf55be48,0x3f7bbf55,0xbf55be48,0x3f7bbf55,0xbf0ebf7b,0xbe48bf0e,0xbf0ebf7b,0xbe48bf0e,
0x3f7f3e95,0xbf463f62,0xbf7fbe95,0x3f46bf62,0xbf223ef1,0x3f7fbe95,0x3f22bef1,0xbf7f3e95,0xbdc9bf75,0xbf22bef1,0x3dc93f75,0x3f223ef1,0x3f463f62,0xbdc93f75,0xbf46bf62,0x3dc9bf75,
0x3f6d3ec4,0xbec43f6d,0x3f6d3ec4,0xbec43f6d,0xbf6dbec4,0x3ec4bf6d,0xbf6dbec4,0x3ec4bf6d,0x3f6d3ec4,0xbec43f6d,0x3f6d3ec4,0xbec43f6d,0xbf6dbec4,0x3ec4bf6d,0xbf6dbec4,0x3ec4bf6d,
0x3f223ef1,0x3dc93f75,0xbf22bef1,0xbdc9bf75,0x3dc9bf75,0xbf46bf62,0xbdc93f75,0x3f463f62,0xbf463f62,0x3f7f3e95,0x3f46bf62,0xbf7fbe95,0x3f7fbe95,0xbf223ef1,0xbf7f3e95,0x3f22bef1,
0x3e483f0e,0x3f0e3f7b,0x3e483f0e,0x3f0e3f7b,0x3f7bbf55,0xbf55be48,0x3f7bbf55,0xbf55be48,0xbe48bf0e,0xbf0ebf7b,0xbe48bf0e,0xbf0ebf7b,0xbf7b3f55,0x3f553e48,0xbf7b3f55,0x3f553e48,
0xbe953f22,0x3f623f7f,0x3e95bf22,0xbf62bf7f,0x3ef1bdc9,0x3e953f22,0xbef13dc9,0xbe95bf22,0x3f75bf46,0xbef1bdc9,0xbf753f46,0x3ef13dc9,0x3f62bf7f,0xbf75bf46,0xbf623f7f,0x3f753f46,
0,0x3f35bf35,0,0x3f35bf35,0,0x3f35bf35,0,0x3f35bf35,0,0x3f35bf35,0,0x3f35bf35,0,0x3f35bf35,0,0x3f35bf35,
0xbef1bdc9,0x3f75bf46,0x3ef13dc9,0xbf753f46,0xbf75bf46,0x3f62bf7f,0x3f753f46,0xbf623f7f,0xbf62bf7f,0x3e95bf22,0x3f623f7f,0xbe953f22,0xbe95bf22,0xbef13dc9,0x3e953f22,0x3ef1bdc9,
0xbf55be48,0x3f7bbf55,0xbf55be48,0x3f7bbf55,0xbf0ebf7b,0xbe48bf0e,0xbf0ebf7b,0xbe48bf0e,0x3f553e48,0xbf7b3f55,0x3f553e48,0xbf7b3f55,0x3f0e3f7b,0x3e483f0e,0x3f0e3f7b,0x3e483f0e,
0xbf7fbe95,0x3f46bf62,0x3f7f3e95,0xbf463f62,0x3f22bef1,0xbf7f3e95,0xbf223ef1,0x3f7fbe95,0x3dc93f75,0x3f223ef1,0xbdc9bf75,0xbf22bef1,0xbf46bf62,0x3dc9bf75,0x3f463f62,0xbdc93f75,
0xbf6dbec4,0x3ec4bf6d,0xbf6dbec4,0x3ec4bf6d,0x3f6d3ec4,0xbec43f6d,0x3f6d3ec4,0xbec43f6d,0xbf6dbec4,0x3ec4bf6d,0xbf6dbec4,0x3ec4bf6d,0x3f6d3ec4,0xbec43f6d,0x3f6d3ec4,0xbec43f6d,
0xbf22bef1,0xbdc9bf75,0x3f223ef1,0x3dc93f75,0xbdc93f75,0x3f463f62,0x3dc9bf75,0xbf46bf62,0x3f46bf62,0xbf7fbe95,0xbf463f62,0x3f7f3e95,0xbf7f3e95,0x3f22bef1,0x3f7fbe95,0xbf223ef1,
0xbe48bf0e,0xbf0ebf7b,0xbe48bf0e,0xbf0ebf7b,0xbf7b3f55,0x3f553e48,0xbf7b3f55,0x3f553e48,0x3e483f0e,0x3f0e3f7b,0x3e483f0e,0x3f0e3f7b,0x3f7bbf55,0xbf55be48,0x3f7bbf55,0xbf55be48,
0x3e95bf22,0xbf62bf7f,0xbe953f22,0x3f623f7f,0xbef13dc9,0xbe95bf22,0x3ef1bdc9,0x3e953f22,0xbf753f46,0x3ef13dc9,0x3f75bf46,0xbef1bdc9,0xbf623f7f,0x3f753f46,0x3f62bf7f,0xbf75bf46,
0x3f800000,0x3f7ffb11,0x3f800000,0x3f6b4b0c,0x3f7fec43,0x3f7fd397,0x3f3085bb,0x3eb263ef,0x3f7fb10f,0x3f7f84ab,0xbd48fb30,0xbee0924f,0x3f7f4e6d,0x3f7f0e58,0xbf41d870,0xbf740bdd,
0x3f800000,0x3f7f84ab,0x3f800000,0x3f660f88,0x3f7e1324,0x3f7baccd,0x3f1d7fd1,0x3e541501,0x3f7853f8,0x3f740bdd,0xbe78cfcc,0xbf24d225,0x3f6ed89e,0x3f68bf3c,0xbf6a09a7,0xbf7fd397,
0x3f800000,0x3f7e70b0,0x3f800000,0x3f604621,0x3f79c79d,0x3f721352,0x3f08f59b,0x3d7b2b74,0x3f676bd8,0x3f59f26a,0xbedae880,0xbf4f7a1f,0x3f49d112,0x3f373a23,0xbf7e1324,0xbf6db293,
0x3f800000,0x3f7cbfc9,0x3f800000,0x3f59f26a,0x3f731447,0x3f633c5a,0x3ee63375,0xbdafb680,0x3f4d9f02,0x3f32c8c9,0xbf187fc0,0xbf6db293,0x3f13682a,0x3ee0924f,0xbf7c3b28,0xbf3fc767,
0x3f800000,0x3f7a7302,0x3f800000,0x3f531849,0x3f6a09a7,0x3f4f7a1f,0x3eb8442a,0xbe6c9a7f,0x3f2beb4a,0x3f00e7e4,0xbf3daef9,0xbf7dabcc,0x3ea09ae5,0x3de1bc2e,0xbf64aa59,0xbef6e0cb,
0x3f800000,0x3f778bc5,0x3f800000,0x3f4bbbf8,0x3f5ebe05,0x3f373a23,0x3e888e93,0xbebe1d4a,0x3f039c3d,0x3e8e9a22,0xbf5b941a,0xbf7e70b0,0x3cc90ab0,0xbe6c9a7f,0xbf396842,0xbe22abb6,
0x3f800000,0x3f740bdd,0x3f800000,0x3f43e200,0x3f514d3d,0x3f1b02c6,0x3e2f10a2,0xbf00e7e4,0x3eac7cd4,0x3d16c32c,0xbf710908,0xbf6ff573,0xbe888e93,0xbf0b9a6b,0xbefc5d27,0x3e3b6ecf,
0x3f800000,0x3f6ff573,0x3f800000,0x3f3b8f3b,0x3f41d870,0x3ef6e0cb,0x3d96a905,0xbf1ff6cb,0x3e164083,0xbe541501,0xbf7d3aac,0xbf531849,0xbf08f59b,0xbf4bbbf8,0xbe605c13,0x3f00e7e4,
0,0x3c490e90,0,0x3ec9b953,0x3cc90ab0,0x3d16c32c,0x3f396842,0x3f6ff573,0x3d48fb30,0x3d7b2b74,0x3f7fb10f,0x3f660f88,0x3d96a905,0x3dafb680,0x3f273656,0x3e9aa086,
0,0x3d7b2b74,0,0x3ee0924f,0x3dfab273,0x3e3b6ecf,0x3f49d112,0x3f7a7302,0x3e78cfcc,0x3e9aa086,0x3f7853f8,0x3f43e200,0x3eb8442a,0x3ed53641,0x3ecf7bca,0xbd16c32c,
0,0x3de1bc2e,0,0x3ef6e0cb,0x3e605c13,0x3ea68f12,0x3f584853,0x3f7f84ab,0x3edae880,0x3f064b82,0x3f676bd8,0x3f15f6d9,0x3f1d7fd1,0x3f32c8c9,0x3dfab273,0xbebe1d4a,
0,0x3e22abb6,0,0x3f064b82,0x3ea09ae5,0x3eebcbbb,0x3f64aa59,0x3f7f0e58,0x3f187fc0,0x3f373a23,0x3f4d9f02,0x3ebe1d4a,0x3f514d3d,0x3f660f88,0xbe2f10a2,0xbf299415,
0,0x3e541501,0,0x3f10d3cd,0x3ecf7bca,0x3f15f6d9,0x3f6ed89e,0x3f791298,0x3f3daef9,0x3f5d2d53,0x3f2beb4a,0x3e09cf86,0x3f731447,0x3f7e70b0,0xbee63375,0xbf604621,
0,0x3e827dc0,0,0x3f1b02c6,0x3efc5d27,0x3f32c8c9,0x3f76ba07,0x3f6db293,0x3f5b941a,0x3f75dec6,0x3f039c3d,0xbde1bc2e,0x3f7fec43,0x3f791298,0xbf3085bb,0xbf7cbfc9,
0,0x3e9aa086,0,0x3f24d225,0x3f13682a,0x3f4bbbf8,0x3f7c3b28,0x3f5d2d53,0x3f710908,0x3f7fd397,0x3eac7cd4,0xbeb263ef,0x3f76ba07,0x3f5695e5,0xbf5ebe05,0xbf7baccd,
0,0x3eb263ef,0,0x3f2e3bde,0x3f273656,0x3f604621,0x3f7f4e6d,0x3f47de65,0x3f7d3aac,0x3f7a7302,0x3e164083,0xbf10d3cd,0x3f584853,0x3f1b02c6,0xbf79c79d,0xbf5d2d53,
0x35cccccd,0x35cccccd,0x35cccccd,0x35cccccd,0x35cccccd,0x35cccccd,0x35cccccd,0x35cccccd,0x35cccccd,0x35cccccd,0x35cccccd,0x35cccccd,0x35cccccd,0x35cccccd,0x35cccccd,0x35cccccd,
0x35ccc8da,0x35cc6a23,0x35bc3c09,0x35b80c6c,0x35cb8d5a,0x35ca3307,0x35b36b4e,0x35ae5b88,0x35c85c01,0x35c6096a,0x35a8e03a,0x35a2fcc6,0x35c33cb1,0x35bff78f,0x359cb4cd,0x35960c2f,
0x35ccbd02,0x35cb4283,0x358d37c9,0x357bffb5,0x35c7d2e4,0x35c276a0,0x355b2291,0x3538292a,0x35bb3aec,0x35b2319e,0x351369bb,0x34da7db8,0x35a770fe,0x359b138d,0x348c0d4f,0x33f10e6e,
0x35cca946,0x35c9570a,0x350eb659,0x34a9aa67,0x35c1a90f,0x35b5c9e1,0x33c8ef90,0xb40c9200,0x35a5fb4c,0x359294e9,0xb4bd4866,0xb518176e,0x3578046f,0x354580a2,0xb54e3fd4,0xb57ff144,
0x35cc8da6,0x35c6a993,0xb3a0c8f3,0xb4c70ca3,0x35b92313,0x35a47f35,0xb52f2067,0xb573ff99,0x35898908,0x35529394,0xb597bf2e,0xb5afa9af,0x3509fd76,0x34706739,0xb5c0d407,0xb5ca9556,
0x35cc6a23,0x35c33cb1,0xb533a83f,0xb583db51,0x35ae5b88,0x358f0707,0xb5a5fb4c,0xb5be2876,0x354e3fd4,0x34e429d0,0xb5caefd6,0xb5cb8d5a,0x33713846,0xb4a9aa67,0xb5bff78f,0xb5a8e03a,
0x35cc3ebe,0x35bf13b1,0xb59b138d,0xb5bb3aec,0x35a1740f,0x356bd9dd,0xb5cb4283,0xb5c9c8ed,0x35007bea,0x3320d559,0xb5b6eeae,0xb5945368,0xb4da7db8,0xb55b2291,0xb549e41f,0xb4b37cdc,
0x35cc0b7a,0x35ba3296,0xb5c33cb1,0xb5cca946,0x359294e9,0x3533a83f,0xb5be2876,0xb5996c52,0x3434968b,0xb4bd4866,0xb54580a2,0xb48222f8,0xb55f5d78,0xb5a2fcc6,0x3495f23f,0x354e3fd4,
0,0,0,0,0,0,0,0,0,0,0,0,0,0,0,0,
0x32a0d873,0x33c8ef90,0x3521610f,0x3533a83f,0x3434968b,0x348222f8,0x354580a2,0x3556df37,0x34a9aa67,0x34d0c934,0x3567b948,0x3578046f,0x34f7673d,0x350eb659,0x3583db51,0x358b6318,
0x3320d559,0x34488ec2,0x35945368,0x35a1740f,0x34b37cdc,0x35007bea,0x35ad06a9,0x35b6eeae,0x3525fca2,0x3549e41f,0x35bf13b1,0x35c5619f,0x356bd9dd,0x3585c511,0x35c9c8ed,0x35cc3ebe,
0x33713846,0x3495f23f,0x35bff78f,0x35c85c01,0x35053f42,0x353ca2fc,0x35cc6a23,0x35cc0b7a,0x356ff15b,0x358f0707,0x35c74213,0x35be2876,0x35a2fcc6,0x35b36b4e,0x35b0f10f,0x359fe51e,
0x33a0c8f3,0x34c70ca3,0x35cc8da6,0x35c6a993,0x352f2067,0x3573ff99,0x35b92313,0x35a47f35,0x3597bf2e,0x35afa9af,0x35898908,0x35529394,0x35c0d407,0x35ca9556,0x3509fd76,0x34706739,
0x33c8ef90,0x34f7673d,0x35b80c6c,0x359cb4cd,0x3556df37,0x359294e9,0x356ff15b,0x3518176e,0x35b0f10f,0x35c4b238,0x345c7f3e,0xb434968b,0x35cca946,0x35c85c01,0xb50eb659,0xb567b948,
0x33f10e6e,0x351369bb,0x3585c511,0x3525fca2,0x357bffb5,0x35a770fe,0x34488ec2,0xb48c0d4f,0x35c276a0,0x35ccbd02,0xb538292a,0xb58d37c9,0x35c5619f,0x35ad06a9,0xb5b2319e,0xb5c7d2e4,
0x340c9200,0x352a91ce,0x34f7673d,0xb3713846,0x358f0707,0x35b80c6c,0xb518176e,0xb587a9aa,0x35cb8d5a,0x35c74213,0xb5b36b4e,0xb5ca3307,0x35abab1e,0x3578046f,0xb5c9570a,0xb5b0f10f,
0x3f803f80,0,0,0x3f803f80,0x3f803f80,0,0,0x3f803f80,0x3f803f80,0,0,0x3f803f80,0x3f803f80,0,0,0x3f803f80,
0x3f353f80,0x3f350000,0xbf350000,0x3f353f80,0xbf350000,0x3f353f80,0xbf35bf80,0xbf350000,0xbf35bf80,0xbf350000,0x3f350000,0xbf35bf80,0x3f350000,0xbf35bf80,0x3f353f80,0x3f350000,
0x3f80,0x3f800000,0xbf800000,0x3f80,0xbf80,0xbf800000,0x3f800000,0xbf80,0x3f80,0x3f800000,0xbf800000,0x3f80,0xbf80,0xbf800000,0x3f800000,0xbf80,
0xbf353f80,0x3f350000,0xbf350000,0xbf353f80,0x3f350000,0x3f35bf80,0xbf353f80,0x3f350000,0x3f35bf80,0xbf350000,0x3f350000,0x3f35bf80,0xbf350000,0xbf353f80,0x3f35bf80,0xbf350000,
0xbf803f80,0,0,0xbf803f80,0xbf803f80,0,0,0xbf803f80,0xbf803f80,0,0,0xbf803f80,0xbf803f80,0,0,0xbf803f80,
0xbf353f80,0xbf350000,0x3f350000,0xbf353f80,0x3f350000,0xbf353f80,0x3f35bf80,0x3f350000,0x3f35bf80,0x3f350000,0xbf350000,0x3f35bf80,0xbf350000,0x3f35bf80,0xbf353f80,0xbf350000,
0x3f80,0xbf800000,0x3f800000,0x3f80,0xbf80,0x3f800000,0xbf800000,0xbf80,0x3f80,0xbf800000,0x3f800000,0x3f80,0xbf80,0x3f800000,0xbf800000,0xbf80,
0x3f353f80,0xbf350000,0x3f350000,0x3f353f80,0xbf350000,0xbf35bf80,0x3f353f80,0xbf350000,0xbf35bf80,0x3f350000,0xbf350000,0xbf35bf80,0x3f350000,0x3f353f80,0xbf35bf80,0x3f350000,
0x3f80,0x3f80,0x3ef13f62,0x3ef13f62,0x3dfb3f7e,0xbdfbbf7e,0x3f133f51,0xbf13bf51,0x3e793f78,0x3e793f78,0x3f2c3f3e,0x3f2c3f3e,0x3eb83f6f,0xbeb8bf6f,0x3f423f27,0xbf42bf27,
0x3f80,0x3f80,0x3f62bef1,0x3f62bef1,0x3efc3f5f,0xbefcbf5f,0x3f09bf58,0xbf093f58,0x3f5c3f04,0x3f5c3f04,0x3d49bf80,0x3d49bf80,0x3f803cc9,0xbf80bcc9,0xbee6bf65,0x3ee63f65,
0x3f80,0x3f80,0xbef1bf62,0xbef1bf62,0x3f4a3f1d,0xbf4abf1d,0xbf7cbe2f,0x3f7c3e2f,0x3f78be79,0x3f78be79,0xbf3e3f2c,0xbf3e3f2c,0x3ecfbf6a,0xbecf3f6a,0x3d973f7f,0xbd97bf7f,
0x3f80,0x3f80,0xbf623ef1,0xbf623ef1,0x3f773e89,0xbf77be89,0x3e603f7a,0xbe60bf7a,0x3f04bf5c,0x3f04bf5c,0x3f803d49,0x3f803d49,0xbf31bf39,0x3f313f39,0x3ea1bf73,0xbea13f73,
0x3f80,0x3f80,0x3ef13f62,0x3ef13f62,0x3f7ebdfb,0xbf7e3dfb,0x3f51bf13,0xbf513f13,0xbe79bf78,0xbe79bf78,0xbf2cbf3e,0xbf2cbf3e,0xbf6f3eb8,0x3f6fbeb8,0xbf273f42,0x3f27bf42,
0x3f80,0x3f80,0x3f62bef1,0x3f62bef1,0x3f5fbefc,0xbf5f3efc,0xbf58bf09,0x3f583f09,0xbf5cbf04,0xbf5cbf04,0xbd493f80,0xbd493f80,0xbcc93f80,0x3cc9bf80,0x3f65bee6,0xbf653ee6,
0x3f80,0x3f80,0xbef1bf62,0xbef1bf62,0x3f1dbf4a,0xbf1d3f4a,0xbe2f3f7c,0x3e2fbf7c,0xbf783e79,0xbf783e79,0x3f3ebf2c,0x3f3ebf2c,0x3f6a3ecf,0xbf6abecf,0xbf7f3d97,0x3f7fbd97,
0x3f80,0x3f80,0xbf623ef1,0xbf623ef1,0x3e89bf77,0xbe893f77,0x3f7abe60,0xbf7a3e60,0xbf043f5c,0xbf043f5c,0xbf80bd49,0xbf80bd49,0x3f39bf31,0xbf393f31,0x3f733ea1,0xbf73bea1,
0x3f553f0e,0x3f553f0e,0x3f7f3dc9,0x3f7f3dc9,0x3f653ee6,0xbf65bee6,0x3f80bcc9,0xbf803cc9,0x3f713eac,0x3f713eac,0x3f7dbe16,0x3f7dbe16,0x3f7a3e60,0xbf7abe60,0x3f77be89,0xbf773e89,
0xbf55bf0e,0xbf55bf0e,0xbdc93f7f,0xbdc93f7f,0xbf7fbd97,0x3f7f3d97,0x3ecf3f6a,0xbecfbf6a,0xbf673edb,0xbf673edb,0x3f4e3f18,0x3f4e3f18,0xbf133f51,0x3f13bf51,0x3f7e3dfb,0xbf7ebdfb,
0x3f553f0e,0x3f553f0e,0xbf7fbdc9,0xbf7fbdc9,0x3f73bea1,0xbf733ea1,0xbf313f39,0x3f31bf39,0x3eacbf71,0x3eacbf71,0x3e163f7d,0x3e163f7d,0xbf09bf58,0x3f093f58,0x3f5f3efc,0xbf5fbefc,
0xbf55bf0e,0xbf55bf0e,0x3dc9bf7f,0x3dc9bf7f,0xbf423f27,0x3f42bf27,0xbf6fbeb8,0x3f6f3eb8,0x3edb3f67,0x3edb3f67,0xbf183f4e,0xbf183f4e,0x3f7cbe2f,0xbf7c3e2f,0x3f1d3f4a,0xbf1dbf4a,
0x3f553f0e,0x3f553f0e,0x3f7f3dc9,0x3f7f3dc9,0x3ee6bf65,0xbee63f65,0xbcc9bf80,0x3cc93f80,0xbf71beac,0xbf71beac,0xbf7d3e16,0xbf7d3e16,0xbe603f7a,0x3e60bf7a,0x3e893f77,0xbe89bf77,
0xbf55bf0e,0xbf55bf0e,0xbdc93f7f,0xbdc93f7f,0xbd973f7f,0x3d97bf7f,0x3f6abecf,0xbf6a3ecf,0x3f67bedb,0x3f67bedb,0xbf4ebf18,0xbf4ebf18,0xbf51bf13,0x3f513f13,0xbdfb3f7e,0x3dfbbf7e,
0x3f553f0e,0x3f553f0e,0xbf7fbdc9,0xbf7fbdc9,0xbea1bf73,0x3ea13f73,0x3f393f31,0xbf39bf31,0xbeac3f71,0xbeac3f71,0xbe16bf7d,0xbe16bf7d,0x3f58bf09,0xbf583f09,0xbefc3f5f,0x3efcbf5f,
0xbf55bf0e,0xbf55bf0e,0x3dc9bf7f,0x3dc9bf7f,0x3f273f42,0xbf27bf42,0xbeb83f6f,0x3eb8bf6f,0xbedbbf67,0xbedbbf67,0x3f18bf4e,0x3f18bf4e,0x3e2f3f7c,0xbe2fbf7c,0xbf4a3f1d,0x3f4abf1d,
0x3f800000,0x3f800000,0x3f62bef1,0x3f62bef1,0x3f7ebdfb,0xbf7e3dfb,0x3f51bf13,0xbf513f13,0x3f78be79,0x3f78be79,0x3f3ebf2c,0x3f3ebf2c,0x3f6fbeb8,0xbf6f3eb8,0x3f27bf42,0xbf273f42,
0x3f800000,0x3f800000,0xbef1bf62,0xbef1bf62,0x3f5fbefc,0xbf5f3efc,0xbf58bf09,0x3f583f09,0x3f04bf5c,0x3f04bf5c,0xbf80bd49,0xbf80bd49,0x3cc9bf80,0xbcc93f80,0xbf653ee6,0x3f65bee6,
0x3f800000,0x3f800000,0xbf623ef1,0xbf623ef1,0x3f1dbf4a,0xbf1d3f4a,0xbe2f3f7c,0x3e2fbf7c,0xbe79bf78,0xbe79bf78,0x3f2c3f3e,0x3f2c3f3e,0xbf6abecf,0x3f6a3ecf,0x3f7fbd97,0xbf7f3d97,
0x3f800000,0x3f800000,0x3ef13f62,0x3ef13f62,0x3e89bf77,0xbe893f77,0x3f7abe60,0xbf7a3e60,0xbf5cbf04,0xbf5cbf04,0x3d49bf80,0x3d49bf80,0xbf393f31,0x3f39bf31,0xbf73bea1,0x3f733ea1,
0x3f800000,0x3f800000,0x3f62bef1,0x3f62bef1,0xbdfbbf7e,0x3dfb3f7e,0xbf13bf51,0x3f133f51,0xbf783e79,0xbf783e79,0xbf3e3f2c,0xbf3e3f2c,0x3eb83f6f,0xbeb8bf6f,0x3f423f27,0xbf42bf27,
0x3f800000,0x3f800000,0xbef1bf62,0xbef1bf62,0xbefcbf5f,0x3efc3f5f,0xbf093f58,0x3f09bf58,0xbf043f5c,0xbf043f5c,0x3f803d49,0x3f803d49,0x3f803cc9,0xbf80bcc9,0xbee6bf65,0x3ee63f65,
0x3f800000,0x3f800000,0xbf623ef1,0xbf623ef1,0xbf4abf1d,0x3f4a3f1d,0x3f7c3e2f,0xbf7cbe2f,0x3e793f78,0x3e793f78,0xbf2cbf3e,0xbf2cbf3e,0x3ecfbf6a,0xbecf3f6a,0x3d973f7f,0xbd97bf7f,
0x3f800000,0x3f800000,0x3ef13f62,0x3ef13f62,0xbf77be89,0x3f773e89,0xbe60bf7a,0x3e603f7a,0x3f5c3f04,0x3f5c3f04,0xbd493f80,0xbd493f80,0xbf31bf39,0x3f313f39,0x3ea1bf73,0xbea13f73,
0x3f0ebf55,0x3f0ebf55,0x3dc9bf7f,0x3dc9bf7f,0x3ee6bf65,0xbee63f65,0xbcc9bf80,0x3cc93f80,0x3eacbf71,0x3eacbf71,0xbe16bf7d,0xbe16bf7d,0x3e60bf7a,0xbe603f7a,0xbe89bf77,0x3e893f77,
0xbf0e3f55,0xbf0e3f55,0x3f7f3dc9,0x3f7f3dc9,0xbd973f7f,0x3d97bf7f,0x3f6abecf,0xbf6a3ecf,0x3edb3f67,0x3edb3f67,0x3f18bf4e,0x3f18bf4e,0x3f513f13,0xbf51bf13,0x3dfbbf7e,0xbdfb3f7e,
0x3f0ebf55,0x3f0ebf55,0xbdc93f7f,0xbdc93f7f,0xbea1bf73,0x3ea13f73,0x3f393f31,0xbf39bf31,0xbf71beac,0xbf71beac,0x3f7dbe16,0x3f7dbe16,0xbf583f09,0x3f58bf09,0x3efcbf5f,0xbefc3f5f,
0xbf0e3f55,0xbf0e3f55,0xbf7fbdc9,0xbf7fbdc9,0x3f273f42,0xbf27bf42,0xbeb83f6f,0x3eb8bf6f,0x3f67bedb,0x3f67bedb,0x3f4e3f18,0x3f4e3f18,0xbe2fbf7c,0x3e2f3f7c,0x3f4abf1d,0xbf4a3f1d,
0x3f0ebf55,0x3f0ebf55,0x3dc9bf7f,0x3dc9bf7f,0xbf65bee6,0x3f653ee6,0xbf803cc9,0x3f80bcc9,0xbeac3f71,0xbeac3f71,0x3e163f7d,0x3e163f7d,0x3f7a3e60,0xbf7abe60,0x3f77be89,0xbf773e89,
0xbf0e3f55,0xbf0e3f55,0x3f7f3dc9,0x3f7f3dc9,0x3f7f3d97,0xbf7fbd97,0xbecfbf6a,0x3ecf3f6a,0xbedbbf67,0xbedbbf67,0xbf183f4e,0xbf183f4e,0xbf133f51,0x3f13bf51,0x3f7e3dfb,0xbf7ebdfb,
0x3f0ebf55,0x3f0ebf55,0xbdc93f7f,0xbdc93f7f,0xbf733ea1,0x3f73bea1,0x3f31bf39,0xbf313f39,0x3f713eac,0x3f713eac,0xbf7d3e16,0xbf7d3e16,0xbf09bf58,0x3f093f58,0x3f5f3efc,0xbf5fbefc,
0xbf0e3f55,0xbf0e3f55,0xbf7fbdc9,0xbf7fbdc9,0x3f42bf27,0xbf423f27,0x3f6f3eb8,0xbf6fbeb8,0xbf673edb,0xbf673edb,0xbf4ebf18,0xbf4ebf18,0x3f7cbe2f,0xbf7c3e2f,0x3f1d3f4a,0xbf1dbf4a,
0x3f803f80,0xbf0e3f0e,0x3f803f80,0xbf0e3f0e,0x3f803f80,0xbf0e3f0e,0x3f803f80,0xbf0e3f0e,0x3f803f80,0xbf0e3f0e,0x3f803f80,0xbf0e3f0e,0x3f803f80,0xbf0e3f0e,0x3f803f80,0xbf0e3f0e,
0x3f5f3f7e,0xbd973ee6,0xbf5fbf7e,0x3d97bee6,0x3e893f1d,0x3f27bea1,0xbe89bf1d,0xbf273ea1,0xbefcbdfb,0x3f7fbf65,0x3efc3dfb,0xbf7f3f65,0xbf77bf4a,0x3f42bf73,0x3f773f4a,0xbf423f73,
0x3f043f78,0x3edb3eac,0x3f043f78,0x3edb3eac,0xbf5cbe79,0x3f67bf71,0xbf5cbe79,0x3f67bf71,0xbf04bf78,0xbedbbeac,0xbf04bf78,0xbedbbeac,0x3f5c3e79,0xbf673f71,0x3f5c3e79,0xbf673f71,
0x3cc93f6f,0x3f513e60,0xbcc9bf6f,0xbf51be60,0xbf39bf6a,0xbe2fbf58,0x3f393f6a,0x3e2f3f58,0x3f803eb8,0xbf133f7a,0xbf80beb8,0x3f13bf7a,0xbf313ecf,0x3f7cbf09,0x3f31becf,0xbf7c3f09,
0xbef13f62,0x3f7f3dc9,0xbef13f62,0x3f7f3dc9,0x3ef1bf62,0xbf7fbdc9,0x3ef1bf62,0xbf7fbdc9,0xbef13f62,0x3f7f3dc9,0xbef13f62,0x3f7f3dc9,0x3ef1bf62,0xbf7fbdc9,0x3ef1bf62,0xbf7fbdc9,
0xbf583f51,0x3f6abcc9,0x3f58bf51,0xbf6a3cc9,0x3f7abe2f,0xbeb83f39,0xbf7a3e2f,0x3eb8bf39,0xbf09bf13,0xbecfbf80,0x3f093f13,0x3ecf3f80,0xbe603f7c,0x3f6f3f31,0x3e60bf7c,0xbf6fbf31,
0xbf803f3e,0x3f18be16,0xbf803f3e,0x3f18be16,0x3d493f2c,0x3f4e3f7d,0x3d493f2c,0x3f4e3f7d,0x3f80bf3e,0xbf183e16,0x3f80bf3e,0xbf183e16,0xbd49bf2c,0xbf4ebf7d,0xbd49bf2c,0xbf4ebf7d,
0xbf653f27,0x3dfbbe89,0x3f65bf27,0xbdfb3e89,0xbf733f7f,0x3f4a3efc,0x3f73bf7f,0xbf4abefc,0xbee63f42,0x3f7e3f77,0x3ee6bf42,0xbf7ebf77,0x3ea13d97,0x3f1d3f5f,0xbea1bd97,0xbf1dbf5f,
0,0xbf553f55,0,0xbf553f55,0,0xbf553f55,0,0xbf553f55,0,0xbf553f55,0,0xbf553f55,0,0xbf553f55,0,0xbf553f55,
0x3efc3dfb,0xbf7f3f65,0xbefcbdfb,0x3f7fbf65,0x3f773f4a,0xbf423f73,0xbf77bf4a,0x3f42bf73,0x3f5f3f7e,0xbd973ee6,0xbf5fbf7e,0x3d97bee6,0x3e893f1d,0x3f27bea1,0xbe89bf1d,0xbf273ea1,
0x3f5c3e79,0xbf673f71,0x3f5c3e79,0xbf673f71,0x3f043f78,0x3edb3eac,0x3f043f78,0x3edb3eac,0xbf5cbe79,0x3f67bf71,0xbf5cbe79,0x3f67bf71,0xbf04bf78,0xbedbbeac,0xbf04bf78,0xbedbbeac,
0x3f803eb8,0xbf133f7a,0xbf80beb8,0x3f13bf7a,0xbf313ecf,0x3f7cbf09,0x3f31becf,0xbf7c3f09,0xbcc9bf6f,0xbf51be60,0x3cc93f6f,0x3f513e60,0x3f393f6a,0x3e2f3f58,0xbf39bf6a,0xbe2fbf58,
0x3f623ef1,0xbdc93f7f,0x3f623ef1,0xbdc93f7f,0xbf62bef1,0x3dc9bf7f,0xbf62bef1,0x3dc9bf7f,0x3f623ef1,0xbdc93f7f,0x3f623ef1,0xbdc93f7f,0xbf62bef1,0x3dc9bf7f,0xbf62bef1,0x3dc9bf7f,
0x3f093f13,0x3ecf3f80,0xbf09bf13,0xbecfbf80,0x3e60bf7c,0xbf6fbf31,0xbe603f7c,0x3f6f3f31,0xbf583f51,0x3f6abcc9,0x3f58bf51,0xbf6a3cc9,0x3f7abe2f,0xbeb83f39,0xbf7a3e2f,0x3eb8bf39,
0x3d493f2c,0x3f4e3f7d,0x3d493f2c,0x3f4e3f7d,0x3f80bf3e,0xbf183e16,0x3f80bf3e,0xbf183e16,0xbd49bf2c,0xbf4ebf7d,0xbd49bf2c,0xbf4ebf7d,0xbf803f3e,0x3f18be16,0xbf803f3e,0x3f18be16,
0xbee63f42,0x3f7e3f77,0x3ee6bf42,0xbf7ebf77,0x3ea13d97,0x3f1d3f5f,0xbea1bd97,0xbf1dbf5f,0x3f65bf27,0xbdfb3e89,0xbf653f27,0x3dfbbe89,0x3f73bf7f,0xbf4abefc,0xbf733f7f,0x3f4a3efc,
0,0x3f55bf55,0,0x3f55bf55,0,0x3f55bf55,0,0x3f55bf55,0,0x3f55bf55,0,0x3f55bf55,0,0x3f55bf55,0,0x3f55bf55,
0xbefcbdfb,0x3f7fbf65,0x3efc3dfb,0xbf7f3f65,0xbf77bf4a,0x3f42bf73,0x3f773f4a,0xbf423f73,0xbf5fbf7e,0x3d97bee6,0x3f5f3f7e,0xbd973ee6,0xbe89bf1d,0xbf273ea1,0x3e893f1d,0x3f27bea1,
0xbf5cbe79,0x3f67bf71,0xbf5cbe79,0x3f67bf71,0xbf04bf78,0xbedbbeac,0xbf04bf78,0xbedbbeac,0x3f5c3e79,0xbf673f71,0x3f5c3e79,0xbf673f71,0x3f043f78,0x3edb3eac,0x3f043f78,0x3edb3eac,
0xbf80beb8,0x3f13bf7a,0x3f803eb8,0xbf133f7a,0x3f31becf,0xbf7c3f09,0xbf313ecf,0x3f7cbf09,0x3cc93f6f,0x3f513e60,0xbcc9bf6f,0xbf51be60,0xbf39bf6a,0xbe2fbf58,0x3f393f6a,0x3e2f3f58,
0xbf62bef1,0x3dc9bf7f,0xbf62bef1,0x3dc9bf7f,0x3f623ef1,0xbdc93f7f,0x3f623ef1,0xbdc93f7f,0xbf62bef1,0x3dc9bf7f,0xbf62bef1,0x3dc9bf7f,0x3f623ef1,0xbdc93f7f,0x3f623ef1,0xbdc93f7f,
0xbf09bf13,0xbecfbf80,0x3f093f13,0x3ecf3f80,0xbe603f7c,0x3f6f3f31,0x3e60bf7c,0xbf6fbf31,0x3f58bf51,0xbf6a3cc9,0xbf583f51,0x3f6abcc9,0xbf7a3e2f,0x3eb8bf39,0x3f7abe2f,0xbeb83f39,
0xbd49bf2c,0xbf4ebf7d,0xbd49bf2c,0xbf4ebf7d,0xbf803f3e,0x3f18be16,0xbf803f3e,0x3f18be16,0x3d493f2c,0x3f4e3f7d,0x3d493f2c,0x3f4e3f7d,0x3f80bf3e,0xbf183e16,0x3f80bf3e,0xbf183e16,
0x3ee6bf42,0xbf7ebf77,0xbee63f42,0x3f7e3f77,0xbea1bd97,0xbf1dbf5f,0x3ea13d97,0x3f1d3f5f,0xbf653f27,0x3dfbbe89,0x3f65bf27,0xbdfb3e89,0xbf733f7f,0x3f4a3efc,0x3f73bf7f,0xbf4abefc,
0x3f800000,0x3f7ff84a,0x3f800000,0x3f6afb8c,0x3f7fe129,0x3f7fba9e,0x3f2f61a5,0x3eadf73c,0x3f7f84ab,0x3f7f3f54,0xbd7b2b74,0xbee79a5d,0x3f7eea9d,0x3f7e868b,0xbf44e3f5,0xbf75a67b,
0x3f800000,0x3f7f7808,0x3f800000,0x3f65b710,0x3f7de0b1,0x3f7b3bab,0x3f1c420c,0x3e4ada4f,0x3f778bc5,0x3f72d4eb,0xbe827dc0,0xbf27ce61,0x3f6d1c1d,0x3f666771,0xbf6be858,0xbf7f90b1,
0x3f800000,0x3f7e5a38,0x3f800000,0x3f5fe4e9,0x3f796e4e,0x3f714c7a,0x3f07a136,0x3d55880e,0x3f660f88,0x3f57dc7f,0xbee0924f,0xbf51c0c2,0x3f46e22a,0x3f33587a,0xbf7e9bc9,0xbf6b99fb,
0x3f800000,0x3f7c9f8a,0x3f800000,0x3f5988ad,0x3f7294f8,0x3f62241a,0x3ee363fa,0xbdc27c39,0x3f4bbbf8,0x3f2ff3e6,0xbf1b02c6,0xbf6f20b0,0x3f0f8784,0x3ed6a399,0xbf7b61fc,0xbf3c17d9,
0x3f800000,0x3f7a4910,0x3f800000,0x3f52a649,0x3f696591,0x3f4e1689,0x3eb554ec,0xbe75c35a,0x3f299415,0x3efafef7,0xbf3fc767,0xbf7e2b72,0x3e97a117,0x3db5f8da,0xbf628210,0xbeed3063,
0x3f800000,0x3f77583a,0x3f800000,0x3f4b41fa,0x3f5df6be,0x3f3592e7,0x3e8586ce,0xbec27b55,0x3f00e7e4,0x3e870ada,0xbf5d2d53,0xbf7dfa38,0x3bc90f88,0xbe80f8c0,0xbf36206c,0xbe0cec4a,
0x3f800000,0x3f73ced9,0x3f800000,0x3f436051,0x3f5064af,0x3f19210f,0x3e28defc,0xbf02ef9f,0x3ea68f12,0x3cafea69,0xbf721352,0xbf6e8ff8,0xbe919ddd,0xbf102dd5,0xbef41f07,0x3e5101f1,
0x3f800000,0x3f6faf1b,0x3f800000,0x3f3b0629,0x3f40d0da,0x3ef2bd43,0x3d8a200a,0xbf21cbfb,0x3e09cf86,0xbe636c83,0xbf7dabcc,0xbf50d937,0xbf0cead0,0xbf4f0417,0xbe4dee60,0x3f05a02c,
0,0x3c7b514b,0,0x3ecb2aae,0x3cfb49ba,0x3d3c6dd5,0x3f3a7ca4,0x3f70c501,0x3d7b2b74,0x3d9cecf9,0x3f7f84ab,0x3f644fac,0x3dbc3ac3,0x3ddb7d37,0x3f239da9,0x3e901c2c,
0,0x3d83db0a,0,0x3ee1fb6a,0x3e039502,0x3e44b0b9,0x3f4ac77f,0x3f7aed37,0x3e827dc0,0x3ea21887,0x3f778bc5,0x3f4154e1,0x3ec1071e,0x3edf28a9,0x3ec6d529,0xbd6ea038,
0,0x3de7fa9a,0,0x3ef840c8,0x3e667c66,0x3eab0201,0x3f591e6a,0x3f7fa6e3,0x3ee0924f,0x3f099f4e,0x3f660f88,0x3f12c39a,0x3f212ff9,0x3f36ad7f,0x3dd53db9,0xbec8477c,
0,0x3e25c58c,0,0x3f06f686,0x3ea395c5,0x3eeff7fb,0x3f655e0b,0x3f7ed7d4,0x3f1b02c6,0x3f39f2ac,0x3f4bbbf8,0x3eb6ccc3,0x3f53fac3,0x3f686b39,0xbe419b37,0xbf2da859,
0,0x3e57278f,0,0x3f11796b,0x3ed25a09,0x3f17de12,0x3f6f6830,0x3f788486,0x3f3fc767,0x3f5f20db,0x3f299415,0x3df475c0,0x3f748422,0x3f7efcc9,0xbeee9479,0xbf62df7b,
0,0x3e840270,0,0x3f1ba299,0x3eff17b2,0x3f34768f,0x3f772417,0x3f6cd007,0x3f5d2d53,0x3f76ef5b,0x3f00e7e4,0xbe007745,0x3f7ffec4,0x3f77beb7,0xbf33e7bc,0xbf7d906e,
0,0x3e9c1faf,0,0x3f256bcb,0x3f14b039,0x3f4d26fd,0x3f7c7eb0,0x3f5bfb34,0x3f721352,0x3f7ff0e3,0x3ea68f12,0xbeb9bb1e,0x3f756d97,0x3f5389c7,0xbf6106f2,0xbf7a9c59,
0,0x3eb3dca5,0,0x3f2ecef7,0x3f286605,0x3f61668a,0x3f7f6ac7,0x3f466354,0x3f7dabcc,0x3f799b43,0x3e09cf86,0xbf140c5f,0x3f55b993,0x3f16999f,0xbf7ac516,0xbf5a5ba0,
0x35cccccd,0x35cccccd,0x35cccccd,0x35cccccd,0x35cccccd,0x35cccccd,0x35cccccd,0x35cccccd,0x35cccccd,0x35cccccd,0x35cccccd,0x35cccccd,0x35cccccd,0x35cccccd,0x35cccccd,0x35cccccd,
0x35ccc6a2,0x35cc6006,0x35bbfc70,0x35b7c5a7,0x35cb7b60,0x35ca193c,0x35b31d87,0x35ae06f1,0x35c83a73,0x35c5e02f,0x35a88507,0x35a29b2e,0x35c30be1,0x35bfbf49,0x359c4d0e,0x35959e88,
0x35ccb421,0x35cb1a27,0x358c4e1d,0x357a0347,0x35c78b72,0x35c210c7,0x355901f0,0x3535e995,0x35bab7a7,0x35b19232,0x351110bd,0x34d5a47e,0x35a6b6f3,0x359a40ae,0x348718ca,0x33dd000f,
0x35cc954b,0x35c8fc89,0x350b2c30,0x34a2483f,0x35c109fb,0x35b4e9ae,0x33aad33e,0xb41b9694,0x35a4ded4,0x35914253,0xb4c49c48,0xb51b95de,0x357501b2,0x35423103,0xb5517f65,0xb5816ffc,
0x35cc6a23,0x35c6096a,0xb3c8ef90,0xb4d0c934,0x35b80c6c,0x35a2fcc6,0xb533a83f,0xb578046f,0x3587a9aa,0x354e3fd4,0xb5996c52,0xb5b0f10f,0x35053f42,0x345c7f3e,0xb5c1a90f,0xb5caefd6,
0x35cc32aa,0x35c243ef,0xb539484b,0xb5863eb4,0x35acb065,0x358cc31e,0xb5a7cd68,0xb5bf4d5a,0x3548cbf9,0x34d8115e,0xb5cb55f5,0xb5cb2e94,0x330cbb87,0xb4b5f068,0xb5bed993,0xb5a7142c,
0x35cbeee4,0x35bdb017,0xb59d832a,0xb5bcb9e0,0x359f1b54,0x3565a5a1,0xb5cbafd4,0xb5c91b30,0x34f29b58,0x3220d93a,0xb5b534da,0xb591b389,0xb4e8fc95,0xb56177b4,0xb5434c06,0xb4a4beb3,
0x35cb9ed5,0x35b852c1,0xb5c4852f,0xb5cc73c1,0x358f79fb,0x352bb614,0xb5bc7b2f,0xb596797a,0x341193e2,0xb4ce5acd,0xb53dc04f,0xb4617a10,0xb566afbb,0xb5a59ce0,0x34a734c1,0x3555cd14,
0,0,0,0,0,0,0,0,0,0,0,0,0,0,0,0,
0x32c90dd6,0x33d2f811,0x3522888b,0x3534c922,0x34399548,0x34849e0a,0x35469a3a,0x3557f0d6,0x34ac1fa5,0x34d3371a,0x3568c245,0x35790428,0x34f9cc4b,0x350fe3b7,0x3584563c,0x358bd8c6,
0x334907c8,0x34528804,0x35953084,0x35a23933,0x34b86384,0x3502de37,0x35adb1ef,0x35b77e6f,0x35284807,0x354c12f5,0x35bf868d,0x35c5b679,0x356de6c2,0x3586b804,0x35c9fef3,0x35cc556c,
0x3396be44,0x349d5a2e,0x35c09d9b,0x35c8bdc6,0x3508ce67,0x353ff996,0x35cc8582,0x35cbdfdd,0x3572fcea,0x35905ed9,0x35c6d06b,0x35bd7339,0x35a41f31,0x35b45208,0x35affc2a,0x359eb5dd,
0x33c8ef90,0x34d0c934,0x35cc6a23,0x35c6096a,0x3533a83f,0x3578046f,0x35b80c6c,0x35a2fcc6,0x35996c52,0x35b0f10f,0x3587a9aa,0x354e3fd4,0x35c1a90f,0x35caefd6,0x35053f42,0x345c7f3e,
0x33fb14c1,0x3501ad39,0x35b6a623,0x359aaa4d,0x355c3217,0x3594c224,0x356ad291,0x35123d69,0x35b280af,0x35c58c49,0x34439166,0xb44d8ba2,0x35ccc0b6,0x35c7af69,0xb51495b2,0xb56ce099,
0x34169569,0x351a6c18,0x3582e487,0x351f10ee,0x3580f32d,0x35a99568,0x342a97c7,0xb49ae293,0x35c39ce8,0x35cccbd0,0xb53edd2d,0xb58fec97,0x35c457ac,0x35aafadc,0xb5b4058e,0xb5c89dab,
0x342f9760,0x353286ed,0x34e6937a,0xb3bee693,0x35922466,0x35b9ef61,0xb5203930,0xb58aed14,0x35cbfd6e,0x35c6322c,0xb5b57f95,0xb5cad9f2,0x35a93b06,0x3570f5cb,0xb5c87d14,0xb5aeafb3,
0x3f803f80,0,0,0x3f803f80,0x3f803f80,0,0,0x3f803f80,0x3f803f80,0,0,0x3f803f80,0x3f803f80,0,0,0x3f803f80,
0x3f353f80,0x3f350000,0xbf350000,0x3f353f80,0xbf350000,0x3f353f80,0xbf35bf80,0xbf350000,0xbf35bf80,0xbf350000,0x3f350000,0xbf35bf80,0x3f350000,0xbf35bf80,0x3f353f80,0x3f350000,
0x3f80,0x3f800000,0xbf800000,0x3f80,0xbf80,0xbf800000,0x3f800000,0xbf80,0x3f80,0x3f800000,0xbf800000,0x3f80,0xbf80,0xbf800000,0x3f800000,0xbf80,
0xbf353f80,0x3f350000,0xbf350000,0xbf353f80,0x3f350000,0x3f35bf80,0xbf353f80,0x3f350000,0x3f35bf80,0xbf350000,0x3f350000,0x3f35bf80,0xbf350000,0xbf353f80,0x3f35bf80,0xbf350000,
0xbf803f80,0,0,0xbf803f80,0xbf803f80,0,0,0xbf803f80,0xbf803f80,0,0,0xbf803f80,0xbf803f80,0,0,0xbf803f80,
0xbf353f80,0xbf350000,0x3f350000,0xbf353f80,0x3f350000,0xbf353f80,0x3f35bf80,0x3f350000,0x3f35bf80,0x3f350000,0xbf350000,0x3f35bf80,0xbf350000,0x3f35bf80,0xbf353f80,0xbf350000,
0x3f80,0xbf800000,0x3f800000,0x3f80,0xbf80,0x3f800000,0xbf800000,0xbf80,0x3f80,0xbf800000,0x3f800000,0x3f80,0xbf80,0x3f800000,0xbf800000,0xbf80,
0x3f353f80,0xbf350000,0x3f350000,0x3f353f80,0xbf350000,0xbf35bf80,0x3f353f80,0xbf350000,0xbf35bf80,0x3f350000,0xbf350000,0xbf35bf80,0x3f350000,0x3f353f80,0xbf35bf80,0x3f350000,
0x3f80,0x3f80,0x3f0e3f55,0x3f0e3f55,0x3e163f7d,0xbe16bf7d,0x3f2c3f3e,0xbf2cbf3e,0x3e953f75,0x3e953f75,0x3f463f22,0x3f463f22,0x3edb3f67,0xbedbbf67,0x3f5c3f04,0xbf5cbf04,
0x3f80,0x3f80,0x3f55bf0e,0x3f55bf0e,0x3f043f5c,0xbf04bf5c,0x3edbbf67,0xbedb3f67,0x3f623ef1,0x3f623ef1,0xbdc9bf7f,0xbdc9bf7f,0x3f80bd49,0xbf803d49,0xbf18bf4e,0x3f183f4e,
0x3f80,0x3f80,0xbf0ebf55,0xbf0ebf55,0x3f4e3f18,0xbf4ebf18,0xbf80bd49,0x3f803d49,0x3f75be95,0x3f75be95,0xbf223f46,0xbf223f46,0x3eacbf71,0xbeac3f71,0x3e793f78,0xbe79bf78,
0x3f80,0x3f80,0xbf553f0e,0xbf553f0e,0x3f783e79,0xbf78be79,0x3eac3f71,0xbeacbf71,0x3ef1bf62,0x3ef1bf62,0x3f7fbdc9,0x3f7fbdc9,0xbf3ebf2c,0x3f3e3f2c,0x3e16bf7d,0xbe163f7d,
0x3f80,0x3f80,0x3f0e3f55,0x3f0e3f55,0x3f7dbe16,0xbf7d3e16,0x3f3ebf2c,0xbf3e3f2c,0xbe95bf75,0xbe95bf75,0xbf46bf22,0xbf46bf22,0xbf673edb,0x3f67bedb,0xbf043f5c,0x3f04bf5c,
0x3f80,0x3f80,0x3f55bf0e,0x3f55bf0e,0x3f5cbf04,0xbf5c3f04,0xbf67bedb,0x3f673edb,0xbf62bef1,0xbf62bef1,0x3dc93f7f,0x3dc93f7f,0x3d493f80,0xbd49bf80,0x3f4ebf18,0xbf4e3f18,
0x3f80,0x3f80,0xbf0ebf55,0xbf0ebf55,0x3f18bf4e,0xbf183f4e,0xbd493f80,0x3d49bf80,0xbf753e95,0xbf753e95,0x3f22bf46,0x3f22bf46,0x3f713eac,0xbf71beac,0xbf783e79,0x3f78be79,
0x3f80,0x3f80,0xbf553f0e,0xbf553f0e,0x3e79bf78,0xbe793f78,0x3f71beac,0xbf713eac,0xbef13f62,0xbef13f62,0xbf7f3dc9,0xbf7f3dc9,0x3f2cbf3e,0xbf2c3f3e,0x3f7d3e16,0xbf7dbe16,
0x3f6d3ec4,0x3f6d3ec4,0x3f7bbe48,0x3f7bbe48,0x3f783e79,0xbf78be79,0x3f71beac,0xbf713eac,0x3f7f3dc9,0x3f7f3dc9,0x3f62bef1,0x3f62bef1,0x3f80bd49,0xbf803d49,0x3f4ebf18,0xbf4e3f18,
0xbf6dbec4,0xbf6dbec4,0x3e483f7b,0x3e483f7b,0xbf7d3e16,0x3f7dbe16,0x3f2c3f3e,0xbf2cbf3e,0xbf463f22,0xbf463f22,0x3f753e95,0x3f753e95,0xbeac3f71,0x3eacbf71,0x3f78be79,0xbf783e79,
0x3f6d3ec4,0x3f6d3ec4,0xbf7b3e48,0xbf7b3e48,0x3f5cbf04,0xbf5c3f04,0xbedb3f67,0x3edbbf67,0x3dc9bf7f,0x3dc9bf7f,0x3ef13f62,0x3ef13f62,0xbf3ebf2c,0x3f3e3f2c,0x3f7d3e16,0xbf7dbe16,
0xbf6dbec4,0xbf6dbec4,0xbe48bf7b,0xbe48bf7b,0xbf183f4e,0x3f18bf4e,0xbf80bd49,0x3f803d49,0x3f223f46,0x3f223f46,0xbe953f75,0xbe953f75,0x3f67bedb,0xbf673edb,0x3f5c3f04,0xbf5cbf04,
0x3f6d3ec4,0x3f6d3ec4,0x3f7bbe48,0x3f7bbe48,0x3e79bf78,0xbe793f78,0xbeacbf71,0x3eac3f71,0xbf7fbdc9,0xbf7fbdc9,0xbf623ef1,0xbf623ef1,0x3d493f80,0xbd49bf80,0x3f183f4e,0xbf18bf4e,
0xbf6dbec4,0xbf6dbec4,0x3e483f7b,0x3e483f7b,0x3e163f7d,0xbe16bf7d,0x3f3ebf2c,0xbf3e3f2c,0x3f46bf22,0x3f46bf22,0xbf75be95,0xbf75be95,0xbf71beac,0x3f713eac,0x3e793f78,0xbe79bf78,
0x3f6d3ec4,0x3f6d3ec4,0xbf7b3e48,0xbf7b3e48,0xbf04bf5c,0x3f043f5c,0x3f673edb,0xbf67bedb,0xbdc93f7f,0xbdc93f7f,0xbef1bf62,0xbef1bf62,0x3f2cbf3e,0xbf2c3f3e,0xbe163f7d,0x3e16bf7d,
0xbf6dbec4,0xbf6dbec4,0xbe48bf7b,0xbe48bf7b,0x3f4e3f18,0xbf4ebf18,0xbd493f80,0x3d49bf80,0xbf22bf46,0xbf22bf46,0x3e95bf75,0x3e95bf75,0x3edb3f67,0xbedbbf67,0xbf043f5c,0x3f04bf5c,
0x3f800000,0x3f800000,0x3f55bf0e,0x3f55bf0e,0x3f7dbe16,0xbf7d3e16,0x3f3ebf2c,0xbf3e3f2c,0x3f75be95,0x3f75be95,0x3f22bf46,0x3f22bf46,0x3f67bedb,0xbf673edb,0x3f04bf5c,0xbf043f5c,
0x3f800000,0x3f800000,0xbf0ebf55,0xbf0ebf55,0x3f5cbf04,0xbf5c3f04,0xbf67bedb,0x3f673edb,0x3ef1bf62,0x3ef1bf62,0xbf7f3dc9,0xbf7f3dc9,0xbd49bf80,0x3d493f80,0xbf4e3f18,0x3f4ebf18,
0x3f800000,0x3f800000,0xbf553f0e,0xbf553f0e,0x3f18bf4e,0xbf183f4e,0xbd493f80,0x3d49bf80,0xbe95bf75,0xbe95bf75,0x3f463f22,0x3f463f22,0xbf71beac,0x3f713eac,0x3f78be79,0xbf783e79,
0x3f800000,0x3f800000,0x3f0e3f55,0x3f0e3f55,0x3e79bf78,0xbe793f78,0x3f71beac,0xbf713eac,0xbf62bef1,0xbf62bef1,0xbdc9bf7f,0xbdc9bf7f,0xbf2c3f3e,0x3f2cbf3e,0xbf7dbe16,0x3f7d3e16,
0x3f800000,0x3f800000,0x3f55bf0e,0x3f55bf0e,0xbe16bf7d,0x3e163f7d,0xbf2cbf3e,0x3f2c3f3e,0xbf753e95,0xbf753e95,0xbf223f46,0xbf223f46,0x3edb3f67,0xbedbbf67,0x3f5c3f04,0xbf5cbf04,
0x3f800000,0x3f800000,0xbf0ebf55,0xbf0ebf55,0xbf04bf5c,0x3f043f5c,0xbedb3f67,0x3edbbf67,0xbef13f62,0xbef13f62,0x3f7fbdc9,0x3f7fbdc9,0x3f80bd49,0xbf803d49,0xbf18bf4e,0x3f183f4e,
0x3f800000,0x3f800000,0xbf553f0e,0xbf553f0e,0xbf4ebf18,0x3f4e3f18,0x3f803d49,0xbf80bd49,0x3e953f75,0x3e953f75,0xbf46bf22,0xbf46bf22,0x3eacbf71,0xbeac3f71,0x3e793f78,0xbe79bf78,
0x3f800000,0x3f800000,0x3f0e3f55,0x3f0e3f55,0xbf78be79,0x3f783e79,0xbeacbf71,0x3eac3f71,0x3f623ef1,0x3f623ef1,0x3dc93f7f,0x3dc93f7f,0xbf3ebf2c,0x3f3e3f2c,0x3e16bf7d,0xbe163f7d,
0x3ec4bf6d,0x3ec4bf6d,0xbe48bf7b,0xbe48bf7b,0x3e79bf78,0xbe793f78,0xbeacbf71,0x3eac3f71,0x3dc9bf7f,0x3dc9bf7f,0xbef1bf62,0xbef1bf62,0xbd49bf80,0x3d493f80,0xbf18bf4e,0x3f183f4e,
0xbec43f6d,0xbec43f6d,0x3f7bbe48,0x3f7bbe48,0x3e163f7d,0xbe16bf7d,0x3f3ebf2c,0xbf3e3f2c,0x3f223f46,0x3f223f46,0x3e95bf75,0x3e95bf75,0x3f713eac,0xbf71beac,0xbe79bf78,0x3e793f78,
0x3ec4bf6d,0x3ec4bf6d,0x3e483f7b,0x3e483f7b,0xbf04bf5c,0x3f043f5c,0x3f673edb,0xbf67bedb,0xbf7fbdc9,0xbf7fbdc9,0x3f62bef1,0x3f62bef1,0xbf2c3f3e,0x3f2cbf3e,0x3e16bf7d,0xbe163f7d,
0xbec43f6d,0xbec43f6d,0xbf7b3e48,0xbf7b3e48,0x3f4e3f18,0xbf4ebf18,0xbd493f80,0x3d49bf80,0x3f46bf22,0x3f46bf22,0x3f753e95,0x3f753e95,0xbedbbf67,0x3edb3f67,0x3f04bf5c,0xbf043f5c,
0x3ec4bf6d,0x3ec4bf6d,0xbe48bf7b,0xbe48bf7b,0xbf78be79,0x3f783e79,0xbf713eac,0x3f71beac,0xbdc93f7f,0xbdc93f7f,0x3ef13f62,0x3ef13f62,0x3f80bd49,0xbf803d49,0x3f4ebf18,0xbf4e3f18,
0xbec43f6d,0xbec43f6d,0x3f7bbe48,0x3f7bbe48,0x3f7dbe16,0xbf7d3e16,0xbf2cbf3e,0x3f2c3f3e,0xbf22bf46,0xbf22bf46,0xbe953f75,0xbe953f75,0xbeac3f71,0x3eacbf71,0x3f78be79,0xbf783e79,
0x3ec4bf6d,0x3ec4bf6d,0x3e483f7b,0x3e483f7b,0xbf5c3f04,0x3f5cbf04,0x3edbbf67,0xbedb3f67,0x3f7f3dc9,0x3f7f3dc9,0xbf623ef1,0xbf623ef1,0xbf3ebf2c,0x3f3e3f2c,0x3f7d3e16,0xbf7dbe16,
0xbec43f6d,0xbec43f6d,0xbf7b3e48,0xbf7b3e48,0x3f18bf4e,0xbf183f4e,0x3f803d49,0xbf80bd49,0xbf463f22,0xbf463f22,0xbf75be95,0xbf75be95,0x3f67bedb,0xbf673edb,0x3f5c3f04,0xbf5cbf04,
0x3f803f80,0xbec43ec4,0x3f803f80,0xbec43ec4,0x3f803f80,0xbec43ec4,0x3f803f80,0xbec43ec4,0x3f803f80,0xbec43ec4,0x3f803f80,0xbec43ec4,0x3f803f80,0xbec43ec4,0x3f803f80,0xbec43ec4,
0x3f5c3f7d,0x3e163e79,0xbf5cbf7d,0xbe16be79,0x3e793f18,0x3f4ebf04,0xbe79bf18,0xbf4e3f04,0xbf04be16,0x3f7dbf78,0x3f043e16,0xbf7d3f78,0xbf78bf4e,0x3f18bf5c,0x3f783f4e,0xbf183f5c,
0x3ef13f75,0x3f223dc9,0x3ef13f75,0x3f223dc9,0xbf62be95,0x3f46bf7f,0xbf62be95,0x3f46bf7f,0xbef1bf75,0xbf22bdc9,0xbef1bf75,0xbf22bdc9,0x3f623e95,0xbf463f7f,0x3f623e95,0xbf463f7f,
0xbd493f67,0x3f71bd49,0x3d49bf67,0xbf713d49,0xbf2cbf71,0xbedbbf2c,0x3f2c3f71,0x3edb3f2c,0x3f803edb,0xbeac3f80,0xbf80bedb,0x3eacbf80,0xbf3e3eac,0x3f67bf3e,0x3f3ebeac,0xbf673f3e,
0xbf0e3f55,0x3f7bbe48,0xbf0e3f55,0x3f7bbe48,0x3f0ebf55,0xbf7b3e48,0x3f0ebf55,0xbf7b3e48,0xbf0e3f55,0x3f7bbe48,0xbf0e3f55,0x3f7bbe48,0x3f0ebf55,0xbf7b3e48,0x3f0ebf55,0xbf7b3e48,
0xbf673f3e,0x3f3ebeac,0x3f67bf3e,0xbf3e3eac,0x3f71bd49,0xbd493f67,0xbf713d49,0x3d49bf67,0xbedbbf2c,0xbf2cbf71,0x3edb3f2c,0x3f2c3f71,0xbeac3f80,0x3f803edb,0x3eacbf80,0xbf80bedb,
0xbf7f3f22,0x3e95bef1,0xbf7f3f22,0x3e95bef1,0xbdc93f46,0x3f753f62,0xbdc93f46,0x3f753f62,0x3f7fbf22,0xbe953ef1,0x3f7fbf22,0xbe953ef1,0x3dc9bf46,0xbf75bf62,0x3dc9bf46,0xbf75bf62,
0xbf4e3f04,0xbe79bf18,0x3f4ebf04,0x3e793f18,0xbf7d3f78,0x3f043e16,0x3f7dbf78,0xbf04be16,0xbf183f5c,0x3f783f4e,0x3f18bf5c,0xbf78bf4e,0x3e163e79,0x3f5c3f7d,0xbe16be79,0xbf5cbf7d,
0,0xbf6d3f6d,0,0xbf6d3f6d,0,0xbf6d3f6d,0,0xbf6d3f6d,0,0xbf6d3f6d,0,0xbf6d3f6d,0,0xbf6d3f6d,0,0xbf6d3f6d,
0x3f043e16,0xbf7d3f78,0xbf04be16,0x3f7dbf78,0x3f783f4e,0xbf183f5c,0xbf78bf4e,0x3f18bf5c,0x3f5c3f7d,0x3e163e79,0xbf5cbf7d,0xbe16be79,0x3e793f18,0x3f4ebf04,0xbe79bf18,0xbf4e3f04,
0x3f623e95,0xbf463f7f,0x3f623e95,0xbf463f7f,0x3ef13f75,0x3f223dc9,0x3ef13f75,0x3f223dc9,0xbf62be95,0x3f46bf7f,0xbf62be95,0x3f46bf7f,0xbef1bf75,0xbf22bdc9,0xbef1bf75,0xbf22bdc9,
0x3f803edb,0xbeac3f80,0xbf80bedb,0x3eacbf80,0xbf3e3eac,0x3f67bf3e,0x3f3ebeac,0xbf673f3e,0x3d49bf67,0xbf713d49,0xbd493f67,0x3f71bd49,0x3f2c3f71,0x3edb3f2c,0xbf2cbf71,0xbedbbf2c,
0x3f553f0e,0x3e483f7b,0x3f553f0e,0x3e483f7b,0xbf55bf0e,0xbe48bf7b,0xbf55bf0e,0xbe48bf7b,0x3f553f0e,0x3e483f7b,0x3f553f0e,0x3e483f7b,0xbf55bf0e,0xbe48bf7b,0xbf55bf0e,0xbe48bf7b,
0x3edb3f2c,0x3f2c3f71,0xbedbbf2c,0xbf2cbf71,0x3eacbf80,0xbf80bedb,0xbeac3f80,0x3f803edb,0xbf673f3e,0x3f3ebeac,0x3f67bf3e,0xbf3e3eac,0x3f71bd49,0xbd493f67,0xbf713d49,0x3d49bf67,
0xbdc93f46,0x3f753f62,0xbdc93f46,0x3f753f62,0x3f7fbf22,0xbe953ef1,0x3f7fbf22,0xbe953ef1,0x3dc9bf46,0xbf75bf62,0x3dc9bf46,0xbf75bf62,0xbf7f3f22,0x3e95bef1,0xbf7f3f22,0x3e95bef1,
0xbf183f5c,0x3f783f4e,0x3f18bf5c,0xbf78bf4e,0x3e163e79,0x3f5c3f7d,0xbe16be79,0xbf5cbf7d,0x3f4ebf04,0x3e793f18,0xbf4e3f04,0xbe79bf18,0x3f7dbf78,0xbf04be16,0xbf7d3f78,0x3f043e16,
0,0x3f6dbf6d,0,0x3f6dbf6d,0,0x3f6dbf6d,0,0x3f6dbf6d,0,0x3f6dbf6d,0,0x3f6dbf6d,0,0x3f6dbf6d,0,0x3f6dbf6d,
0xbf04be16,0x3f7dbf78,0x3f043e16,0xbf7d3f78,0xbf78bf4e,0x3f18bf5c,0x3f783f4e,0xbf183f5c,0xbf5cbf7d,0xbe16be79,0x3f5c3f7d,0x3e163e79,0xbe79bf18,0xbf4e3f04,0x3e793f18,0x3f4ebf04,
0xbf62be95,0x3f46bf7f,0xbf62be95,0x3f46bf7f,0xbef1bf75,0xbf22bdc9,0xbef1bf75,0xbf22bdc9,0x3f623e95,0xbf463f7f,0x3f623e95,0xbf463f7f,0x3ef13f75,0x3f223dc9,0x3ef13f75,0x3f223dc9,
0xbf80bedb,0x3eacbf80,0x3f803edb,0xbeac3f80,0x3f3ebeac,0xbf673f3e,0xbf3e3eac,0x3f67bf3e,0xbd493f67,0x3f71bd49,0x3d49bf67,0xbf713d49,0xbf2cbf71,0xbedbbf2c,0x3f2c3f71,0x3edb3f2c,
0xbf55bf0e,0xbe48bf7b,0xbf55bf0e,0xbe48bf7b,0x3f553f0e,0x3e483f7b,0x3f553f0e,0x3e483f7b,0xbf55bf0e,0xbe48bf7b,0xbf55bf0e,0xbe48bf7b,0x3f553f0e,0x3e483f7b,0x3f553f0e,0x3e483f7b,
0xbedbbf2c,0xbf2cbf71,0x3edb3f2c,0x3f2c3f71,0xbeac3f80,0x3f803edb,0x3eacbf80,0xbf80bedb,0x3f67bf3e,0xbf3e3eac,0xbf673f3e,0x3f3ebeac,0xbf713d49,0x3d49bf67,0x3f71bd49,0xbd493f67,
0x3dc9bf46,0xbf75bf62,0x3dc9bf46,0xbf75bf62,0xbf7f3f22,0x3e95bef1,0xbf7f3f22,0x3e95bef1,0xbdc93f46,0x3f753f62,0xbdc93f46,0x3f753f62,0x3f7fbf22,0xbe953ef1,0x3f7fbf22,0xbe953ef1,
0x3f18bf5c,0xbf78bf4e,0xbf183f5c,0x3f783f4e,0xbe16be79,0xbf5cbf7d,0x3e163e79,0x3f5c3f7d,0xbf4e3f04,0xbe79bf18,0x3f4ebf04,0x3e793f18,0xbf7d3f78,0x3f043e16,0x3f7dbf78,0xbf04be16,
0x3f800000,0x3f7ff4e6,0x3f800000,0x3f6aab7b,0x3f7fd397,0x3f7f9c18,0x3f2e3bde,0x3ea986c4,0x3f7f4e6d,0x3f7eea9d,0xbd96a905,0xbeee9479,0x3f7e70b0,0x3f7de0b1,0xbf47de65,0xbf772417,
0x3f800000,0x3f7f6ac7,0x3f800000,0x3f655e0b,0x3f7dabcc,0x3f7ac516,0x3f1b02c6,0x3e419b37,0x3f76ba07,0x3f718f57,0xbe888e93,0xbf2ac082,0x3f6b4b0c,0x3f63f473,0xbf6db293,0xbf7f2f9d,
0x3f800000,0x3f7e4323,0x3f800000,0x3f5f8327,0x3f791298,0x3f708066,0x3f064b82,0x3d2fe007,0x3f64aa59,0x3f55b993,0xbee63375,0xbf53fac3,0x3f43e200,0x3f2f61a5,0xbf7f0e58,0xbf696591,
0x3f800000,0x3f7c7eb0,0x3f800000,0x3f591e6a,0x3f721352,0x3f6106f2,0x3ee0924f,0xbdd53db9,0x3f49d112,0x3f2d1469,0xbf1d7fd1,0xbf708066,0x3f0b9a6b,0x3ecc9b8b,0xbf7a7302,0xbf385216,
0x3f800000,0x3f7a1e84,0x3f800000,0x3f5233c6,0x3f68bf3c,0x3f4cae79,0x3eb263ef,0xbe7ee6e1,0x3f273656,0x3ef41f07,0xbf41d870,0xbf7e9bc9,0x3e8e9a22,0x3d8a200a,0xbf604621,0xbee363fa,
0x3f800000,0x3f772417,0x3f800000,0x3f4ac77f,0x3f5d2d53,0x3f33e7bc,0x3e827dc0,0xbec6d529,0x3efc5d27,0x3e7ee6e1,0xbf5ebe05,0xbf7d7474,0xbc490e90,0xbe8b9507,0xbf32c8c9,0xbdee3876,
0x3f800000,0x3f73913f,0x3f800000,0x3f42de29,0x3f4f7a1f,0x3f173c07,0x3e22abb6,0xbf04f484,0x3ea09ae5,0x3bc90f88,0xbf731447,0xbf6d1c1d,0xbe9aa086,0xbf14b039,0xbeebcbbb,0x3e667c66,
0x3f800000,0x3f6f6830,0x3f800000,0x3f3a7ca4,0x3f3fc767,0x3eee9479,0x3d7b2b74,0xbf239da9,0x3dfab273,0xbe72b651,0xbf7e1324,0xbf4e8d90,0xbf10d3cd,0xbf5233c6,0xbe3b6ecf,0x3f0a48ad,
0,0x3c96c9b6,0,0x3ecc9b8b,0x3d16c32c,0x3d621469,0x3f3b8f3b,0x3f718f57,0x3d96a905,0x3dbc3ac3,0x3f7f4e6d,0x3f628210,0x3de1bc2e,0x3e039502,0x3f1ff6cb,0x3e8586ce,
0,0x3d8a200a,0,0x3ee363fa,0x3e09cf86,0x3e4dee60,0x3f4bbbf8,0x3f7b61fc,0x3e888e93,0x3ea986c4,0x3f76ba07,0x3f3ebc1b,0x3ec9b953,0x3ee900b7,0x3ebe1d4a,0xbda3308c,
0,0x3dee3876,0,0x3ef9a02d,0x3e6c9a7f,0x3eaf713a,0x3f59f26a,0x3f7fc38f,0x3ee63375,0x3f0cead0,0x3f64aa59,0x3f0f8784,0x3f24d225,0x3f3a7ca4,0x3dafb680,0xbed25a09,
0,0x3e28defc,0,0x3f07a136,0x3ea68f12,0x3ef41f07,0x3f660f88,0x3f7e9bc9,0x3f1d7fd1,0x3f3ca003,0x3f49d112,0x3eaf713a,0x3f5695e5,0x3f6aab7b,0xbe541501,0xbf31a81d,
0,0x3e5a3997,0,0x3f121eb0,0x3ed53641,0x3f19c200,0x3f6ff573,0x3f77f110,0x3f41d870,0x3f6106f2,0x3f273656,0x3dd53db9,0x3f75dec6,0x3f7f6ac7,0xbef6e0cb,0xbf655e0b,
0,0x3e8586ce,0,0x3f1c420c,0x3f00e7e4,0x3f36206c,0x3f778bc5,0x3f6be858,0x3f5ebe05,0x3f77f110,0x3efc5d27,0xbe1008b7,0x3f7ffb11,0x3f764d97,0xbf373a23,0xbf7e4323,
0,0x3e9d9e78,0,0x3f26050a,0x3f15f6d9,0x3f4e8d90,0x3f7cbfc9,0x3f5ac450,0x3f731447,0x3f7ffec4,0x3ea09ae5,0xbec1071e,0x3f740bdd,0x3f5064af,0xbf633c5a,0xbf796e4e,
0,0x3eb554ec,0,0x3f2f61a5,0x3f299415,0x3f628210,0x3f7f84ab,0x3f44e3f5,0x3f7e1324,0x3f78b47b,0x3dfab273,0xbf173c07,0x3f531849,0x3f121eb0,0xbf7baccd,0xbf577026,
0x35cccccd,0x35cccccd,0x35cccccd,0x35cccccd,0x35cccccd,0x35cccccd,0x35cccccd,0x35cccccd,0x35cccccd,0x35cccccd,0x35cccccd,0x35cccccd,0x35cccccd,0x35cccccd,0x35cccccd,0x35cccccd,
0x35ccc3eb,0x35cc556c,0x35bbbc62,0x35b77e6f,0x35cb68e9,0x35c9fef3,0x35b2cf52,0x35adb1ef,0x35c8186a,0x35c5b679,0x35a8296b,0x35a23933,0x35c2da99,0x35bf868d,0x359be4ed,0x35953084,
0x35cca946,0x35caefd6,0x358b6318,0x3578046f,0x35c74213,0x35c1a90f,0x3556df37,0x3533a83f,0x35ba3296,0x35b0f10f,0x350eb659,0x34d0c934,0x35a5fb4c,0x35996c52,0x348222f8,0x33c8ef90,
0x35cc7ce0,0x35c89dab,0x35079f03,0x349ae293,0x35c066b8,0x35b4058e,0x338cb338,0xb42a97c7,0x35a3bec8,0x358fec97,0xb4cbebe7,0xb51f10ee,0x3571f9a5,0x353edd2d,0xb554ba6c,0xb582e487,
0x35cc3ebe,0x35c5619f,0xb3f10e6e,0xb4da7db8,0x35b6eeae,0x35a1740f,0xb538292a,0xb57bffb5,0x3585c511,0x3549e41f,0xb59b138d,0xb5b2319e,0x35007bea,0x34488ec2,0xb5c276a0,0xb5cb4283,
0x35cbeee4,0x35c13f79,0xb53edd2d,0xb5889a01,0x35aafadc,0x358a76bb,0xb5a99568,0xb5c066b8,0x35434c06,0x34cbebe7,0xb5cbafd4,0xb5cac390,0x3220d93a,0xb4c22b74,0xb5bdb017,0xb5a53e0d,
0x35cb8d5a,0x35bc3c09,0xb59fe51e,0xb5be2876,0x359cb4cd,0x355f5d78,0xb5cc0b7a,0xb5c85c01,0x34e429d0,0xb2a0d873,0xb5b36b4e,0xb58f0707,0xb4f7673d,0xb567b948,0xb53ca2fc,0xb495f23f,
0x35cb1a27,0x35b65d28,0xb5c5b679,0xb5cc2618,0x358c4e1d,0x3523afa2,0xb5bab7a7,0xb59374de,0x33dd000f,0xb4df54d8,0xb535e995,0xb43e9392,0xb56de6c2,0xb5a8296b,0x34b86384,0x355d4116,
0,0,0,0,0,0,0,0,0,0,0,0,0,0,0,0,
0x32f142bd,0x33dd000f,0x3523afa2,0x3535e995,0x343e9392,0x348718ca,0x3547b357,0x355901f0,0x34ae9479,0x34d5a47e,0x3569cab3,0x357a0347,0x34fc30c0,0x351110bd,0x3584d0d5,0x358c4e1d,
0x33713846,0x345c7f3e,0x35960c2f,0x35a2fcc6,0x34bd4866,0x35053f42,0x35ae5b88,0x35b80c6c,0x352a91ce,0x354e3fd4,0x35bff78f,0x35c6096a,0x356ff15b,0x3587a9aa,0x35ca3307,0x35cc6a23,
0x33b4dd20,0x34a4beb3,0x35c13f79,0x35c91b30,0x350c5a95,0x35434c06,0x35cc9c72,0x35cbafd4,0x35760334,0x3591b389,0x35c65a74,0x35bcb9e0,0x35a53e0d,0x35b534da,0x35af0373,0x359d832a,
0x33f10e6e,0x34da7db8,0x35cc3ebe,0x35c5619f,0x3538292a,0x357bffb5,0x35b6eeae,0x35a1740f,0x359b138d,0x35b2319e,0x3585c511,0x3549e41f,0x35c276a0,0x35cb4283,0x35007bea,0x34488ec2,
0x34169569,0x35079f03,0x35b534da,0x3598967c,0x356177b4,0x3596e669,0x3565a5a1,0x350c5a95,0x35b4058e,0x35c65a74,0x342a97c7,0xb4667457,0x35cccbd0,0x35c6f6c8,0xb51a6c18,0xb571f9a5,
0x3434968b,0x3521610f,0x357ff144,0x3518176e,0x3583db51,0x35abab1e,0x340c9200,0xb4a9aa67,0x35c4b238,0x35ccc8da,0xb54580a2,0xb59294e9,0x35c33cb1,0x35a8e03a,0xb5b5c9e1,0xb5c9570a,
0x34528804,0x353a66f9,0x34d5a47e,0xb4028d3d,0x35953084,0x35bbbc62,0xb5284807,0xb58e2017,0x35cc556c,0x35c50adf,0xb5b77e6f,0xb5cb68e9,0x35a6b6f3,0x3569cab3,0xb5c78b72,0xb5ac59b8,
0x3f803f80,0,0,0x3f803f80,0x3f803f80,0,0,0x3f803f80,0x3f803f80,0,0,0x3f803f80,0x3f803f80,0,0,0x3f803f80,
0x3f353f80,0x3f350000,0xbf350000,0x3f353f80,0xbf350000,0x3f353f80,0xbf35bf80,0xbf350000,0xbf35bf80,0xbf350000,0x3f350000,0xbf35bf80,0x3f350000,0xbf35bf80,0x3f353f80,0x3f350000,
0x3f80,0x3f800000,0xbf800000,0x3f80,0xbf80,0xbf800000,0x3f800000,0xbf80,0x3f80,0x3f800000,0xbf800000,0x3f80,0xbf80,0xbf800000,0x3f800000,0xbf80,
0xbf353f80,0x3f350000,0xbf350000,0xbf353f80,0x3f350000,0x3f35bf80,0xbf353f80,0x3f350000,0x3f35bf80,0xbf350000,0x3f350000,0x3f35bf80,0xbf350000,0xbf353f80,0x3f35bf80,0xbf350000,
0xbf803f80,0,0,0xbf803f80,0xbf803f80,0,0,0xbf803f80,0xbf803f80,0,0,0xbf803f80,0xbf803f80,0,0,0xbf803f80,
0xbf353f80,0xbf350000,0x3f350000,0xbf353f80,0x3f350000,0xbf353f80,0x3f35bf80,0x3f350000,0x3f35bf80,0x3f350000,0xbf350000,0x3f35bf80,0xbf350000,0x3f35bf80,0xbf353f80,0xbf350000,
0x3f80,0xbf800000,0x3f800000,0x3f80,0xbf80,0x3f800000,0xbf800000,0xbf80,0x3f80,0xbf800000,0x3f800000,0x3f80,0xbf80,0x3f800000,0xbf800000,0xbf80,
0x3f353f80,0xbf350000,0x3f350000,0x3f353f80,0xbf350000,0xbf35bf80,0x3f353f80,0xbf350000,0xbf35bf80,0x3f350000,0xbf350000,0xbf35bf80,0x3f350000,0x3f353f80,0xbf35bf80,0x3f350000,
0x3f80,0x3f80,0x3f223f46,0x3f223f46,0x3e2f3f7c,0xbe2fbf7c,0x3f423f27,0xbf42bf27,0x3eac3f71,0x3eac3f71,0x3f5c3f04,0x3f5c3f04,0x3efc3f5f,0xbefcbf5f,0x3f6f3eb8,0xbf6fbeb8,
0x3f80,0x3f80,0x3f46bf22,0x3f46bf22,0x3f093f58,0xbf09bf58,0x3ea1bf73,0xbea13f73,0x3f673edb,0x3f673edb,0xbe79bf78,0xbe79bf78,0x3f7ebdfb,0xbf7e3dfb,0xbf39bf31,0x3f393f31,
0x3f80,0x3f80,0xbf22bf46,0xbf22bf46,0x3f513f13,0xbf51bf13,0xbf7f3d97,0x3f7fbd97,0x3f71beac,0x3f71beac,0xbf043f5c,0xbf043f5c,0x3e89bf77,0xbe893f77,0x3ecf3f6a,0xbecfbf6a,
0x3f80,0x3f80,0xbf463f22,0xbf463f22,0x3f7a3e60,0xbf7abe60,0x3ee63f65,0xbee6bf65,0x3edbbf67,0x3edbbf67,0x3f78be79,0x3f78be79,0xbf4abf1d,0x3f4a3f1d,0xbcc9bf80,0x3cc93f80,
0x3f80,0x3f80,0x3f223f46,0x3f223f46,0x3f7cbe2f,0xbf7c3e2f,0x3f27bf42,0xbf273f42,0xbeacbf71,0xbeacbf71,0xbf5cbf04,0xbf5cbf04,0xbf5f3efc,0x3f5fbefc,0xbeb83f6f,0x3eb8bf6f,
0x3f80,0x3f80,0x3f46bf22,0x3f46bf22,0x3f58bf09,0xbf583f09,0xbf73bea1,0x3f733ea1,0xbf67bedb,0xbf67bedb,0x3e793f78,0x3e793f78,0x3dfb3f7e,0xbdfbbf7e,0x3f31bf39,0xbf313f39,
0x3f80,0x3f80,0xbf22bf46,0xbf22bf46,0x3f13bf51,0xbf133f51,0x3d973f7f,0xbd97bf7f,0xbf713eac,0xbf713eac,0x3f04bf5c,0x3f04bf5c,0x3f773e89,0xbf77be89,0xbf6a3ecf,0x3f6abecf,
0x3f80,0x3f80,0xbf463f22,0xbf463f22,0x3e60bf7a,0xbe603f7a,0x3f65bee6,0xbf653ee6,0xbedb3f67,0xbedb3f67,0xbf783e79,0xbf783e79,0x3f1dbf4a,0xbf1d3f4a,0x3f80bcc9,0xbf803cc9,
0x3f7b3e48,0x3f7b3e48,0x3f62bef1,0x3f62bef1,0x3f803cc9,0xbf80bcc9,0x3f4abf1d,0xbf4a3f1d,0x3f7dbe16,0x3f7dbe16,0x3f2cbf3e,0x3f2cbf3e,0x3f73bea1,0xbf733ea1,0x3f09bf58,0xbf093f58,
0xbf7bbe48,0xbf7bbe48,0x3ef13f62,0x3ef13f62,0xbf6f3eb8,0x3f6fbeb8,0x3f5f3efc,0xbf5fbefc,0xbf183f4e,0xbf183f4e,0x3f80bd49,0x3f80bd49,0xbd973f7f,0x3d97bf7f,0x3f51bf13,0xbf513f13,
0x3f7b3e48,0x3f7b3e48,0xbf623ef1,0xbf623ef1,0x3f39bf31,0xbf393f31,0xbdfb3f7e,0x3dfbbf7e,0xbe16bf7d,0xbe16bf7d,0x3f3e3f2c,0x3f3e3f2c,0xbf65bee6,0x3f653ee6,0x3f7abe60,0xbf7a3e60,
0xbf7bbe48,0xbf7bbe48,0xbef1bf62,0xbef1bf62,0xbecf3f6a,0x3ecfbf6a,0xbf773e89,0x3f77be89,0x3f4e3f18,0x3f4e3f18,0x3d493f80,0x3d493f80,0x3f42bf27,0xbf423f27,0x3f7c3e2f,0xbf7cbe2f,
0x3f7b3e48,0x3f7b3e48,0x3f62bef1,0x3f62bef1,0x3cc9bf80,0xbcc93f80,0xbf1dbf4a,0x3f1d3f4a,0xbf7d3e16,0xbf7d3e16,0xbf2c3f3e,0xbf2c3f3e,0x3ea13f73,0xbea1bf73,0x3f583f09,0xbf58bf09,
0xbf7bbe48,0xbf7bbe48,0x3ef13f62,0x3ef13f62,0x3eb83f6f,0xbeb8bf6f,0x3efcbf5f,0xbefc3f5f,0x3f18bf4e,0x3f18bf4e,0xbf803d49,0xbf803d49,0xbf7fbd97,0x3f7f3d97,0x3f133f51,0xbf13bf51,
0x3f7b3e48,0x3f7b3e48,0xbf623ef1,0xbf623ef1,0xbf31bf39,0x3f313f39,0x3f7e3dfb,0xbf7ebdfb,0x3e163f7d,0x3e163f7d,0xbf3ebf2c,0xbf3ebf2c,0x3ee6bf65,0xbee63f65,0x3e603f7a,0xbe60bf7a,
0xbf7bbe48,0xbf7bbe48,0xbef1bf62,0xbef1bf62,0x3f6a3ecf,0xbf6abecf,0x3e893f77,0xbe89bf77,0xbf4ebf18,0xbf4ebf18,0xbd49bf80,0xbd49bf80,0x3f273f42,0xbf27bf42,0xbe2f3f7c,0x3e2fbf7c,
0x3f800000,0x3f800000,0x3f46bf22,0x3f46bf22,0x3f7cbe2f,0xbf7c3e2f,0x3f27bf42,0xbf273f42,0x3f71beac,0x3f71beac,0x3f04bf5c,0x3f04bf5c,0x3f5fbefc,0xbf5f3efc,0x3eb8bf6f,0xbeb83f6f,
0x3f800000,0x3f800000,0xbf22bf46,0xbf22bf46,0x3f58bf09,0xbf583f09,0xbf73bea1,0x3f733ea1,0x3edbbf67,0x3edbbf67,0xbf783e79,0xbf783e79,0xbdfbbf7e,0x3dfb3f7e,0xbf313f39,0x3f31bf39,
0x3f800000,0x3f800000,0xbf463f22,0xbf463f22,0x3f13bf51,0xbf133f51,0x3d973f7f,0xbd97bf7f,0xbeacbf71,0xbeacbf71,0x3f5c3f04,0x3f5c3f04,0xbf77be89,0x3f773e89,0x3f6abecf,0xbf6a3ecf,
0x3f800000,0x3f800000,0x3f223f46,0x3f223f46,0x3e60bf7a,0xbe603f7a,0x3f65bee6,0xbf653ee6,0xbf67bedb,0xbf67bedb,0xbe79bf78,0xbe79bf78,0xbf1d3f4a,0x3f1dbf4a,0xbf803cc9,0x3f80bcc9,
0x3f800000,0x3f800000,0x3f46bf22,0x3f46bf22,0xbe2fbf7c,0x3e2f3f7c,0xbf42bf27,0x3f423f27,0xbf713eac,0xbf713eac,0xbf043f5c,0xbf043f5c,0x3efc3f5f,0xbefcbf5f,0x3f6f3eb8,0xbf6fbeb8,
0x3f800000,0x3f800000,0xbf22bf46,0xbf22bf46,0xbf09bf58,0x3f093f58,0xbea13f73,0x3ea1bf73,0xbedb3f67,0xbedb3f67,0x3f78be79,0x3f78be79,0x3f7ebdfb,0xbf7e3dfb,0xbf39bf31,0x3f393f31,
0x3f800000,0x3f800000,0xbf463f22,0xbf463f22,0xbf51bf13,0x3f513f13,0x3f7fbd97,0xbf7f3d97,0x3eac3f71,0x3eac3f71,0xbf5cbf04,0xbf5cbf04,0x3e89bf77,0xbe893f77,0x3ecf3f6a,0xbecfbf6a,
0x3f800000,0x3f800000,0x3f223f46,0x3f223f46,0xbf7abe60,0x3f7a3e60,0xbee6bf65,0x3ee63f65,0x3f673edb,0x3f673edb,0x3e793f78,0x3e793f78,0xbf4abf1d,0x3f4a3f1d,0xbcc9bf80,0x3cc93f80,
0x3e48bf7b,0x3e48bf7b,0xbef1bf62,0xbef1bf62,0x3cc9bf80,0xbcc93f80,0xbf1dbf4a,0x3f1d3f4a,0xbe16bf7d,0xbe16bf7d,0xbf3ebf2c,0xbf3ebf2c,0xbea1bf73,0x3ea13f73,0xbf58bf09,0x3f583f09,
0xbe483f7b,0xbe483f7b,0x3f62bef1,0x3f62bef1,0x3eb83f6f,0xbeb8bf6f,0x3efcbf5f,0xbefc3f5f,0x3f4e3f18,0x3f4e3f18,0xbd49bf80,0xbd49bf80,0x3f7f3d97,0xbf7fbd97,0xbf13bf51,0x3f133f51,
0x3e48bf7b,0x3e48bf7b,0x3ef13f62,0x3ef13f62,0xbf31bf39,0x3f313f39,0x3f7e3dfb,0xbf7ebdfb,0xbf7d3e16,0xbf7d3e16,0x3f2cbf3e,0x3f2cbf3e,0xbee63f65,0x3ee6bf65,0xbe60bf7a,0x3e603f7a,
0xbe483f7b,0xbe483f7b,0xbf623ef1,0xbf623ef1,0x3f6a3ecf,0xbf6abecf,0x3e893f77,0xbe89bf77,0x3f18bf4e,0x3f18bf4e,0x3f80bd49,0x3f80bd49,0xbf27bf42,0x3f273f42,0x3e2fbf7c,0xbe2f3f7c,
0x3e48bf7b,0x3e48bf7b,0xbef1bf62,0xbef1bf62,0xbf80bcc9,0x3f803cc9,0xbf4a3f1d,0x3f4abf1d,0x3e163f7d,0x3e163f7d,0x3f3e3f2c,0x3f3e3f2c,0x3f73bea1,0xbf733ea1,0x3f09bf58,0xbf093f58,
0xbe483f7b,0xbe483f7b,0x3f62bef1,0x3f62bef1,0x3f6fbeb8,0xbf6f3eb8,0xbf5fbefc,0x3f5f3efc,0xbf4ebf18,0xbf4ebf18,0x3d493f80,0x3d493f80,0xbd973f7f,0x3d97bf7f,0x3f51bf13,0xbf513f13,
0x3e48bf7b,0x3e48bf7b,0x3ef13f62,0x3ef13f62,0xbf393f31,0x3f39bf31,0x3dfbbf7e,0xbdfb3f7e,0x3f7dbe16,0x3f7dbe16,0xbf2c3f3e,0xbf2c3f3e,0xbf65bee6,0x3f653ee6,0x3f7abe60,0xbf7a3e60,
0xbe483f7b,0xbe483f7b,0xbf623ef1,0xbf623ef1,0x3ecfbf6a,0xbecf3f6a,0x3f77be89,0xbf773e89,0xbf183f4e,0xbf183f4e,0xbf803d49,0xbf803d49,0x3f42bf27,0xbf423f27,0x3f7c3e2f,0xbf7cbe2f,
0x3f803f80,0xbe483e48,0x3f803f80,0xbe483e48,0x3f803f80,0xbe483e48,0x3f803f80,0xbe483e48,0x3f803f80,0xbe483e48,0x3f803f80,0xbe483e48,0x3f803f80,0xbe483e48,0x3f803f80,0xbe483e48,
0x3f583f7c,0x3eb83cc9,0xbf58bf7c,0xbeb8bcc9,0x3e603f13,0x3f6abf31,0xbe60bf13,0xbf6a3f31,0xbf09be2f,0x3f6fbf80,0x3f093e2f,0xbf6f3f80,0xbf7abf51,0x3ecfbf39,0x3f7a3f51,0xbecf3f39,
0x3edb3f71,0x3f4ebe16,0x3edb3f71,0x3f4ebe16,0xbf67beac,0x3f18bf7d,0xbf67beac,0x3f18bf7d,0xbedbbf71,0xbf4e3e16,0xbedbbf71,0xbf4e3e16,0x3f673eac,0xbf183f7d,0x3f673eac,0xbf183f7d,
0xbdfb3f5f,0x3f7fbea1,0x3dfbbf5f,0xbf7f3ea1,0xbf1dbf77,0xbf27bee6,0x3f1d3f77,0x3f273ee6,0x3f7e3efc,0xbd973f73,0xbf7ebefc,0x3d97bf73,0xbf4a3e89,0x3f42bf65,0x3f4abe89,0xbf423f65,
0xbf223f46,0x3f62bef1,0xbf223f46,0x3f62bef1,0x3f22bf46,0xbf623ef1,0x3f22bf46,0xbf623ef1,0xbf223f46,0x3f62bef1,0xbf223f46,0x3f62bef1,0x3f22bf46,0xbf623ef1,0x3f22bf46,0xbf623ef1,
0xbf733f27,0x3efcbf1d,0x3f73bf27,0xbefc3f1d,0x3f653d97,0x3e893f7e,0xbf65bd97,0xbe89bf7e,0xbea1bf42,0xbf5fbf4a,0x3ea13f42,0x3f5f3f4a,0xbee63f7f,0x3f773dfb,0x3ee6bf7f,0xbf77bdfb,
0xbf783f04,0xbd49bf3e,0xbf783f04,0xbd49bf3e,0xbe793f5c,0x3f803f2c,0xbe793f5c,0x3f803f2c,0x3f78bf04,0x3d493f3e,0x3f78bf04,0x3d493f3e,0x3e79bf5c,0xbf80bf2c,0x3e79bf5c,0xbf80bf2c,
0xbf313eb8,0xbf13bf58,0x3f31beb8,0x3f133f58,0xbf803f6a,0x3e2fbe60,0x3f80bf6a,0xbe2f3e60,0xbf393f6f,0x3f513f09,0x3f39bf6f,0xbf51bf09,0xbcc93ecf,0x3f7c3f7a,0x3cc9becf,0xbf7cbf7a,
0,0xbf7b3f7b,0,0xbf7b3f7b,0,0xbf7b3f7b,0,0xbf7b3f7b,0,0xbf7b3f7b,0,0xbf7b3f7b,0,0xbf7b3f7b,0,0xbf7b3f7b,
0x3f093e2f,0xbf6f3f80,0xbf09be2f,0x3f6fbf80,0x3f7a3f51,0xbecf3f39,0xbf7abf51,0x3ecfbf39,0x3f583f7c,0x3eb83cc9,0xbf58bf7c,0xbeb8bcc9,0x3e603f13,0x3f6abf31,0xbe60bf13,0xbf6a3f31,
0x3f673eac,0xbf183f7d,0x3f673eac,0xbf183f7d,0x3edb3f71,0x3f4ebe16,0x3edb3f71,0x3f4ebe16,0xbf67beac,0x3f18bf7d,0xbf67beac,0x3f18bf7d,0xbedbbf71,0xbf4e3e16,0xbedbbf71,0xbf4e3e16,
0x3f7e3efc,0xbd973f73,0xbf7ebefc,0x3d97bf73,0xbf4a3e89,0x3f42bf65,0x3f4abe89,0xbf423f65,0x3dfbbf5f,0xbf7f3ea1,0xbdfb3f5f,0x3f7fbea1,0x3f1d3f77,0x3f273ee6,0xbf1dbf77,0xbf27bee6,
0x3f463f22,0x3ef13f62,0x3f463f22,0x3ef13f62,0xbf46bf22,0xbef1bf62,0xbf46bf22,0xbef1bf62,0x3f463f22,0x3ef13f62,0x3f463f22,0x3ef13f62,0xbf46bf22,0xbef1bf62,0xbf46bf22,0xbef1bf62,
0x3ea13f42,0x3f5f3f4a,0xbea1bf42,0xbf5fbf4a,0x3ee6bf7f,0xbf77bdfb,0xbee63f7f,0x3f773dfb,0xbf733f27,0x3efcbf1d,0x3f73bf27,0xbefc3f1d,0x3f653d97,0x3e893f7e,0xbf65bd97,0xbe89bf7e,
0xbe793f5c,0x3f803f2c,0xbe793f5c,0x3f803f2c,0x3f78bf04,0x3d493f3e,0x3f78bf04,0x3d493f3e,0x3e79bf5c,0xbf80bf2c,0x3e79bf5c,0xbf80bf2c,0xbf783f04,0xbd49bf3e,0xbf783f04,0xbd49bf3e,
0xbf393f6f,0x3f513f09,0x3f39bf6f,0xbf51bf09,0xbcc93ecf,0x3f7c3f7a,0x3cc9becf,0xbf7cbf7a,0x3f31beb8,0x3f133f58,0xbf313eb8,0xbf13bf58,0x3f80bf6a,0xbe2f3e60,0xbf803f6a,0x3e2fbe60,
0,0x3f7bbf7b,0,0x3f7bbf7b,0,0x3f7bbf7b,0,0x3f7bbf7b,0,0x3f7bbf7b,0,0x3f7bbf7b,0,0x3f7bbf7b,0,0x3f7bbf7b,
0xbf09be2f,0x3f6fbf80,0x3f093e2f,0xbf6f3f80,0xbf7abf51,0x3ecfbf39,0x3f7a3f51,0xbecf3f39,0xbf58bf7c,0xbeb8bcc9,0x3f583f7c,0x3eb83cc9,0xbe60bf13,0xbf6a3f31,0x3e603f13,0x3f6abf31,
0xbf67beac,0x3f18bf7d,0xbf67beac,0x3f18bf7d,0xbedbbf71,0xbf4e3e16,0xbedbbf71,0xbf4e3e16,0x3f673eac,0xbf183f7d,0x3f673eac,0xbf183f7d,0x3edb3f71,0x3f4ebe16,0x3edb3f71,0x3f4ebe16,
0xbf7ebefc,0x3d97bf73,0x3f7e3efc,0xbd973f73,0x3f4abe89,0xbf423f65,0xbf4a3e89,0x3f42bf65,0xbdfb3f5f,0x3f7fbea1,0x3dfbbf5f,0xbf7f3ea1,0xbf1dbf77,0xbf27bee6,0x3f1d3f77,0x3f273ee6,
0xbf46bf22,0xbef1bf62,0xbf46bf22,0xbef1bf62,0x3f463f22,0x3ef13f62,0x3f463f22,0x3ef13f62,0xbf46bf22,0xbef1bf62,0xbf46bf22,0xbef1bf62,0x3f463f22,0x3ef13f62,0x3f463f22,0x3ef13f62,
0xbea1bf42,0xbf5fbf4a,0x3ea13f42,0x3f5f3f4a,0xbee63f7f,0x3f773dfb,0x3ee6bf7f,0xbf77bdfb,0x3f73bf27,0xbefc3f1d,0xbf733f27,0x3efcbf1d,0xbf65bd97,0xbe89bf7e,0x3f653d97,0x3e893f7e,
0x3e79bf5c,0xbf80bf2c,0x3e79bf5c,0xbf80bf2c,0xbf783f04,0xbd49bf3e,0xbf783f04,0xbd49bf3e,0xbe793f5c,0x3f803f2c,0xbe793f5c,0x3f803f2c,0x3f78bf04,0x3d493f3e,0x3f78bf04,0x3d493f3e,
0x3f39bf6f,0xbf51bf09,0xbf393f6f,0x3f513f09,0x3cc9becf,0xbf7cbf7a,0xbcc93ecf,0x3f7c3f7a,0xbf313eb8,0xbf13bf58,0x3f31beb8,0x3f133f58,0xbf803f6a,0x3e2fbe60,0x3f80bf6a,0xbe2f3e60,
0x3f800000,0x3f7ff0e3,0x3f800000,0x3f6a5ad9,0x3f7fc38f,0x3f7f7808,0x3f2d1469,0x3ea5129f,0x3f7f0e58,0x3f7e868b,0xbdafb680,0xbef58035,0x3f7de0b1,0x3f7d1cdd,0xbf4ac77f,0xbf788486,
0x3f800000,0x3f7f5ce9,0x3f800000,0x3f650479,0x3f7d7474,0x3f7a4910,0x3f19c200,0x3e3857ec,0x3f75dec6,0x3f703b37,0xbe8e9a22,0xbf2da859,0x3f696591,0x3f61668a,0xbf6f6830,0xbf7eb069,
0x3f800000,0x3f7e2b72,0x3f800000,0x3f5f20db,0x3f78b47b,0x3f6faf1b,0x3f04f484,0x3d0a342f,0x3f633c5a,0x3f5389c7,0xbeebcbbb,0xbf5627fe,0x3f40d0da,0x3f2b561b,0xbf7f6ac7,0xbf671599,
0x3f800000,0x3f7c5d3a,0x3f800000,0x3f58b3a1,0x3f718f57,0x3f5fe4e9,0x3eddbe79,0xbde7fa9a,0x3f47de65,0x3f2a2a80,0xbf1ff6cb,0xbf71d19f,0x3f07a136,0x3ec27b55,0xbf796e4e,0xbf34768f,
0x3f800000,0x3f79f35e,0x3f800000,0x3f51c0c2,0x3f6816a8,0x3f4b41fa,0x3eaf713a,0xbe840270,0x3f24d225,0x3eed3063,0xbf43e200,0xbf7efcc9,0x3e8586ce,0x3d3c6dd5,0xbf5df6be,0xbed97cb9,
0x3f800000,0x3f76ef5b,0x3f800000,0x3f4a4c87,0x3f5c61c7,0x3f3238aa,0x3e7ee6e1,0xbecb2aae,0x3ef6e0cb,0x3e6fa8b2,0xbf604621,0xbf7cdf6c,0xbcfb49ba,0xbe9620d2,0xbf2f61a5,0xbdc27c39,
0x3f800000,0x3f73530e,0x3f800000,0x3f425b89,0x3f4e8d90,0x3f1553b7,0x3e1c76de,0xbf06f686,0x3e9aa086,0xbc16cb58,0xbf740bdd,0xbf6b99fb,0xbea395c5,0xbf19210f,0xbee363fa,0x3e7bdba4,
0x3f800000,0x3f6f20b0,0x3f800000,0x3f39f2ac,0x3f3ebc1b,0x3eea6681,0x3d621469,0xbf256bcb,0x3de1bc2e,0xbe80f8c0,0xbf7e70b0,0xbf4c3578,0xbf14b039,0xbf554aa4,0xbe28defc,0x3f0ee0db,
0,0x3cafea69,0,0x3ece0bea,0x3d2fe007,0x3d83db0a,0x3f3ca003,0x3f725470,0x3dafb680,0x3ddb7d37,0x3f7f0e58,0x3f60a6cf,0x3e039502,0x3e195be0,0x3f1c420c,0x3e75c35a,
0,0x3d9064b4,0,0x3ee4cbfe,0x3e1008b7,0x3e57278f,0x3f4cae79,0x3f7bd14d,0x3e8e9a22,0x3eb0eacb,0x3f75dec6,0x3f3c17d9,0x3ed25a09,0x3ef2bd43,0x3eb554ec,0xbdcefdb7,
0,0x3df475c0,0,0x3efafef7,0x3e72b651,0x3eb3dca5,0x3f5ac450,0x3f7fdaaf,0x3eebcbbb,0x3f102dd5,0x3f633c5a,0x3f0c42c9,0x3f286605,0x3f3e35c5,0x3d8a200a,0xbedc53c1,
0,0x3e2bf804,0,0x3f084b92,0x3ea986c4,0x3ef840c8,0x3f66becc,0x3f7e5a38,0x3f1ff6cb,0x3f3f41fc,0x3f47de65,0x3ea80b1f,0x3f591e6a,0x3f6cd007,0xbe667c66,0xbf3592e7,
0,0x3e5d4b1a,0,0x3f12c39a,0x3ed8106b,0x3f1ba299,0x3f708066,0x3f77583a,0x3f43e200,0x3f62df7b,0x3f24d225,0x3db5f8da,0x3f772417,0x3f7fba9e,0xbeff17b2,0xbf67c187,
0,0x3e870ada,0,0x3f1ce11f,0x3f0242b1,0x3f37c655,0x3f77f110,0x3f6afb8c,0x3f604621,0x3f78e3d6,0x3ef6e0cb,0xbe1f917b,0x3f7fe129,0x3f74bf62,0xbf3a7ca4,0xbf7ed7d4,
0,0x3e9f1cdf,0,0x3f269de3,0x3f173c07,0x3f4fefa8,0x3f7cfe73,0x3f5988ad,0x3f740bdd,0x3f7ffd39,0x3e9aa086,0xbec8477c,0x3f7294f8,0x3f4d26fd,0xbf655e0b,0xbf7822d1,
0,0x3eb6ccc3,0,0x3f2ff3e6,0x3f2ac082,0x3f6398ac,0x3f7f9c18,0x3f436051,0x3f7e70b0,0x3f77beb7,0x3de1bc2e,0xbf1a6293,0x3f5064af,0x3f0d9281,0xbf7c7eb0,0xbf546b3b,
0x35cccccd,0x35cccccd,0x35cccccd,0x35cccccd,0x35cccccd,0x35cccccd,0x35cccccd,0x35cccccd,0x35cccccd,0x35cccccd,0x35cccccd,0x35cccccd,0x35cccccd,0x35cccccd,0x35cccccd,0x35cccccd,
0x35ccc0b6,0x35cc4a54,0x35bb7be1,0x35b736c7,0x35cb55f5,0x35c9e42e,0x35b280af,0x35ad5c81,0x35c7f5e5,0x35c58c49,0x35a7cd68,0x35a1d6d2,0x35c2a8d8,0x35bf4d5a,0x359b7c6d,0x3594c224,
0x35cc9c72,0x35cac390,0x358a76bb,0x35760334,0x35c6f6c8,0x35c13f79,0x3554ba6c,0x3531652e,0x35b9abba,0x35b04e38,0x350c5a95,0x34cbebe7,0x35a53e0d,0x3598967c,0x347a57c9,0x33b4dd20,
0x35cc6006,0x35c83a73,0x35040ee5,0x3493798a,0x35bfbf49,0x35b31d87,0x335d204b,0xb4399548,0x35a29b2e,0x358e93bb,0xb4d3371a,0xb522888b,0x356eec58,0x353b8534,0xb557f0d6,0xb584563c,
0x35cc0b7a,0x35c4b238,0xb40c9200,0xb4e429d0,0x35b5c9e1,0x359fe51e,0xb53ca2fc,0xb57ff144,0x3583db51,0x354580a2,0xb59cb4cd,0xb5b36b4e,0x34f7673d,0x3434968b,0xb5c33cb1,0xb5cb8d5a,
0x35cb9ed5,0x35c02f5f,0xb5446691,0xb58aed14,0x35a93b06,0x35882200,0xb5ab5332,0xb5c17480,0x353dc04f,0x34bfba28,0xb5cbfd6e,0xb5ca4c56,0xb271455a,0xb4ce5acd,0xb5bc7b2f,0xb5a35df9,
0x35cb1a27,0x35bab7a7,0xb5a23933,0xb5bf868d,0x359a40ae,0x355901f0,0xb5cc556c,0xb5c78b72,0x34d5a47e,0xb34907c8,0xb5b19232,0xb58c4e1d,0xb502de37,0xb56de6c2,0xb535e995,0xb48718ca,
0x35ca7d7e,0x35b45208,0xb5c6d06b,0xb5cbc054,0x358911af,0x351b95de,0xb5b8de14,0xb5905ed9,0x3396be44,0xb4f03484,0xb52dfd61,0xb41b9694,0xb57501b2,0xb5aaa21d,0x34c97c83,0x35649af8,
0,0,0,0,0,0,0,0,0,0,0,0,0,0,0,0,
0x330cbb87,0x33e70786,0x3524d655,0x35370998,0x34439166,0x34899337,0x3548cbf9,0x355a1284,0x34b108e1,0x34d8115e,0x356ad291,0x357b01cb,0x34fe9498,0x35123d69,0x35854b1c,0x358cc31e,
0x338cb338,0x34667457,0x3596e669,0x35a3bec8,0x34c22b74,0x35079f03,0x35af0373,0x35b898a3,0x352cd9f0,0x35506ab5,0x35c066b8,0x35c65a74,0x3571f9a5,0x35889a01,0x35ca6529,0x35cc7ce0,
0x33d2f811,0x34ac1fa5,0x35c1dd26,0x35c9743e,0x350fe3b7,0x35469a3a,0x35ccaef3,0x35cb7b60,0x35790428,0x35930511,0x35c5e02f,0x35bbfc70,0x35a65953,0x35b613bd,0x35ae06f1,0x359c4d0e,
0x340c9200,0x34e429d0,0x35cc0b7a,0x35c4b238,0x353ca2fc,0x357ff144,0x35b5c9e1,0x359fe51e,0x359cb4cd,0x35b36b4e,0x3583db51,0x354580a2,0x35c33cb1,0x35cb8d5a,0x34f7673d,0x3434968b,
0x342f9760,0x350d88a2,0x35b3b8a6,0x3596797a,0x3566afbb,0x35990197,0x35606adb,0x35066f4c,0x35b57f95,0x35c71cab,0x341193e2,0xb47f4f2b,0x35ccca94,0x35c6322c,0xb5203930,0xb577041e,
0x34528804,0x35284807,0x357a0347,0x351110bd,0x3586b804,0x35adb1ef,0x33dd000f,0xb4b86384,0x35c5b679,0x35ccb421,0xb54c12f5,0xb5953084,0x35c210c7,0x35a6b6f3,0xb5b77e6f,0xb5c9fef3,
0x34755fcc,0x35423103,0x34c49c48,0xb42597c6,0x35982b04,0x35bd7339,0xb5304301,0xb5914253,0x35cc954b,0x35c3cc4e,0xb5b9679f,0xb5cbdfdd,0x35a41f31,0x35628401,0xb5c68241,0xb5a9ef63,
0x3f803f80,0,0,0x3f803f80,0x3f803f80,0,0,0x3f803f80,0x3f803f80,0,0,0x3f803f80,0x3f803f80,0,0,0x3f803f80,
0x3f353f80,0x3f350000,0xbf350000,0x3f353f80,0xbf350000,0x3f353f80,0xbf35bf80,0xbf350000,0xbf35bf80,0xbf350000,0x3f350000,0xbf35bf80,0x3f350000,0xbf35bf80,0x3f353f80,0x3f350000,
0x3f80,0x3f800000,0xbf800000,0x3f80,0xbf80,0xbf800000,0x3f800000,0xbf80,0x3f80,0x3f800000,0xbf800000,0x3f80,0xbf80,0xbf800000,0x3f800000,0xbf80,
0xbf353f80,0x3f350000,0xbf350000,0xbf353f80,0x3f350000,0x3f35bf80,0xbf353f80,0x3f350000,0x3f35bf80,0xbf350000,0x3f350000,0x3f35bf80,0xbf350000,0xbf353f80,0x3f35bf80,0xbf350000,
0xbf803f80,0,0,0xbf803f80,0xbf803f80,0,0,0xbf803f80,0xbf803f80,0,0,0xbf803f80,0xbf803f80,0,0,0xbf803f80,
0xbf353f80,0xbf350000,0x3f350000,0xbf353f80,0x3f350000,0xbf353f80,0x3f35bf80,0x3f350000,0x3f35bf80,0x3f350000,0xbf350000,0x3f35bf80,0xbf350000,0x3f35bf80,0xbf353f80,0xbf350000,
0x3f80,0xbf800000,0x3f800000,0x3f80,0xbf80,0x3f800000,0xbf800000,0xbf80,0x3f80,0xbf800000,0x3f800000,0x3f80,0xbf80,0x3f800000,0xbf800000,0xbf80,
0x3f353f80,0xbf350000,0x3f350000,0x3f353f80,0xbf350000,0xbf35bf80,0x3f353f80,0xbf350000,0xbf35bf80,0x3f350000,0xbf350000,0xbf35bf80,0x3f350000,0x3f353f80,0xbf35bf80,0x3f350000,
0x3f80,0x3f80,0x3f353f35,0x3f353f35,0x3e483f7b,0xbe48bf7b,0x3f553f0e,0xbf55bf0e,0x3ec43f6d,0x3ec43f6d,0x3f6d3ec4,0x3f6d3ec4,0x3f0e3f55,0xbf0ebf55,0x3f7b3e48,0xbf7bbe48,
0x3f80,0x3f80,0x3f35bf35,0x3f35bf35,0x3f0e3f55,0xbf0ebf55,0x3e48bf7b,0xbe483f7b,0x3f6d3ec4,0x3f6d3ec4,0xbec4bf6d,0xbec4bf6d,0x3f7bbe48,0xbf7b3e48,0xbf55bf0e,0x3f553f0e,
0x3f80,0x3f80,0xbf35bf35,0xbf35bf35,0x3f553f0e,0xbf55bf0e,0xbf7b3e48,0x3f7bbe48,0x3f6dbec4,0x3f6dbec4,0xbec43f6d,0xbec43f6d,0x3e48bf7b,0xbe483f7b,0x3f0e3f55,0xbf0ebf55,
0x3f80,0x3f80,0xbf353f35,0xbf353f35,0x3f7b3e48,0xbf7bbe48,0x3f0e3f55,0xbf0ebf55,0x3ec4bf6d,0x3ec4bf6d,0x3f6dbec4,0x3f6dbec4,0xbf55bf0e,0x3f553f0e,0xbe48bf7b,0x3e483f7b,
0x3f80,0x3f80,0x3f353f35,0x3f353f35,0x3f7bbe48,0xbf7b3e48,0x3f0ebf55,0xbf0e3f55,0xbec4bf6d,0xbec4bf6d,0xbf6dbec4,0xbf6dbec4,0xbf553f0e,0x3f55bf0e,0xbe483f7b,0x3e48bf7b,
0x3f80,0x3f80,0x3f35bf35,0x3f35bf35,0x3f55bf0e,0xbf553f0e,0xbf7bbe48,0x3f7b3e48,0xbf6dbec4,0xbf6dbec4,0x3ec43f6d,0x3ec43f6d,0x3e483f7b,0xbe48bf7b,0x3f0ebf55,0xbf0e3f55,
0x3f80,0x3f80,0xbf35bf35,0xbf35bf35,0x3f0ebf55,0xbf0e3f55,0x3e483f7b,0xbe48bf7b,0xbf6d3ec4,0xbf6d3ec4,0x3ec4bf6d,0x3ec4bf6d,0x3f7b3e48,0xbf7bbe48,0xbf553f0e,0x3f55bf0e,
0x3f80,0x3f80,0xbf353f35,0xbf353f35,0x3e48bf7b,0xbe483f7b,0x3f55bf0e,0xbf553f0e,0xbec43f6d,0xbec43f6d,0xbf6d3ec4,0xbf6d3ec4,0x3f0ebf55,0xbf0e3f55,0x3f7bbe48,0xbf7b3e48,
0x3f800000,0x3f800000,0x3f35bf35,0x3f35bf35,0x3f7bbe48,0xbf7b3e48,0x3f0ebf55,0xbf0e3f55,0x3f6dbec4,0x3f6dbec4,0x3ec4bf6d,0x3ec4bf6d,0x3f55bf0e,0xbf553f0e,0x3e48bf7b,0xbe483f7b,
0xbf800000,0xbf800000,0x3f353f35,0x3f353f35,0xbf553f0e,0x3f55bf0e,0x3f7b3e48,0xbf7bbe48,0xbec43f6d,0xbec43f6d,0x3f6dbec4,0x3f6dbec4,0x3e483f7b,0xbe48bf7b,0x3f0ebf55,0xbf0e3f55,
0x3f800000,0x3f800000,0xbf353f35,0xbf353f35,0x3f0ebf55,0xbf0e3f55,0x3e483f7b,0xbe48bf7b,0xbec4bf6d,0xbec4bf6d,0x3f6d3ec4,0x3f6d3ec4,0xbf7bbe48,0x3f7b3e48,0x3f55bf0e,0xbf553f0e,
0xbf800000,0xbf800000,0xbf35bf35,0xbf35bf35,0xbe483f7b,0x3e48bf7b,0xbf553f0e,0x3f55bf0e,0x3f6d3ec4,0x3f6d3ec4,0x3ec43f6d,0x3ec43f6d,0x3f0ebf55,0xbf0e3f55,0x3f7bbe48,0xbf7b3e48,
0x3f800000,0x3f800000,0x3f35bf35,0x3f35bf35,0xbe48bf7b,0x3e483f7b,0xbf55bf0e,0x3f553f0e,0xbf6d3ec4,0xbf6d3ec4,0xbec43f6d,0xbec43f6d,0x3f0e3f55,0xbf0ebf55,0x3f7b3e48,0xbf7bbe48,
0xbf800000,0xbf800000,0x3f353f35,0x3f353f35,0x3f0e3f55,0xbf0ebf55,0x3e48bf7b,0xbe483f7b,0x3ec4bf6d,0x3ec4bf6d,0xbf6d3ec4,0xbf6d3ec4,0xbf7b3e48,0x3f7bbe48,0x3f553f0e,0xbf55bf0e,
0x3f800000,0x3f800000,0xbf353f35,0xbf353f35,0xbf55bf0e,0x3f553f0e,0x3f7bbe48,0xbf7b3e48,0x3ec43f6d,0x3ec43f6d,0xbf6dbec4,0xbf6dbec4,0x3e48bf7b,0xbe483f7b,0x3f0e3f55,0xbf0ebf55,
0xbf800000,0xbf800000,0xbf35bf35,0xbf35bf35,0x3f7b3e48,0xbf7bbe48,0x3f0e3f55,0xbf0ebf55,0xbf6dbec4,0xbf6dbec4,0xbec4bf6d,0xbec4bf6d,0x3f553f0e,0xbf55bf0e,0x3e483f7b,0xbe48bf7b,
0x3f800000,0x3f800000,0x3f35bf35,0x3f35bf35,0x3f7bbe48,0xbf7b3e48,0x3f0ebf55,0xbf0e3f55,0x3f6dbec4,0x3f6dbec4,0x3ec4bf6d,0x3ec4bf6d,0x3f55bf0e,0xbf553f0e,0x3e48bf7b,0xbe483f7b,
0x3f800000,0x3f800000,0xbf35bf35,0xbf35bf35,0x3f55bf0e,0xbf553f0e,0xbf7bbe48,0x3f7b3e48,0x3ec4bf6d,0x3ec4bf6d,0xbf6d3ec4,0xbf6d3ec4,0xbe48bf7b,0x3e483f7b,0xbf0e3f55,0x3f0ebf55,
0x3f800000,0x3f800000,0xbf353f35,0xbf353f35,0x3f0ebf55,0xbf0e3f55,0x3e483f7b,0xbe48bf7b,0xbec4bf6d,0xbec4bf6d,0x3f6d3ec4,0x3f6d3ec4,0xbf7bbe48,0x3f7b3e48,0x3f55bf0e,0xbf553f0e,
0x3f800000,0x3f800000,0x3f353f35,0x3f353f35,0x3e48bf7b,0xbe483f7b,0x3f55bf0e,0xbf553f0e,0xbf6dbec4,0xbf6dbec4,0xbec4bf6d,0xbec4bf6d,0xbf0e3f55,0x3f0ebf55,0xbf7b3e48,0x3f7bbe48,
0x3f800000,0x3f800000,0x3f35bf35,0x3f35bf35,0xbe48bf7b,0x3e483f7b,0xbf55bf0e,0x3f553f0e,0xbf6d3ec4,0xbf6d3ec4,0xbec43f6d,0xbec43f6d,0x3f0e3f55,0xbf0ebf55,0x3f7b3e48,0xbf7bbe48,
0x3f800000,0x3f800000,0xbf35bf35,0xbf35bf35,0xbf0ebf55,0x3f0e3f55,0xbe483f7b,0x3e48bf7b,0xbec43f6d,0xbec43f6d,0x3f6dbec4,0x3f6dbec4,0x3f7bbe48,0xbf7b3e48,0xbf55bf0e,0x3f553f0e,
0x3f800000,0x3f800000,0xbf353f35,0xbf353f35,0xbf55bf0e,0x3f553f0e,0x3f7bbe48,0xbf7b3e48,0x3ec43f6d,0x3ec43f6d,0xbf6dbec4,0xbf6dbec4,0x3e48bf7b,0xbe483f7b,0x3f0e3f55,0xbf0ebf55,
0x3f800000,0x3f800000,0x3f353f35,0x3f353f35,0xbf7bbe48,0x3f7b3e48,0xbf0ebf55,0x3f0e3f55,0x3f6d3ec4,0x3f6d3ec4,0x3ec43f6d,0x3ec43f6d,0xbf55bf0e,0x3f553f0e,0xbe48bf7b,0x3e483f7b,
0xbf80,0xbf80,0xbf35bf35,0xbf35bf35,0xbe48bf7b,0x3e483f7b,0xbf55bf0e,0x3f553f0e,0xbec4bf6d,0xbec4bf6d,0xbf6dbec4,0xbf6dbec4,0xbf0ebf55,0x3f0e3f55,0xbf7bbe48,0x3f7b3e48,
0x3f80,0x3f80,0x3f35bf35,0x3f35bf35,0x3f0e3f55,0xbf0ebf55,0x3e48bf7b,0xbe483f7b,0x3f6d3ec4,0x3f6d3ec4,0xbec4bf6d,0xbec4bf6d,0x3f7bbe48,0xbf7b3e48,0xbf55bf0e,0x3f553f0e,
0xbf80,0xbf80,0x3f353f35,0x3f353f35,0xbf55bf0e,0x3f553f0e,0x3f7bbe48,0xbf7b3e48,0xbf6d3ec4,0xbf6d3ec4,0x3ec4bf6d,0x3ec4bf6d,0xbe483f7b,0x3e48bf7b,0xbf0ebf55,0x3f0e3f55,
0x3f80,0x3f80,0xbf353f35,0xbf353f35,0x3f7b3e48,0xbf7bbe48,0x3f0e3f55,0xbf0ebf55,0x3ec4bf6d,0x3ec4bf6d,0x3f6dbec4,0x3f6dbec4,0xbf55bf0e,0x3f553f0e,0xbe48bf7b,0x3e483f7b,
0xbf80,0xbf80,0xbf35bf35,0xbf35bf35,0xbf7b3e48,0x3f7bbe48,0xbf0e3f55,0x3f0ebf55,0x3ec43f6d,0x3ec43f6d,0x3f6d3ec4,0x3f6d3ec4,0x3f55bf0e,0xbf553f0e,0x3e48bf7b,0xbe483f7b,
0x3f80,0x3f80,0x3f35bf35,0x3f35bf35,0x3f55bf0e,0xbf553f0e,0xbf7bbe48,0x3f7b3e48,0xbf6dbec4,0xbf6dbec4,0x3ec43f6d,0x3ec43f6d,0x3e483f7b,0xbe48bf7b,0x3f0ebf55,0xbf0e3f55,
0xbf80,0xbf80,0x3f353f35,0x3f353f35,0xbf0e3f55,0x3f0ebf55,0xbe48bf7b,0x3e483f7b,0x3f6dbec4,0x3f6dbec4,0xbec43f6d,0xbec43f6d,0xbf7bbe48,0x3f7b3e48,0x3f55bf0e,0xbf553f0e,
0x3f80,0x3f80,0xbf353f35,0xbf353f35,0x3e48bf7b,0xbe483f7b,0x3f55bf0e,0xbf553f0e,0xbec43f6d,0xbec43f6d,0xbf6d3ec4,0xbf6d3ec4,0x3f0ebf55,0xbf0e3f55,0x3f7bbe48,0xbf7b3e48,
0x3f803f80,0,0x3f803f80,0,0x3f803f80,0,0x3f803f80,0,0x3f803f80,0,0x3f803f80,0,0x3f803f80,0,0x3f803f80,0,
0x3f553f7b,0x3f0ebe48,0xbf55bf7b,0xbf0e3e48,0x3e483f0e,0x3f7bbf55,0xbe48bf0e,0xbf7b3f55,0xbf0ebe48,0x3f55bf7b,0x3f0e3e48,0xbf553f7b,0xbf7bbf55,0x3e48bf0e,0x3f7b3f55,0xbe483f0e,
0x3ec43f6d,0x3f6dbec4,0x3ec43f6d,0x3f6dbec4,0xbf6dbec4,0x3ec4bf6d,0xbf6dbec4,0x3ec4bf6d,0xbec4bf6d,0xbf6d3ec4,0xbec4bf6d,0xbf6d3ec4,0x3f6d3ec4,0xbec43f6d,0x3f6d3ec4,0xbec43f6d,
0xbe483f55,0x3f7bbf0e,0x3e48bf55,0xbf7b3f0e,0xbf0ebf7b,0xbf55be48,0x3f0e3f7b,0x3f553e48,0x3f7b3f0e,0x3e483f55,0xbf7bbf0e,0xbe48bf55,0xbf553e48,0x3f0ebf7b,0x3f55be48,0xbf0e3f7b,
0xbf353f35,0x3f35bf35,0xbf353f35,0x3f35bf35,0x3f35bf35,0xbf353f35,0x3f35bf35,0xbf353f35,0xbf353f35,0x3f35bf35,0xbf353f35,0x3f35bf35,0x3f35bf35,0xbf353f35,0x3f35bf35,0xbf353f35,
0xbf7b3f0e,0x3e48bf55,0x3f7bbf0e,0xbe483f55,0x3f553e48,0x3f0e3f7b,0xbf55be48,0xbf0ebf7b,0xbe48bf55,0xbf7bbf0e,0x3e483f55,0x3f7b3f0e,0xbf0e3f7b,0x3f55be48,0x3f0ebf7b,0xbf553e48,
0xbf6d3ec4,0xbec4bf6d,0xbf6d3ec4,0xbec4bf6d,0xbec43f6d,0x3f6d3ec4,0xbec43f6d,0x3f6d3ec4,0x3f6dbec4,0x3ec43f6d,0x3f6dbec4,0x3ec43f6d,0x3ec4bf6d,0xbf6dbec4,0x3ec4bf6d,0xbf6dbec4,
0xbf0e3e48,0xbf55bf7b,0x3f0ebe48,0x3f553f7b,0xbf7b3f55,0xbe48bf0e,0x3f7bbf55,0x3e483f0e,0xbf553f7b,0x3f0e3e48,0x3f55bf7b,0xbf0ebe48,0xbe483f0e,0x3f7b3f55,0x3e48bf0e,0xbf7bbf55,
0,0xbf803f80,0,0xbf803f80,0,0xbf803f80,0,0xbf803f80,0,0xbf803f80,0,0xbf803f80,0,0xbf803f80,0,0xbf803f80,
0x3f0e3e48,0xbf553f7b,0xbf0ebe48,0x3f55bf7b,0x3f7b3f55,0xbe483f0e,0xbf7bbf55,0x3e48bf0e,0x3f553f7b,0x3f0ebe48,0xbf55bf7b,0xbf0e3e48,0x3e483f0e,0x3f7bbf55,0xbe48bf0e,0xbf7b3f55,
0x3f6d3ec4,0xbec43f6d,0x3f6d3ec4,0xbec43f6d,0x3ec43f6d,0x3f6dbec4,0x3ec43f6d,0x3f6dbec4,0xbf6dbec4,0x3ec4bf6d,0xbf6dbec4,0x3ec4bf6d,0xbec4bf6d,0xbf6d3ec4,0xbec4bf6d,0xbf6d3ec4,
0x3f7b3f0e,0x3e483f55,0xbf7bbf0e,0xbe48bf55,0xbf553e48,0x3f0ebf7b,0x3f55be48,0xbf0e3f7b,0x3e48bf55,0xbf7b3f0e,0xbe483f55,0x3f7bbf0e,0x3f0e3f7b,0x3f553e48,0xbf0ebf7b,0xbf55be48,
0x3f353f35,0x3f353f35,0x3f353f35,0x3f353f35,0xbf35bf35,0xbf35bf35,0xbf35bf35,0xbf35bf35,0x3f353f35,0x3f353f35,0x3f353f35,0x3f353f35,0xbf35bf35,0xbf35bf35,0xbf35bf35,0xbf35bf35,
0x3e483f55,0x3f7b3f0e,0xbe48bf55,0xbf7bbf0e,0x3f0ebf7b,0xbf553e48,0xbf0e3f7b,0x3f55be48,0xbf7b3f0e,0x3e48bf55,0x3f7bbf0e,0xbe483f55,0x3f553e48,0x3f0e3f7b,0xbf55be48,0xbf0ebf7b,
0xbec43f6d,0x3f6d3ec4,0xbec43f6d,0x3f6d3ec4,0x3f6dbec4,0x3ec43f6d,0x3f6dbec4,0x3ec43f6d,0x3ec4bf6d,0xbf6dbec4,0x3ec4bf6d,0xbf6dbec4,0xbf6d3ec4,0xbec4bf6d,0xbf6d3ec4,0xbec4bf6d,
0xbf553f7b,0x3f0e3e48,0x3f55bf7b,0xbf0ebe48,0xbe483f0e,0x3f7b3f55,0x3e48bf0e,0xbf7bbf55,0x3f0ebe48,0x3f553f7b,0xbf0e3e48,0xbf55bf7b,0x3f7bbf55,0x3e483f0e,0xbf7b3f55,0xbe48bf0e,
0,0x3f80bf80,0,0x3f80bf80,0,0x3f80bf80,0,0x3f80bf80,0,0x3f80bf80,0,0x3f80bf80,0,0x3f80bf80,0,0x3f80bf80,
0xbf0ebe48,0x3f55bf7b,0x3f0e3e48,0xbf553f7b,0xbf7bbf55,0x3e48bf0e,0x3f7b3f55,0xbe483f0e,0xbf55bf7b,0xbf0e3e48,0x3f553f7b,0x3f0ebe48,0xbe48bf0e,0xbf7b3f55,0x3e483f0e,0x3f7bbf55,
0xbf6dbec4,0x3ec4bf6d,0xbf6dbec4,0x3ec4bf6d,0xbec4bf6d,0xbf6d3ec4,0xbec4bf6d,0xbf6d3ec4,0x3f6d3ec4,0xbec43f6d,0x3f6d3ec4,0xbec43f6d,0x3ec43f6d,0x3f6dbec4,0x3ec43f6d,0x3f6dbec4,
0xbf7bbf0e,0xbe48bf55,0x3f7b3f0e,0x3e483f55,0x3f55be48,0xbf0e3f7b,0xbf553e48,0x3f0ebf7b,0xbe483f55,0x3f7bbf0e,0x3e48bf55,0xbf7b3f0e,0xbf0ebf7b,0xbf55be48,0x3f0e3f7b,0x3f553e48,
0xbf35bf35,0xbf35bf35,0xbf35bf35,0xbf35bf35,0x3f353f35,0x3f353f35,0x3f353f35,0x3f353f35,0xbf35bf35,0xbf35bf35,0xbf35bf35,0xbf35bf35,0x3f353f35,0x3f353f35,0x3f353f35,0x3f353f35,
0xbe48bf55,0xbf7bbf0e,0x3e483f55,0x3f7b3f0e,0xbf0e3f7b,0x3f55be48,0x3f0ebf7b,0xbf553e48,0x3f7bbf0e,0xbe483f55,0xbf7b3f0e,0x3e48bf55,0xbf55be48,0xbf0ebf7b,0x3f553e48,0x3f0e3f7b,
0x3ec4bf6d,0xbf6dbec4,0x3ec4bf6d,0xbf6dbec4,0xbf6d3ec4,0xbec4bf6d,0xbf6d3ec4,0xbec4bf6d,0xbec43f6d,0x3f6d3ec4,0xbec43f6d,0x3f6d3ec4,0x3f6dbec4,0x3ec43f6d,0x3f6dbec4,0x3ec43f6d,
0x3f55bf7b,0xbf0ebe48,0xbf553f7b,0x3f0e3e48,0x3e48bf0e,0xbf7bbf55,0xbe483f0e,0x3f7b3f55,0xbf0e3e48,0xbf55bf7b,0x3f0ebe48,0x3f553f7b,0xbf7b3f55,0xbe48bf0e,0x3f7bbf55,0x3e483f0e,
0x3f800000,0x3f7fec43,0x3f800000,0x3f6a09a7,0x3f7fb10f,0x3f7f4e6d,0x3f2beb4a,0x3ea09ae5,0x3f7ec46d,0x3f7e1324,0xbdc8bd36,0xbefc5d27,0x3f7d3aac,0x3f7c3b28,0xbf4d9f02,0xbf79c79d,
0x3f800000,0x3f7f4e6d,0x3f800000,0x3f64aa59,0x3f7d3aac,0x3f79c79d,0x3f187fc0,0x3e2f10a2,0x3f74fa0b,0x3f6ed89e,0xbe94a031,0xbf3085bb,0x3f676bd8,0x3f5ebe05,0xbf710908,0xbf7e1324,
0x3f800000,0x3f7e1324,0x3f800000,0x3f5ebe05,0x3f7853f8,0x3f6ed89e,0x3f039c3d,0x3cc90ab0,0x3f61c598,0x3f514d3d,0xbef15aea,0xbf584853,0x3f3daef9,0x3f273656,0xbf7fb10f,0xbf64aa59,
0x3f800000,0x3f7c3b28,0x3f800000,0x3f584853,0x3f710908,0x3f5ebe05,0x3edae880,0xbdfab273,0x3f45e403,0x3f273656,0xbf226799,0xbf731447,0x3f039c3d,0x3eb8442a,0xbf7853f8,0xbf3085bb,
0x3f800000,0x3f79c79d,0x3f800000,0x3f514d3d,0x3f676bd8,0x3f49d112,0x3eac7cd4,0xbe888e93,0x3f226799,0x3ee63375,0xbf45e403,0xbf7f4e6d,0x3e78cfcc,0x3cc90ab0,0xbf5b941a,0xbecf7bca,
0x3f800000,0x3f76ba07,0x3f800000,0x3f49d112,0x3f5b941a,0x3f3085bb,0x3e78cfcc,0xbecf7bca,0x3ef15aea,0x3e605c13,0xbf61c598,0xbf7c3b28,0xbd48fb30,0xbea09ae5,0xbf2beb4a,0xbd96a905,
0x3f800000,0x3f731447,0x3f800000,0x3f41d870,0x3f4d9f02,0x3f13682a,0x3e164083,0xbf08f59b,0x3e94a031,0xbcc90ab0,0xbf74fa0b,0xbf6a09a7,0xbeac7cd4,0xbf1d7fd1,0xbedae880,0x3e888e93,
0x3f800000,0x3f6ed89e,0x3f800000,0x3f396842,0x3f3daef9,0x3ee63375,0x3d48fb30,0xbf273656,0x3dc8bd36,0xbe888e93,0xbf7ec46d,0xbf49d112,0xbf187fc0,0xbf584853,0xbe164083,0x3f13682a,
0,0x3cc90ab0,0,0x3ecf7bca,0x3d48fb30,0x3d96a905,0x3f3daef9,0x3f731447,0x3dc8bd36,0x3dfab273,0x3f7ec46d,0x3f5ebe05,0x3e164083,0x3e2f10a2,0x3f187fc0,0x3e605c13,
0,0x3d96a905,0,0x3ee63375,0x3e164083,0x3e605c13,0x3f4d9f02,0x3f7c3b28,0x3e94a031,0x3eb8442a,0x3f74fa0b,0x3f396842,0x3edae880,0x3efc5d27,0x3eac7cd4,0xbdfab273,
0,0x3dfab273,0,0x3efc5d27,0x3e78cfcc,0x3eb8442a,0x3f5b941a,0x3f7fec43,0x3ef15aea,0x3f13682a,0x3f61c598,0x3f08f59b,0x3f2beb4a,0x3f41d870,0x3d48fb30,0xbee63375,
0,0x3e2f10a2,0,0x3f08f59b,0x3eac7cd4,0x3efc5d27,0x3f676bd8,0x3f7e1324,0x3f226799,0x3f41d870,0x3f45e403,0x3ea09ae5,0x3f5b941a,0x3f6ed89e,0xbe78cfcc,0xbf396842,
0,0x3e605c13,0,0x3f13682a,0x3edae880,0x3f1d7fd1,0x3f710908,0x3f76ba07,0x3f45e403,0x3f64aa59,0x3f226799,0x3d96a905,0x3f7853f8,0x3f7fec43,0xbf039c3d,0xbf6a09a7,
0,0x3e888e93,0,0x3f1d7fd1,0x3f039c3d,0x3f396842,0x3f7853f8,0x3f6a09a7,0x3f61c598,0x3f79c79d,0x3ef15aea,0xbe2f10a2,0x3f7fb10f,0x3f731447,0xbf3daef9,0xbf7f4e6d,
0,0x3ea09ae5,0,0x3f273656,0x3f187fc0,0x3f514d3d,0x3f7d3aac,0x3f584853,0x3f74fa0b,0x3f7fec43,0x3e94a031,0xbecf7bca,0x3f710908,0x3f49d112,0xbf676bd8,0xbf76ba07,
0,0x3eb8442a,0,0x3f3085bb,0x3f2beb4a,0x3f64aa59,0x3f7fb10f,0x3f41d870,0x3f7ec46d,0x3f76ba07,0x3dc8bd36,0xbf1d7fd1,0x3f4d9f02,0x3f08f59b,0xbf7d3aac,0xbf514d3d,
0x35cccccd,0x35cccccd,0x35cccccd,0x35cccccd,0x35cccccd,0x35cccccd,0x35cccccd,0x35cccccd,0x35cccccd,0x35cccccd,0x35cccccd,0x35cccccd,0x35cccccd,0x35cccccd,0x35cccccd,0x35cccccd,
0x35ccbd02,0x35cc3ebe,0x35bb3aec,0x35b6eeae,0x35cb4283,0x35c9c8ed,0x35b2319e,0x35ad06a9,0x35c7d2e4,0x35c5619f,0x35a770fe,0x35a1740f,0x35c276a0,0x35bf13b1,0x359b138d,0x35945368,
0x35cc8da6,0x35ca9556,0x35898908,0x3573ff99,0x35c6a993,0x35c0d407,0x35529394,0x352f2067,0x35b92313,0x35afa9af,0x3509fd76,0x34c70ca3,0x35a47f35,0x3597bf2e,0x34706739,0x33a0c8f3,
0x35cc3ebe,0x35c7d2e4,0x35007bea,0x348c0d4f,0x35bf13b1,0x35b2319e,0x3320d559,0xb4488ec2,0x35a1740f,0x358d37c9,0xb4da7db8,0xb525fca2,0x356bd9dd,0x3538292a,0xb55b2291,0xb585c511,
0x35cbd057,0x35c3fb3c,0xb420975e,0xb4edcd1c,0x35b49e13,0x359e5003,0xb5411588,0xb581ec7b,0x3581ec7b,0x35411588,0xb59e5003,0xb5b49e13,0x34edcd1c,0x3420975e,0xb5c3fb3c,0xb5cbd057,
0x35cb4283,0x35bf13b1,0xb549e41f,0xb58d37c9,0x35a770fe,0x3585c511,0xb5ad06a9,0xb5c276a0,0x3538292a,0x34b37cdc,0xb5cc3ebe,0xb5c9c8ed,0xb320d559,0xb4da7db8,0xb5bb3aec,0xb5a1740f,
0x35ca9556,0x35b92313,0xb5a47f35,0xb5c0d407,0x3597bf2e,0x35529394,0xb5cc8da6,0xb5c6a993,0x34c70ca3,0xb3a0c8f3,0xb5afa9af,0xb5898908,0xb509fd76,0xb573ff99,0xb52f2067,0xb4706739,
0x35c9c8ed,0x35b2319e,0xb5c7d2e4,0xb5cb4283,0x3585c511,0x351369bb,0xb5b6eeae,0xb58d37c9,0x3320d559,0xb5007bea,0xb525fca2,0xb3f10e6e,0xb57bffb5,0xb5ad06a9,0x34da7db8,0x356bd9dd,
0,0,0,0,0,0,0,0,0,0,0,0,0,0,0,0,
0x3320d559,0x33f10e6e,0x3525fca2,0x3538292a,0x34488ec2,0x348c0d4f,0x3549e41f,0x355b2291,0x34b37cdc,0x34da7db8,0x356bd9dd,0x357bffb5,0x35007bea,0x351369bb,0x3585c511,0x358d37c9,
0x33a0c8f3,0x34706739,0x3597bf2e,0x35a47f35,0x34c70ca3,0x3509fd76,0x35afa9af,0x35b92313,0x352f2067,0x35529394,0x35c0d407,0x35c6a993,0x3573ff99,0x35898908,0x35ca9556,0x35cc8da6,
0x33f10e6e,0x34b37cdc,0x35c276a0,0x35c9c8ed,0x351369bb,0x3549e41f,0x35ccbd02,0x35cb4283,0x357bffb5,0x35945368,0x35c5619f,0x35bb3aec,0x35a770fe,0x35b6eeae,0x35ad06a9,0x359b138d,
0x3420975e,0x34edcd1c,0x35cbd057,0x35c3fb3c,0x35411588,0x3581ec7b,0x35b49e13,0x359e5003,0x359e5003,0x35b49e13,0x3581ec7b,0x35411588,0x35c3fb3c,0x35cbd057,0x34edcd1c,0x3420975e,
0x34488ec2,0x351369bb,0x35b2319e,0x35945368,0x356bd9dd,0x359b138d,0x355b2291,0x35007bea,0x35b6eeae,0x35c7d2e4,0x33f10e6e,0xb48c0d4f,0x35ccbd02,0x35c5619f,0xb525fca2,0xb57bffb5,
0x34706739,0x352f2067,0x3573ff99,0x3509fd76,0x35898908,0x35afa9af,0x33a0c8f3,0xb4c70ca3,0x35c6a993,0x35cc8da6,0xb5529394,0xb597bf2e,0x35c0d407,0x35a47f35,0xb5b92313,0xb5ca9556,
0x348c0d4f,0x3549e41f,0x34b37cdc,0xb4488ec2,0x359b138d,0x35bf13b1,0xb538292a,0xb5945368,0x35ccbd02,0x35c276a0,0xb5bb3aec,0xb5cc3ebe,0x35a1740f,0x355b2291,0xb5c5619f,0xb5a770fe,
0x3f803f80,0,0,0x3f803f80,0x3f803f80,0,0,0x3f803f80,0x3f803f80,0,0,0x3f803f80,0x3f803f80,0,0,0x3f803f80,
0x3f353f80,0x3f350000,0xbf350000,0x3f353f80,0xbf350000,0x3f353f80,0xbf35bf80,0xbf350000,0xbf35bf80,0xbf350000,0x3f350000,0xbf35bf80,0x3f350000,0xbf35bf80,0x3f353f80,0x3f350000,
0x3f80,0x3f800000,0xbf800000,0x3f80,0xbf80,0xbf800000,0x3f800000,0xbf80,0x3f80,0x3f800000,0xbf800000,0x3f80,0xbf80,0xbf800000,0x3f800000,0xbf80,
0xbf353f80,0x3f350000,0xbf350000,0xbf353f80,0x3f350000,0x3f35bf80,0xbf353f80,0x3f350000,0x3f35bf80,0xbf350000,0x3f350000,0x3f35bf80,0xbf350000,0xbf353f80,0x3f35bf80,0xbf350000,
0xbf803f80,0,0,0xbf803f80,0xbf803f80,0,0,0xbf803f80,0xbf803f80,0,0,0xbf803f80,0xbf803f80,0,0,0xbf803f80,
0xbf353f80,0xbf350000,0x3f350000,0xbf353f80,0x3f350000,0xbf353f80,0x3f35bf80,0x3f350000,0x3f35bf80,0x3f350000,0xbf350000,0x3f35bf80,0xbf350000,0x3f35bf80,0xbf353f80,0xbf350000,
0x3f80,0xbf800000,0x3f800000,0x3f80,0xbf80,0x3f800000,0xbf800000,0xbf80,0x3f80,0xbf800000,0x3f800000,0x3f80,0xbf80,0x3f800000,0xbf800000,0xbf80,
0x3f353f80,0xbf350000,0x3f350000,0x3f353f80,0xbf350000,0xbf35bf80,0x3f353f80,0xbf350000,0xbf35bf80,0x3f350000,0xbf350000,0xbf35bf80,0x3f350000,0x3f353f80,0xbf35bf80,0x3f350000,
0x3f80,0x3f80,0x3f463f22,0x3f463f22,0x3e603f7a,0xbe60bf7a,0x3f653ee6,0xbf65bee6,0x3edb3f67,0x3edb3f67,0x3f783e79,0x3f783e79,0x3f1d3f4a,0xbf1dbf4a,0x3f803cc9,0xbf80bcc9,
0x3f80,0x3f80,0x3f22bf46,0x3f22bf46,0x3f133f51,0xbf13bf51,0x3d97bf7f,0xbd973f7f,0x3f713eac,0x3f713eac,0xbf04bf5c,0xbf04bf5c,0x3f77be89,0xbf773e89,0xbf6abecf,0x3f6a3ecf,
0x3f80,0x3f80,0xbf46bf22,0xbf46bf22,0x3f583f09,0xbf58bf09,0xbf733ea1,0x3f73bea1,0x3f67bedb,0x3f67bedb,0xbe793f78,0xbe793f78,0x3dfbbf7e,0xbdfb3f7e,0x3f313f39,0xbf31bf39,
0x3f80,0x3f80,0xbf223f46,0xbf223f46,0x3f7c3e2f,0xbf7cbe2f,0x3f273f42,0xbf27bf42,0x3eacbf71,0x3eacbf71,0x3f5cbf04,0x3f5cbf04,0xbf5fbefc,0x3f5f3efc,0xbeb8bf6f,0x3eb83f6f,
0x3f80,0x3f80,0x3f463f22,0x3f463f22,0x3f7abe60,0xbf7a3e60,0x3ee6bf65,0xbee63f65,0xbedbbf67,0xbedbbf67,0xbf78be79,0xbf78be79,0xbf4a3f1d,0x3f4abf1d,0xbcc93f80,0x3cc9bf80,
0x3f80,0x3f80,0x3f22bf46,0x3f22bf46,0x3f51bf13,0xbf513f13,0xbf7fbd97,0x3f7f3d97,0xbf71beac,0xbf71beac,0x3f043f5c,0x3f043f5c,0x3e893f77,0xbe89bf77,0x3ecfbf6a,0xbecf3f6a,
0x3f80,0x3f80,0xbf46bf22,0xbf46bf22,0x3f09bf58,0xbf093f58,0x3ea13f73,0xbea1bf73,0xbf673edb,0xbf673edb,0x3e79bf78,0x3e79bf78,0x3f7e3dfb,0xbf7ebdfb,0xbf393f31,0x3f39bf31,
0x3f80,0x3f80,0xbf223f46,0xbf223f46,0x3e2fbf7c,0xbe2f3f7c,0x3f42bf27,0xbf423f27,0xbeac3f71,0xbeac3f71,0xbf5c3f04,0xbf5c3f04,0x3efcbf5f,0xbefc3f5f,0x3f6fbeb8,0xbf6f3eb8,
0x3f7bbe48,0x3f7bbe48,0x3ef1bf62,0x3ef1bf62,0x3f6abecf,0xbf6a3ecf,0x3e89bf77,0xbe893f77,0x3f4ebf18,0x3f4ebf18,0x3d49bf80,0x3d49bf80,0x3f27bf42,0xbf273f42,0xbe2fbf7c,0x3e2f3f7c,
0xbf7b3e48,0xbf7b3e48,0x3f623ef1,0x3f623ef1,0xbf313f39,0x3f31bf39,0x3f7ebdfb,0xbf7e3dfb,0xbe163f7d,0xbe163f7d,0x3f3ebf2c,0x3f3ebf2c,0x3ee63f65,0xbee6bf65,0x3e60bf7a,0xbe603f7a,
0x3f7bbe48,0x3f7bbe48,0xbef13f62,0xbef13f62,0x3eb8bf6f,0xbeb83f6f,0x3efc3f5f,0xbefcbf5f,0xbf18bf4e,0xbf18bf4e,0x3f803d49,0x3f803d49,0xbf7f3d97,0x3f7fbd97,0x3f13bf51,0xbf133f51,
0xbf7b3e48,0xbf7b3e48,0xbf62bef1,0xbf62bef1,0x3cc93f80,0xbcc9bf80,0xbf1d3f4a,0x3f1dbf4a,0x3f7d3e16,0x3f7d3e16,0x3f2c3f3e,0x3f2c3f3e,0x3ea1bf73,0xbea13f73,0x3f58bf09,0xbf583f09,
0x3f7bbe48,0x3f7bbe48,0x3ef1bf62,0x3ef1bf62,0xbecfbf6a,0x3ecf3f6a,0xbf77be89,0x3f773e89,0xbf4e3f18,0xbf4e3f18,0xbd493f80,0xbd493f80,0x3f423f27,0xbf42bf27,0x3f7cbe2f,0xbf7c3e2f,
0xbf7b3e48,0xbf7b3e48,0x3f623ef1,0x3f623ef1,0x3f393f31,0xbf39bf31,0xbdfbbf7e,0x3dfb3f7e,0x3e16bf7d,0x3e16bf7d,0xbf3e3f2c,0xbf3e3f2c,0xbf653ee6,0x3f65bee6,0x3f7a3e60,0xbf7abe60,
0x3f7bbe48,0x3f7bbe48,0xbef13f62,0xbef13f62,0xbf6fbeb8,0x3f6f3eb8,0x3f5fbefc,0xbf5f3efc,0x3f183f4e,0x3f183f4e,0xbf80bd49,0xbf80bd49,0xbd97bf7f,0x3d973f7f,0x3f513f13,0xbf51bf13,
0xbf7b3e48,0xbf7b3e48,0xbf62bef1,0xbf62bef1,0x3f80bcc9,0xbf803cc9,0x3f4a3f1d,0xbf4abf1d,0xbf7dbe16,0xbf7dbe16,0xbf2cbf3e,0xbf2cbf3e,0x3f733ea1,0xbf73bea1,0x3f093f58,0xbf09bf58,
0x3f800000,0x3f800000,0x3f22bf46,0x3f22bf46,0x3f7abe60,0xbf7a3e60,0x3ee6bf65,0xbee63f65,0x3f67bedb,0x3f67bedb,0x3e79bf78,0x3e79bf78,0x3f4abf1d,0xbf4a3f1d,0x3cc9bf80,0xbcc93f80,
0x3f800000,0x3f800000,0xbf46bf22,0xbf46bf22,0x3f51bf13,0xbf513f13,0xbf7fbd97,0x3f7f3d97,0x3eacbf71,0x3eacbf71,0xbf5c3f04,0xbf5c3f04,0xbe89bf77,0x3e893f77,0xbecf3f6a,0x3ecfbf6a,
0x3f800000,0x3f800000,0xbf223f46,0xbf223f46,0x3f09bf58,0xbf093f58,0x3ea13f73,0xbea1bf73,0xbedbbf67,0xbedbbf67,0x3f783e79,0x3f783e79,0xbf7ebdfb,0x3f7e3dfb,0x3f39bf31,0xbf393f31,
0x3f800000,0x3f800000,0x3f463f22,0x3f463f22,0x3e2fbf7c,0xbe2f3f7c,0x3f42bf27,0xbf423f27,0xbf71beac,0xbf71beac,0xbf04bf5c,0xbf04bf5c,0xbefc3f5f,0x3efcbf5f,0xbf6f3eb8,0x3f6fbeb8,
0x3f800000,0x3f800000,0x3f22bf46,0x3f22bf46,0xbe60bf7a,0x3e603f7a,0xbf65bee6,0x3f653ee6,0xbf673edb,0xbf673edb,0xbe793f78,0xbe793f78,0x3f1d3f4a,0xbf1dbf4a,0x3f803cc9,0xbf80bcc9,
0x3f800000,0x3f800000,0xbf46bf22,0xbf46bf22,0xbf13bf51,0x3f133f51,0xbd973f7f,0x3d97bf7f,0xbeac3f71,0xbeac3f71,0x3f5cbf04,0x3f5cbf04,0x3f77be89,0xbf773e89,0xbf6abecf,0x3f6a3ecf,
0x3f800000,0x3f800000,0xbf223f46,0xbf223f46,0xbf58bf09,0x3f583f09,0x3f73bea1,0xbf733ea1,0x3edb3f67,0x3edb3f67,0xbf78be79,0xbf78be79,0x3dfbbf7e,0xbdfb3f7e,0x3f313f39,0xbf31bf39,
0x3f800000,0x3f800000,0x3f463f22,0x3f463f22,0xbf7cbe2f,0x3f7c3e2f,0xbf27bf42,0x3f273f42,0x3f713eac,0x3f713eac,0x3f043f5c,0x3f043f5c,0xbf5fbefc,0x3f5f3efc,0xbeb8bf6f,0x3eb83f6f,
0xbe48bf7b,0xbe48bf7b,0xbf62bef1,0xbf62bef1,0xbecfbf6a,0x3ecf3f6a,0xbf77be89,0x3f773e89,0xbf18bf4e,0xbf18bf4e,0xbf80bd49,0xbf80bd49,0xbf42bf27,0x3f423f27,0xbf7c3e2f,0x3f7cbe2f,
0x3e483f7b,0x3e483f7b,0x3ef1bf62,0x3ef1bf62,0x3f393f31,0xbf39bf31,0xbdfbbf7e,0x3dfb3f7e,0x3f7d3e16,0x3f7d3e16,0xbf2cbf3e,0xbf2cbf3e,0x3f65bee6,0xbf653ee6,0xbf7abe60,0x3f7a3e60,
0xbe48bf7b,0xbe48bf7b,0x3f623ef1,0x3f623ef1,0xbf6fbeb8,0x3f6f3eb8,0x3f5fbefc,0xbf5f3efc,0xbf4e3f18,0xbf4e3f18,0x3d49bf80,0x3d49bf80,0x3d973f7f,0xbd97bf7f,0xbf51bf13,0x3f513f13,
0x3e483f7b,0x3e483f7b,0xbef13f62,0xbef13f62,0x3f80bcc9,0xbf803cc9,0x3f4a3f1d,0xbf4abf1d,0x3e16bf7d,0x3e16bf7d,0x3f3ebf2c,0x3f3ebf2c,0xbf73bea1,0x3f733ea1,0xbf09bf58,0x3f093f58,
0xbe48bf7b,0xbe48bf7b,0xbf62bef1,0xbf62bef1,0xbf6a3ecf,0x3f6abecf,0xbe893f77,0x3e89bf77,0x3f183f4e,0x3f183f4e,0x3f803d49,0x3f803d49,0x3f27bf42,0xbf273f42,0xbe2fbf7c,0x3e2f3f7c,
0x3e483f7b,0x3e483f7b,0x3ef1bf62,0x3ef1bf62,0x3f31bf39,0xbf313f39,0xbf7e3dfb,0x3f7ebdfb,0xbf7dbe16,0xbf7dbe16,0x3f2c3f3e,0x3f2c3f3e,0x3ee63f65,0xbee6bf65,0x3e60bf7a,0xbe603f7a,
0xbe48bf7b,0xbe48bf7b,0x3f623ef1,0x3f623ef1,0xbeb83f6f,0x3eb8bf6f,0xbefcbf5f,0x3efc3f5f,0x3f4ebf18,0x3f4ebf18,0xbd493f80,0xbd493f80,0xbf7f3d97,0x3f7fbd97,0x3f13bf51,0xbf133f51,
0x3e483f7b,0x3e483f7b,0xbef13f62,0xbef13f62,0xbcc9bf80,0x3cc93f80,0x3f1dbf4a,0xbf1d3f4a,0xbe163f7d,0xbe163f7d,0xbf3e3f2c,0xbf3e3f2c,0x3ea1bf73,0xbea13f73,0x3f58bf09,0xbf583f09,
0x3f803f80,0x3e48be48,0x3f803f80,0x3e48be48,0x3f803f80,0x3e48be48,0x3f803f80,0x3e48be48,0x3f803f80,0x3e48be48,0x3f803f80,0x3e48be48,0x3f803f80,0x3e48be48,0x3f803f80,0x3e48be48,
0x3f513f7a,0x3f39becf,0xbf51bf7a,0xbf393ecf,0x3e2f3f09,0x3f80bf6f,0xbe2fbf09,0xbf803f6f,0xbf13be60,0x3f31bf6a,0x3f133e60,0xbf313f6a,0xbf7cbf58,0xbcc9beb8,0x3f7c3f58,0x3cc93eb8,
0x3eac3f67,0x3f7dbf18,0x3eac3f67,0x3f7dbf18,0xbf71bedb,0x3e16bf4e,0xbf71bedb,0x3e16bf4e,0xbeacbf67,0xbf7d3f18,0xbeacbf67,0xbf7d3f18,0x3f713edb,0xbe163f4e,0x3f713edb,0xbe163f4e,
0xbe893f4a,0x3f65bf42,0x3e89bf4a,0xbf653f42,0xbefcbf7e,0xbf733d97,0x3efc3f7e,0x3f73bd97,0x3f773f1d,0x3ee63f27,0xbf77bf1d,0xbee6bf27,0xbf5f3dfb,0x3ea1bf7f,0x3f5fbdfb,0xbea13f7f,
0xbf463f22,0x3ef1bf62,0xbf463f22,0x3ef1bf62,0x3f46bf22,0xbef13f62,0x3f46bf22,0xbef13f62,0xbf463f22,0x3ef1bf62,0xbf463f22,0x3ef1bf62,0x3f46bf22,0xbef13f62,0x3f46bf22,0xbef13f62,
0xbf7f3ee6,0xbdfbbf77,0x3f7fbee6,0x3dfb3f77,0x3f423ea1,0x3f4a3f5f,0xbf42bea1,0xbf4abf5f,0xbd97bf65,0xbf7ebe89,0x3d973f65,0x3f7e3e89,0xbf273f73,0x3f1dbefc,0x3f27bf73,0xbf1d3efc,
0xbf5c3e79,0xbf2cbf80,0xbf5c3e79,0xbf2cbf80,0xbf043f78,0x3f3e3d49,0xbf043f78,0x3f3e3d49,0x3f5cbe79,0x3f2c3f80,0x3f5cbe79,0x3f2c3f80,0x3f04bf78,0xbf3ebd49,0x3f04bf78,0xbf3ebd49,
0xbecf3cc9,0xbf7abf7c,0x3ecfbcc9,0x3f7a3f7c,0xbf6f3f39,0xbf09bf51,0x3f6fbf39,0x3f093f51,0xbf6a3f80,0x3e60be2f,0x3f6abf80,0xbe603e2f,0xbeb83f31,0x3f583f13,0x3eb8bf31,0xbf58bf13,
0,0xbf7b3f7b,0,0xbf7b3f7b,0,0xbf7b3f7b,0,0xbf7b3f7b,0,0xbf7b3f7b,0,0xbf7b3f7b,0,0xbf7b3f7b,0,0xbf7b3f7b,
0x3f133e60,0xbf313f6a,0xbf13be60,0x3f31bf6a,0x3f7c3f58,0x3cc93eb8,0xbf7cbf58,0xbcc9beb8,0x3f513f7a,0x3f39becf,0xbf51bf7a,0xbf393ecf,0x3e2f3f09,0x3f80bf6f,0xbe2fbf09,0xbf803f6f,
0x3f713edb,0xbe163f4e,0x3f713edb,0xbe163f4e,0x3eac3f67,0x3f7dbf18,0x3eac3f67,0x3f7dbf18,0xbf71bedb,0x3e16bf4e,0xbf71bedb,0x3e16bf4e,0xbeacbf67,0xbf7d3f18,0xbeacbf67,0xbf7d3f18,
0x3f773f1d,0x3ee63f27,0xbf77bf1d,0xbee6bf27,0xbf5f3dfb,0x3ea1bf7f,0x3f5fbdfb,0xbea13f7f,0x3e89bf4a,0xbf653f42,0xbe893f4a,0x3f65bf42,0x3efc3f7e,0x3f73bd97,0xbefcbf7e,0xbf733d97,
0x3f223f46,0x3f623ef1,0x3f223f46,0x3f623ef1,0xbf22bf46,0xbf62bef1,0xbf22bf46,0xbf62bef1,0x3f223f46,0x3f623ef1,0x3f223f46,0x3f623ef1,0xbf22bf46,0xbf62bef1,0xbf22bf46,0xbf62bef1,
0x3d973f65,0x3f7e3e89,0xbd97bf65,0xbf7ebe89,0x3f27bf73,0xbf1d3efc,0xbf273f73,0x3f1dbefc,0xbf7f3ee6,0xbdfbbf77,0x3f7fbee6,0x3dfb3f77,0x3f423ea1,0x3f4a3f5f,0xbf42bea1,0xbf4abf5f,
0xbf043f78,0x3f3e3d49,0xbf043f78,0x3f3e3d49,0x3f5cbe79,0x3f2c3f80,0x3f5cbe79,0x3f2c3f80,0x3f04bf78,0xbf3ebd49,0x3f04bf78,0xbf3ebd49,0xbf5c3e79,0xbf2cbf80,0xbf5c3e79,0xbf2cbf80,
0xbf6a3f80,0x3e60be2f,0x3f6abf80,0xbe603e2f,0xbeb83f31,0x3f583f13,0x3eb8bf31,0xbf58bf13,0x3ecfbcc9,0x3f7a3f7c,0xbecf3cc9,0xbf7abf7c,0x3f6fbf39,0x3f093f51,0xbf6f3f39,0xbf09bf51,
0,0x3f7bbf7b,0,0x3f7bbf7b,0,0x3f7bbf7b,0,0x3f7bbf7b,0,0x3f7bbf7b,0,0x3f7bbf7b,0,0x3f7bbf7b,0,0x3f7bbf7b,
0xbf13be60,0x3f31bf6a,0x3f133e60,0xbf313f6a,0xbf7cbf58,0xbcc9beb8,0x3f7c3f58,0x3cc93eb8,0xbf51bf7a,0xbf393ecf,0x3f513f7a,0x3f39becf,0xbe2fbf09,0xbf803f6f,0x3e2f3f09,0x3f80bf6f,
0xbf71bedb,0x3e16bf4e,0xbf71bedb,0x3e16bf4e,0xbeacbf67,0xbf7d3f18,0xbeacbf67,0xbf7d3f18,0x3f713edb,0xbe163f4e,0x3f713edb,0xbe163f4e,0x3eac3f67,0x3f7dbf18,0x3eac3f67,0x3f7dbf18,
0xbf77bf1d,0xbee6bf27,0x3f773f1d,0x3ee63f27,0x3f5fbdfb,0xbea13f7f,0xbf5f3dfb,0x3ea1bf7f,0xbe893f4a,0x3f65bf42,0x3e89bf4a,0xbf653f42,0xbefcbf7e,0xbf733d97,0x3efc3f7e,0x3f73bd97,
0xbf22bf46,0xbf62bef1,0xbf22bf46,0xbf62bef1,0x3f223f46,0x3f623ef1,0x3f223f46,0x3f623ef1,0xbf22bf46,0xbf62bef1,0xbf22bf46,0xbf62bef1,0x3f223f46,0x3f623ef1,0x3f223f46,0x3f623ef1,
0xbd97bf65,0xbf7ebe89,0x3d973f65,0x3f7e3e89,0xbf273f73,0x3f1dbefc,0x3f27bf73,0xbf1d3efc,0x3f7fbee6,0x3dfb3f77,0xbf7f3ee6,0xbdfbbf77,0xbf42bea1,0xbf4abf5f,0x3f423ea1,0x3f4a3f5f,
0x3f04bf78,0xbf3ebd49,0x3f04bf78,0xbf3ebd49,0xbf5c3e79,0xbf2cbf80,0xbf5c3e79,0xbf2cbf80,0xbf043f78,0x3f3e3d49,0xbf043f78,0x3f3e3d49,0x3f5cbe79,0x3f2c3f80,0x3f5cbe79,0x3f2c3f80,
0x3f6abf80,0xbe603e2f,0xbf6a3f80,0x3e60be2f,0x3eb8bf31,0xbf58bf13,0xbeb83f31,0x3f583f13,0xbecf3cc9,0xbf7abf7c,0x3ecfbcc9,0x3f7a3f7c,0xbf6f3f39,0xbf09bf51,0x3f6fbf39,0x3f093f51,
0x3f800000,0x3f7fe705,0x3f800000,0x3f69b7e4,0x3f7f9c18,0x3f7f1f49,0x3f2ac082,0x3e9c1faf,0x3f7e70b0,0x3f7d906e,0xbde1bc2e,0xbf019573,0x3f7c7eb0,0x3f7b3bab,0xbf5064af,0xbf7aed37,
0x3f800000,0x3f7f3f54,0x3f800000,0x3f644fac,0x3f7cfe73,0x3f7940c0,0x3f173c07,0x3e25c58c,0x3f740bdd,0x3f6d67a1,0xbe9aa086,0xbf33587a,0x3f655e0b,0x3f5bfb34,0xbf7294f8,0xbf7d57de,
0x3f800000,0x3f7dfa38,0x3f800000,0x3f5e5aa6,0x3f77f110,0x3f6dfcf2,0x3f0242b1,0x3c7b514b,0x3f604621,0x3f4f0417,0xbef6e0cb,0xbf5a5ba0,0x3f3a7ca4,0x3f2302d3,0xbf7fe129,0xbf62241a,
0x3f800000,0x3f7c187a,0x3f800000,0x3f57dc7f,0x3f708066,0x3f5d924d,0x3ed8106b,0xbe06b26e,0x3f43e200,0x3f24381a,0xbf24d225,0xbf74484b,0x3eff17b2,0x3eadf73c,0xbf772417,0xbf2c800f,
0x3f800000,0x3f799b43,0x3f800000,0x3f50d937,0x3f66becc,0x3f485bca,0x3ea986c4,0xbe8d17c0,0x3f1ff6cb,0x3edf28a9,0xbf47de65,0xbf7f90b1,0x3e667c66,0x3b490fc6,0xbf591e6a,0xbec5625c,
0x3f800000,0x3f76841b,0x3f800000,0x3f495521,0x3f5ac450,0x3f2ecef7,0x3e72b651,0xbed3c867,0x3eebcbbb,0x3e5101f1,0xbf633c5a,0xbf7b87b2,0xbd8a200a,0xbeab0201,0xbf286605,0xbd55880e,
0x3f800000,0x3f72d4eb,0x3f800000,0x3f4154e1,0x3f4cae79,0x3f11796b,0x3e1008b7,0xbf0af1b7,0x3e8e9a22,0xbd2351cb,0xbf75dec6,0xbf686b39,0xbeb554ec,0xbf21cbfb,0xbed25a09,0x3e931f35,
0x3f800000,0x3f6e8ff8,0x3f800000,0x3f38dd65,0x3f3ca003,0x3ee1fb6a,0x3d2fe007,0xbf28fd41,0x3dafb680,0xbe901c2c,0xbf7f0e58,0xbf476085,0xbf1c420c,0xbf5b2c79,0xbe039502,0x3f17de12,
0,0x3ce22a7a,0,0x3ed0eb2a,0x3d621469,0x3da973ba,0x3f3ebc1b,0x3f73ced9,0x3de1bc2e,0x3e0cec4a,0x3f7e70b0,0x3f5cc7d1,0x3e28defc,0x3e44b0b9,0x3f14b039,0x3e4ada4f,
0,0x3d9cecf9,0,0x3ee79a5d,0x3e1c76de,0x3e698bba,0x3f4e8d90,0x3f7c9f8a,0x3e9aa086,0x3ebf926f,0x3f740bdd,0x3f36ad7f,0x3ee363fa,0x3f02ef9f,0x3ea395c5,0xbe1324ca,
0,0x3e007745,0,0x3efdbabb,0x3e7ee6e1,0x3ebca7af,0x3f5c61c7,0x3f7ff84a,0x3ef6e0cb,0x3f16999f,0x3f604621,0x3f05a02c,0x3f2f61a5,0x3f456439,0x3cfb49ba,0xbeeff7fb,
0,0x3e3228d4,0,0x3f099f4e,0x3eaf713a,0x3f003a06,0x3f6816a8,0x3f7dc68c,0x3f24d225,0x3f446337,0x3f43e200,0x3e9920fe,0x3f5df6be,0x3f70c501,0xbe8586ce,0xbf3d27b8,
0,0x3e636c83,0,0x3f140c5f,0x3eddbe79,0x3f1f599f,0x3f718f57,0x3f76167a,0x3f47de65,0x3f666771,0x3f1ff6cb,0x3d6ea038,0x3f796e4e,0x3f7fffb1,0xbf07a136,0xbf6c3624,
0,0x3e8a11f7,0,0x3f1e1e22,0x3f04f484,0x3f3b0629,0x3f78b47b,0x3f6912ae,0x3f633c5a,0x3f7a9c59,0x3eebcbbb,0xbe3e853e,0x3f7f6ac7,0x3f714c7a,0xbf40d0da,0xbf7fa6e3,
0,0x3ea21887,0,0x3f27ce61,0x3f19c200,0x3f52a649,0x3f7d7474,0x3f570348,0x3f75dec6,0x3f7fcbe2,0x3e8e9a22,0xbed6a399,0x3f6f6830,0x3f466354,0xbf696591,0xbf75341d,
0,0x3eb9bb1e,0,0x3f311722,0x3f2d1469,0x3f65b710,0x3f7fc38f,0x3f404c5c,0x3f7f0e58,0x3f75a67b,0x3dafb680,0xbf209393,0x3f4ac77f,0x3f044889,0xbf7de0b1,0xbf4e1689,
0x35cccccd,0x35cccccd,0x35cccccd,0x35cccccd,0x35cccccd,0x35cccccd,0x35cccccd,0x35cccccd,0x35cccccd,0x35cccccd,0x35cccccd,0x35cccccd,0x35cccccd,0x35cccccd,0x35cccccd,0x35cccccd,
0x35ccb8d1,0x35cc32aa,0x35baf983,0x35b6a623,0x35cb2e94,0x35c9ad2f,0x35b1e21f,0x35acb065,0x35c7af69,0x35c5367c,0x35a7142c,0x35a110e7,0x35c243ef,0x35bed993,0x359aaa4d,0x3593e451,
0x35cc7ce0,0x35ca6529,0x35889a01,0x3571f9a5,0x35c65a74,0x35c066b8,0x35506ab5,0x352cd9f0,0x35b898a3,0x35af0373,0x35079f03,0x34c22b74,0x35a3bec8,0x3596e669,0x34667457,0x338cb338,
0x35cc1907,0x35c76700,0x34f9cc4b,0x34849e0a,0x35be63f5,0x35b141d7,0x32c90dd6,0xb45783e3,0x35a0496e,0x358bd8c6,0xb4e1bf99,0xb5296d1f,0x3568c245,0x3534c922,0xb55e4f8b,0xb5873101,
0x35cb8d5a,0x35c33cb1,0xb434968b,0xb4f7673d,0x35b36b4e,0x359cb4cd,0xb54580a2,0xb583db51,0x357ff144,0x353ca2fc,0xb59fe51e,0xb5b5c9e1,0x34e429d0,0x340c9200,0xb5c4b238,0xb5cc0b7a,
0x35cad9f2,0x35bdec81,0xb54f5584,0xb58f79fb,0x35a59ce0,0x35836014,0xb5aeafb3,0xb5c36d09,0x353286ed,0x34a734c1,0xb5cc73c1,0xb5c9395b,0xb382a7d6,0xb4e6937a,0xb5b9ef61,0xb59f806a,
0x35c9fef3,0x35b77e6f,0xb5a6b6f3,0xb5c210c7,0x35953084,0x354c12f5,0xb5ccb421,0xb5c5b679,0x34b86384,0xb3dd000f,0xb5adb1ef,0xb586b804,0xb51110bd,0xb57a0347,0xb5284807,0xb4528804,
0x35c8fc89,0x35affc2a,0xb5c8bdc6,0xb5caacb2,0x358268a9,0x350b2c30,0xb5b4e9ae,0xb58a000c,0x31a0d96b,0xb508ce67,0xb51de84a,0xb3aad33e,0xb5816ffc,0xb5af56c7,0x34eb6521,0x3572fcea,
0,0,0,0,0,0,0,0,0,0,0,0,0,0,0,0,
0x3334eec8,0x33fb14c1,0x35272288,0x3539484b,0x344d8ba2,0x348e8710,0x354afbc9,0x355c3217,0x34b5f068,0x34dce98c,0x356ce099,0x357cfd04,0x3501ad39,0x351495b2,0x35863eb4,0x358dac1c,
0x33b4dd20,0x347a57c9,0x3598967c,0x35a53e0d,0x34cbebe7,0x350c5a95,0x35b04e38,0x35b9abba,0x3531652e,0x3554ba6c,0x35c13f79,0x35c6f6c8,0x35760334,0x358a76bb,0x35cac390,0x35cc9c72,
0x34078fc8,0x34bad62f,0x35c30be1,0x35ca193c,0x3516ec8c,0x354d29a4,0x35ccc6a2,0x35cb053d,0x357ef5cc,0x35959e88,0x35c4dec8,0x35ba7558,0x35a88507,0x35b7c5a7,0x35ac02a0,0x3599d6b0,
0x3434968b,0x34f7673d,0x35cb8d5a,0x35c33cb1,0x354580a2,0x3583db51,0x35b36b4e,0x359cb4cd,0x359fe51e,0x35b5c9e1,0x357ff144,0x353ca2fc,0x35c4b238,0x35cc0b7a,0x34e429d0,0x340c9200,
0x34617a10,0x351941f2,0x35b09fda,0x35922466,0x3570f5cb,0x359d1c2c,0x3555cd14,0x34f50196,0x35b852c1,0x35c87d14,0x33bee693,0xb4986a98,0x35cca31b,0x35c4852f,0xb52bb614,0xb580760f,
0x348718ca,0x3535e995,0x356de6c2,0x3502de37,0x358c4e1d,0x35b19232,0x334907c8,0xb4d5a47e,0x35c78b72,0x35cc556c,0xb55901f0,0xb59a40ae,0x35bf868d,0x35a23933,0xb5bab7a7,0xb5cb1a27,
0x349d5a2e,0x35517f65,0x34a2483f,0xb46b6e11,0x359de9c7,0x35c09d9b,0xb53ff996,0xb59752fa,0x35cccc8e,0x35c109fb,0xb5bcf81d,0xb5cc8582,0x359eb5dd,0x3553a742,0xb5c429b0,0xb5a4ded4,
0x3f803f80,0,0,0x3f803f80,0x3f803f80,0,0,0x3f803f80,0x3f803f80,0,0,0x3f803f80,0x3f803f80,0,0,0x3f803f80,
0x3f353f80,0x3f350000,0xbf350000,0x3f353f80,0xbf350000,0x3f353f80,0xbf35bf80,0xbf350000,0xbf35bf80,0xbf350000,0x3f350000,0xbf35bf80,0x3f350000,0xbf35bf80,0x3f353f80,0x3f350000,
0x3f80,0x3f800000,0xbf800000,0x3f80,0xbf80,0xbf800000,0x3f800000,0xbf80,0x3f80,0x3f800000,0xbf800000,0x3f80,0xbf80,0xbf800000,0x3f800000,0xbf80,
0xbf353f80,0x3f350000,0xbf350000,0xbf353f80,0x3f350000,0x3f35bf80,0xbf353f80,0x3f350000,0x3f35bf80,0xbf350000,0x3f350000,0x3f35bf80,0xbf350000,0xbf353f80,0x3f35bf80,0xbf350000,
0xbf803f80,0,0,0xbf803f80,0xbf803f80,0,0,0xbf803f80,0xbf803f80,0,0,0xbf803f80,0xbf803f80,0,0,0xbf803f80,
0xbf353f80,0xbf350000,0x3f350000,0xbf353f80,0x3f350000,0xbf353f80,0x3f35bf80,0x3f350000,0x3f35bf80,0x3f350000,0xbf350000,0x3f35bf80,0xbf350000,0x3f35bf80,0xbf353f80,0xbf350000,
0x3f80,0xbf800000,0x3f800000,0x3f80,0xbf80,0x3f800000,0xbf800000,0xbf80,0x3f80,0xbf800000,0x3f800000,0x3f80,0xbf80,0x3f800000,0xbf800000,0xbf80,
0x3f353f80,0xbf350000,0x3f350000,0x3f353f80,0xbf350000,0xbf35bf80,0x3f353f80,0xbf350000,0xbf35bf80,0x3f350000,0xbf350000,0xbf35bf80,0x3f350000,0x3f353f80,0xbf35bf80,0x3f350000,
0x3f80,0x3f80,0x3f553f0e,0x3f553f0e,0x3e793f78,0xbe79bf78,0x3f713eac,0xbf71beac,0x3ef13f62,0x3ef13f62,0x3f7f3dc9,0x3f7f3dc9,0x3f2c3f3e,0xbf2cbf3e,0x3f7dbe16,0xbf7d3e16,
0x3f80,0x3f80,0x3f0ebf55,0x3f0ebf55,0x3f183f4e,0xbf18bf4e,0xbd49bf80,0x3d493f80,0x3f753e95,0x3f753e95,0xbf22bf46,0xbf22bf46,0x3f71beac,0xbf713eac,0xbf78be79,0x3f783e79,
0x3f80,0x3f80,0xbf55bf0e,0xbf55bf0e,0x3f5c3f04,0xbf5cbf04,0xbf673edb,0x3f67bedb,0x3f62bef1,0x3f62bef1,0xbdc93f7f,0xbdc93f7f,0x3d49bf80,0xbd493f80,0x3f4e3f18,0xbf4ebf18,
0x3f80,0x3f80,0xbf0e3f55,0xbf0e3f55,0x3f7d3e16,0xbf7dbe16,0x3f3e3f2c,0xbf3ebf2c,0x3e95bf75,0x3e95bf75,0x3f46bf22,0x3f46bf22,0xbf67bedb,0x3f673edb,0xbf04bf5c,0x3f043f5c,
0x3f80,0x3f80,0x3f553f0e,0x3f553f0e,0x3f78be79,0xbf783e79,0x3eacbf71,0xbeac3f71,0xbef1bf62,0xbef1bf62,0xbf7fbdc9,0xbf7fbdc9,0xbf3e3f2c,0x3f3ebf2c,0x3e163f7d,0xbe16bf7d,
0x3f80,0x3f80,0x3f0ebf55,0x3f0ebf55,0x3f4ebf18,0xbf4e3f18,0xbf803d49,0x3f80bd49,0xbf75be95,0xbf75be95,0x3f223f46,0x3f223f46,0x3eac3f71,0xbeacbf71,0x3e79bf78,0xbe793f78,
0x3f80,0x3f80,0xbf55bf0e,0xbf55bf0e,0x3f04bf5c,0xbf043f5c,0x3edb3f67,0xbedbbf67,0xbf623ef1,0xbf623ef1,0x3dc9bf7f,0x3dc9bf7f,0x3f803d49,0xbf80bd49,0xbf183f4e,0x3f18bf4e,
0x3f80,0x3f80,0xbf0e3f55,0xbf0e3f55,0x3e16bf7d,0xbe163f7d,0x3f2cbf3e,0xbf2c3f3e,0xbe953f75,0xbe953f75,0xbf463f22,0xbf463f22,0x3edbbf67,0xbedb3f67,0x3f5cbf04,0xbf5c3f04,
0x3f6dbec4,0x3f6dbec4,0x3e48bf7b,0x3e48bf7b,0x3f4ebf18,0xbf4e3f18,0xbd49bf80,0x3d493f80,0x3f22bf46,0x3f22bf46,0xbe95bf75,0xbe95bf75,0x3edbbf67,0xbedb3f67,0xbf04bf5c,0x3f043f5c,
0xbf6d3ec4,0xbf6d3ec4,0x3f7b3e48,0x3f7b3e48,0xbf043f5c,0x3f04bf5c,0x3f67bedb,0xbf673edb,0x3dc93f7f,0x3dc93f7f,0x3ef1bf62,0x3ef1bf62,0x3f2c3f3e,0xbf2cbf3e,0xbe16bf7d,0x3e163f7d,
0x3f6dbec4,0x3f6dbec4,0xbe483f7b,0xbe483f7b,0x3e16bf7d,0xbe163f7d,0x3f3e3f2c,0xbf3ebf2c,0xbf46bf22,0xbf46bf22,0x3f75be95,0x3f75be95,0xbf713eac,0x3f71beac,0x3e79bf78,0xbe793f78,
0xbf6d3ec4,0xbf6d3ec4,0xbf7bbe48,0xbf7bbe48,0x3e793f78,0xbe79bf78,0xbeac3f71,0x3eacbf71,0x3f7fbdc9,0x3f7fbdc9,0x3f623ef1,0x3f623ef1,0x3d49bf80,0xbd493f80,0x3f18bf4e,0xbf183f4e,
0x3f6dbec4,0x3f6dbec4,0x3e48bf7b,0x3e48bf7b,0xbf18bf4e,0x3f183f4e,0xbf803d49,0x3f80bd49,0xbf223f46,0xbf223f46,0x3e953f75,0x3e953f75,0x3f673edb,0xbf67bedb,0x3f5cbf04,0xbf5c3f04,
0xbf6d3ec4,0xbf6d3ec4,0x3f7b3e48,0x3f7b3e48,0x3f5c3f04,0xbf5cbf04,0xbedbbf67,0x3edb3f67,0xbdc9bf7f,0xbdc9bf7f,0xbef13f62,0xbef13f62,0xbf3e3f2c,0x3f3ebf2c,0x3f7dbe16,0xbf7d3e16,
0x3f6dbec4,0x3f6dbec4,0xbe483f7b,0xbe483f7b,0xbf7dbe16,0x3f7d3e16,0x3f2cbf3e,0xbf2c3f3e,0x3f463f22,0x3f463f22,0xbf753e95,0xbf753e95,0xbeacbf71,0x3eac3f71,0x3f783e79,0xbf78be79,
0xbf6d3ec4,0xbf6d3ec4,0xbf7bbe48,0xbf7bbe48,0x3f78be79,0xbf783e79,0x3f713eac,0xbf71beac,0xbf7f3dc9,0xbf7f3dc9,0xbf62bef1,0xbf62bef1,0x3f803d49,0xbf80bd49,0x3f4e3f18,0xbf4ebf18,
0x3f800000,0x3f800000,0x3f0ebf55,0x3f0ebf55,0x3f78be79,0xbf783e79,0x3eacbf71,0xbeac3f71,0x3f62bef1,0x3f62bef1,0x3dc9bf7f,0x3dc9bf7f,0x3f3ebf2c,0xbf3e3f2c,0xbe16bf7d,0x3e163f7d,
0x3f800000,0x3f800000,0xbf55bf0e,0xbf55bf0e,0x3f4ebf18,0xbf4e3f18,0xbf803d49,0x3f80bd49,0x3e95bf75,0x3e95bf75,0xbf463f22,0xbf463f22,0xbeacbf71,0x3eac3f71,0xbe793f78,0x3e79bf78,
0x3f800000,0x3f800000,0xbf0e3f55,0xbf0e3f55,0x3f04bf5c,0xbf043f5c,0x3edb3f67,0xbedbbf67,0xbef1bf62,0xbef1bf62,0x3f7f3dc9,0x3f7f3dc9,0xbf80bd49,0x3f803d49,0x3f18bf4e,0xbf183f4e,
0x3f800000,0x3f800000,0x3f553f0e,0x3f553f0e,0x3e16bf7d,0xbe163f7d,0x3f2cbf3e,0xbf2c3f3e,0xbf75be95,0xbf75be95,0xbf22bf46,0xbf22bf46,0xbedb3f67,0x3edbbf67,0xbf5c3f04,0x3f5cbf04,
0x3f800000,0x3f800000,0x3f0ebf55,0x3f0ebf55,0xbe79bf78,0x3e793f78,0xbf71beac,0x3f713eac,0xbf623ef1,0xbf623ef1,0xbdc93f7f,0xbdc93f7f,0x3f2c3f3e,0xbf2cbf3e,0x3f7dbe16,0xbf7d3e16,
0x3f800000,0x3f800000,0xbf55bf0e,0xbf55bf0e,0xbf18bf4e,0x3f183f4e,0x3d493f80,0xbd49bf80,0xbe953f75,0xbe953f75,0x3f46bf22,0x3f46bf22,0x3f71beac,0xbf713eac,0xbf78be79,0x3f783e79,
0x3f800000,0x3f800000,0xbf0e3f55,0xbf0e3f55,0xbf5cbf04,0x3f5c3f04,0x3f67bedb,0xbf673edb,0x3ef13f62,0x3ef13f62,0xbf7fbdc9,0xbf7fbdc9,0x3d49bf80,0xbd493f80,0x3f4e3f18,0xbf4ebf18,
0x3f800000,0x3f800000,0x3f553f0e,0x3f553f0e,0xbf7dbe16,0x3f7d3e16,0xbf3ebf2c,0x3f3e3f2c,0x3f753e95,0x3f753e95,0x3f223f46,0x3f223f46,0xbf67bedb,0x3f673edb,0xbf04bf5c,0x3f043f5c,
0xbec4bf6d,0xbec4bf6d,0xbf7bbe48,0xbf7bbe48,0xbf18bf4e,0x3f183f4e,0xbf803d49,0x3f80bd49,0xbf46bf22,0xbf46bf22,0xbf753e95,0xbf753e95,0xbf67bedb,0x3f673edb,0xbf5c3f04,0x3f5cbf04,
0x3ec43f6d,0x3ec43f6d,0x3e48bf7b,0x3e48bf7b,0x3f5c3f04,0xbf5cbf04,0xbedbbf67,0x3edb3f67,0x3f7fbdc9,0x3f7fbdc9,0xbf62bef1,0xbf62bef1,0x3f3ebf2c,0xbf3e3f2c,0xbf7d3e16,0x3f7dbe16,
0xbec4bf6d,0xbec4bf6d,0x3f7b3e48,0x3f7b3e48,0xbf7dbe16,0x3f7d3e16,0x3f2cbf3e,0xbf2c3f3e,0xbf223f46,0xbf223f46,0xbe95bf75,0xbe95bf75,0x3eac3f71,0xbeacbf71,0xbf78be79,0x3f783e79,
0x3ec43f6d,0x3ec43f6d,0xbe483f7b,0xbe483f7b,0x3f78be79,0xbf783e79,0x3f713eac,0xbf71beac,0xbdc9bf7f,0xbdc9bf7f,0x3ef1bf62,0x3ef1bf62,0xbf80bd49,0x3f803d49,0xbf4ebf18,0x3f4e3f18,
0xbec4bf6d,0xbec4bf6d,0xbf7bbe48,0xbf7bbe48,0xbf4e3f18,0x3f4ebf18,0x3d493f80,0xbd49bf80,0x3f463f22,0x3f463f22,0x3f75be95,0x3f75be95,0x3edbbf67,0xbedb3f67,0xbf04bf5c,0x3f043f5c,
0x3ec43f6d,0x3ec43f6d,0x3e48bf7b,0x3e48bf7b,0x3f04bf5c,0xbf043f5c,0xbf673edb,0x3f67bedb,0xbf7f3dc9,0xbf7f3dc9,0x3f623ef1,0x3f623ef1,0x3f2c3f3e,0xbf2cbf3e,0xbe16bf7d,0x3e163f7d,
0xbec4bf6d,0xbec4bf6d,0x3f7b3e48,0x3f7b3e48,0xbe163f7d,0x3e16bf7d,0xbf3ebf2c,0x3f3e3f2c,0x3f22bf46,0x3f22bf46,0x3e953f75,0x3e953f75,0xbf713eac,0x3f71beac,0x3e79bf78,0xbe793f78,
0x3ec43f6d,0x3ec43f6d,0xbe483f7b,0xbe483f7b,0xbe79bf78,0x3e793f78,0x3eacbf71,0xbeac3f71,0x3dc93f7f,0x3dc93f7f,0xbef13f62,0xbef13f62,0x3d49bf80,0xbd493f80,0x3f18bf4e,0xbf183f4e,
0x3f803f80,0x3ec4bec4,0x3f803f80,0x3ec4bec4,0x3f803f80,0x3ec4bec4,0x3f803f80,0x3ec4bec4,0x3f803f80,0x3ec4bec4,0x3f803f80,0x3ec4bec4,0x3f803f80,0x3ec4bec4,0x3f803f80,0x3ec4bec4,
0x3f4e3f78,0x3f5cbf18,0xbf4ebf78,0xbf5c3f18,0x3e163f04,0x3f78bf7d,0xbe16bf04,0xbf783f7d,0xbf18be79,0x3f04bf4e,0x3f183e79,0xbf043f4e,0xbf7dbf5c,0xbe79be16,0x3f7d3f5c,0x3e793e16,
0x3e953f62,0x3f7fbf46,0x3e953f62,0x3f7fbf46,0xbf75bef1,0xbdc9bf22,0xbf75bef1,0xbdc9bf22,0xbe95bf62,0xbf7f3f46,0xbe95bf62,0xbf7f3f46,0x3f753ef1,0x3dc93f22,0x3f753ef1,0x3dc93f22,
0xbeac3f3e,0x3f3ebf67,0x3eacbf3e,0xbf3e3f67,0xbedbbf80,0xbf803eac,0x3edb3f80,0x3f80beac,0x3f713f2c,0x3f2c3edb,0xbf71bf2c,0xbf2cbedb,0xbf673d49,0x3d49bf71,0x3f67bd49,0xbd493f71,
0xbf553f0e,0x3e48bf7b,0xbf553f0e,0x3e48bf7b,0x3f55bf0e,0xbe483f7b,0x3f55bf0e,0xbe483f7b,0xbf553f0e,0x3e48bf7b,0xbf553f0e,0x3e48bf7b,0x3f55bf0e,0xbe483f7b,0x3f55bf0e,0xbe483f7b,
0xbf803eac,0xbedbbf80,0x3f80beac,0x3edb3f80,0x3f2c3edb,0x3f713f2c,0xbf2cbedb,0xbf71bf2c,0x3d49bf71,0xbf673d49,0xbd493f71,0x3f67bd49,0xbf3e3f67,0x3eacbf3e,0x3f3ebf67,0xbeac3f3e,
0xbf463dc9,0xbf62bf75,0xbf463dc9,0xbf62bf75,0xbf223f7f,0x3ef1be95,0xbf223f7f,0x3ef1be95,0x3f46bdc9,0x3f623f75,0x3f46bdc9,0x3f623f75,0x3f22bf7f,0xbef13e95,0x3f22bf7f,0xbef13e95,
0xbe79be16,0xbf7dbf5c,0x3e793e16,0x3f7d3f5c,0xbf5c3f18,0xbf4ebf78,0x3f5cbf18,0x3f4e3f78,0xbf783f7d,0xbe16bf04,0x3f78bf7d,0x3e163f04,0xbf043f4e,0x3f183e79,0x3f04bf4e,0xbf18be79,
0,0xbf6d3f6d,0,0xbf6d3f6d,0,0xbf6d3f6d,0,0xbf6d3f6d,0,0xbf6d3f6d,0,0xbf6d3f6d,0,0xbf6d3f6d,0,0xbf6d3f6d,
0x3f183e79,0xbf043f4e,0xbf18be79,0x3f04bf4e,0x3f7d3f5c,0x3e793e16,0xbf7dbf5c,0xbe79be16,0x3f4e3f78,0x3f5cbf18,0xbf4ebf78,0xbf5c3f18,0x3e163f04,0x3f78bf7d,0xbe16bf04,0xbf783f7d,
0x3f753ef1,0x3dc93f22,0x3f753ef1,0x3dc93f22,0x3e953f62,0x3f7fbf46,0x3e953f62,0x3f7fbf46,0xbf75bef1,0xbdc9bf22,0xbf75bef1,0xbdc9bf22,0xbe95bf62,0xbf7f3f46,0xbe95bf62,0xbf7f3f46,
0x3f713f2c,0x3f2c3edb,0xbf71bf2c,0xbf2cbedb,0xbf673d49,0x3d49bf71,0x3f67bd49,0xbd493f71,0x3eacbf3e,0xbf3e3f67,0xbeac3f3e,0x3f3ebf67,0x3edb3f80,0x3f80beac,0xbedbbf80,0xbf803eac,
0x3f0e3f55,0x3f7b3e48,0x3f0e3f55,0x3f7b3e48,0xbf0ebf55,0xbf7bbe48,0xbf0ebf55,0xbf7bbe48,0x3f0e3f55,0x3f7b3e48,0x3f0e3f55,0x3f7b3e48,0xbf0ebf55,0xbf7bbe48,0xbf0ebf55,0xbf7bbe48,
0xbd493f71,0x3f67bd49,0x3d49bf71,0xbf673d49,0x3f3ebf67,0xbeac3f3e,0xbf3e3f67,0x3eacbf3e,0xbf803eac,0xbedbbf80,0x3f80beac,0x3edb3f80,0x3f2c3edb,0x3f713f2c,0xbf2cbedb,0xbf71bf2c,
0xbf223f7f,0x3ef1be95,0xbf223f7f,0x3ef1be95,0x3f46bdc9,0x3f623f75,0x3f46bdc9,0x3f623f75,0x3f22bf7f,0xbef13e95,0x3f22bf7f,0xbef13e95,0xbf463dc9,0xbf62bf75,0xbf463dc9,0xbf62bf75,
0xbf783f7d,0xbe16bf04,0x3f78bf7d,0x3e163f04,0xbf043f4e,0x3f183e79,0x3f04bf4e,0xbf18be79,0x3e793e16,0x3f7d3f5c,0xbe79be16,0xbf7dbf5c,0x3f5cbf18,0x3f4e3f78,0xbf5c3f18,0xbf4ebf78,
0,0x3f6dbf6d,0,0x3f6dbf6d,0,0x3f6dbf6d,0,0x3f6dbf6d,0,0x3f6dbf6d,0,0x3f6dbf6d,0,0x3f6dbf6d,0,0x3f6dbf6d,
0xbf18be79,0x3f04bf4e,0x3f183e79,0xbf043f4e,0xbf7dbf5c,0xbe79be16,0x3f7d3f5c,0x3e793e16,0xbf4ebf78,0xbf5c3f18,0x3f4e3f78,0x3f5cbf18,0xbe16bf04,0xbf783f7d,0x3e163f04,0x3f78bf7d,
0xbf75bef1,0xbdc9bf22,0xbf75bef1,0xbdc9bf22,0xbe95bf62,0xbf7f3f46,0xbe95bf62,0xbf7f3f46,0x3f753ef1,0x3dc93f22,0x3f753ef1,0x3dc93f22,0x3e953f62,0x3f7fbf46,0x3e953f62,0x3f7fbf46,
0xbf71bf2c,0xbf2cbedb,0x3f713f2c,0x3f2c3edb,0x3f67bd49,0xbd493f71,0xbf673d49,0x3d49bf71,0xbeac3f3e,0x3f3ebf67,0x3eacbf3e,0xbf3e3f67,0xbedbbf80,0xbf803eac,0x3edb3f80,0x3f80beac,
0xbf0ebf55,0xbf7bbe48,0xbf0ebf55,0xbf7bbe48,0x3f0e3f55,0x3f7b3e48,0x3f0e3f55,0x3f7b3e48,0xbf0ebf55,0xbf7bbe48,0xbf0ebf55,0xbf7bbe48,0x3f0e3f55,0x3f7b3e48,0x3f0e3f55,0x3f7b3e48,
0x3d49bf71,0xbf673d49,0xbd493f71,0x3f67bd49,0xbf3e3f67,0x3eacbf3e,0x3f3ebf67,0xbeac3f3e,0x3f80beac,0x3edb3f80,0xbf803eac,0xbedbbf80,0xbf2cbedb,0xbf71bf2c,0x3f2c3edb,0x3f713f2c,
0x3f22bf7f,0xbef13e95,0x3f22bf7f,0xbef13e95,0xbf463dc9,0xbf62bf75,0xbf463dc9,0xbf62bf75,0xbf223f7f,0x3ef1be95,0xbf223f7f,0x3ef1be95,0x3f46bdc9,0x3f623f75,0x3f46bdc9,0x3f623f75,
0x3f78bf7d,0x3e163f04,0xbf783f7d,0xbe16bf04,0x3f04bf4e,0xbf18be79,0xbf043f4e,0x3f183e79,0xbe79be16,0xbf7dbf5c,0x3e793e16,0x3f7d3f5c,0xbf5c3f18,0xbf4ebf78,0x3f5cbf18,0x3f4e3f78,
0x3f800000,0x3f7fe129,0x3f800000,0x3f696591,0x3f7f84ab,0x3f7eea9d,0x3f299415,0x3e97a117,0x3f7e1324,0x3f7cfe73,0xbdfab273,0xbf04f484,0x3f7baccd,0x3f7a1e84,0xbf531849,0xbf7bf531,
0x3f800000,0x3f7f2f9d,0x3f800000,0x3f63f473,0x3f7cbfc9,0x3f78b47b,0x3f15f6d9,0x3e1c76de,0x3f731447,0x3f6be858,0xbea09ae5,0xbf36206c,0x3f633c5a,0x3f591e6a,0xbf740bdd,0xbf7c7eb0,
0x3f800000,0x3f7de0b1,0x3f800000,0x3f5df6be,0x3f778bc5,0x3f6d1c1d,0x3f00e7e4,0x3bc90f88,0x3f5ebe05,0x3f4cae79,0xbefc5d27,0xbf5c61c7,0x3f373a23,0x3f1ebc12,0xbf7ffb11,0xbf5f8327,
0x3f800000,0x3f7bf531,0x3f800000,0x3f577026,0x3f6ff573,0x3f5c61c7,0x3ed53641,0xbe1008b7,0x3f41d870,0x3f212ff9,0xbf273656,0xbf756d97,0x3ef6e0cb,0x3ea395c5,0xbf75dec6,0xbf286605,
0x3f800000,0x3f796e4e,0x3f800000,0x3f5064af,0x3f660f88,0x3f46e22a,0x3ea68f12,0xbe919ddd,0x3f1d7fd1,0x3ed8106b,0xbf49d112,0xbf7fc38f,0x3e541501,0xbc96c9b6,0xbf5695e5,0xbebb31a0,
0x3f800000,0x3f764d97,0x3f800000,0x3f48d8b3,0x3f59f26a,0x3f2d1469,0x3e6c9a7f,0xbed8106b,0x3ee63375,0x3e419b37,0xbf64aa59,0xbf7ac516,0xbdafb680,0xbeb554ec,0xbf24d225,0xbcfb49ba,
0x3f800000,0x3f7294f8,0x3f800000,0x3f40d0da,0x3f4bbbf8,0x3f0f8784,0x3e09cf86,0xbf0cead0,0x3e888e93,0xbd621469,0xbf76ba07,0xbf66becc,0xbebe1d4a,0xbf26050a,0xbec9b953,0x3e9d9e78,
0x3f800000,0x3f6e46be,0x3f800000,0x3f385216,0x3f3b8f3b,0x3eddbe79,0x3d16c32c,0xbf2ac082,0x3d96a905,0xbe97a117,0xbf7f4e6d,0xbf44e3f5,0xbf1ff6cb,0xbf5df6be,0xbde1bc2e,0x3f1c420c,
0,0x3cfb49ba,0,0x3ed25a09,0x3d7b2b74,0x3dbc3ac3,0x3f3fc767,0x3f748422,0x3dfab273,0x3e1c76de,0x3f7e1324,0x3f5ac450,0x3e3b6ecf,0x3e5a3997,0x3f10d3cd,0x3e354098,
0,0x3da3308c,0,0x3ee900b7,0x3e22abb6,0x3e72b651,0x3f4f7a1f,0x3f7cfe73,0x3ea09ae5,0x3ec6d529,0x3f731447,0x3f33e7bc,0x3eebcbbb,0x3f07a136,0x3e9aa086,0xbe28defc,
0,0x3e039502,0,0x3eff17b2,0x3e827dc0,0x3ec1071e,0x3f5d2d53,0x3f7ffec4,0x3efc5d27,0x3f19c200,0x3f5ebe05,0x3f0242b1,0x3f32c8c9,0x3f48d8b3,0x3c490e90,0xbef9a02d,
0,0x3e354098,0,0x3f0a48ad,0x3eb263ef,0x3f0242b1,0x3f68bf3c,0x3f7d7474,0x3f273656,0x3f46e22a,0x3f41d870,0x3e919ddd,0x3f604621,0x3f7294f8,0xbe8e9a22,0xbf40d0da,
0,0x3e667c66,0,0x3f14b039,0x3ee0924f,0x3f212ff9,0x3f721352,0x3f756d97,0x3f49d112,0x3f6816a8,0x3f1d7fd1,0x3d2fe007,0x3f7a7302,0x3f7ff4e6,0xbf0b9a6b,0xbf6e46be,
0,0x3e8b9507,0,0x3f1ebc12,0x3f064b82,0x3f3ca003,0x3f791298,0x3f6816a8,0x3f64aa59,0x3f7b61fc,0x3ee63375,0xbe4dee60,0x3f7f0e58,0x3f6f6830,0xbf43e200,0xbf7fe129,
0,0x3ea395c5,0,0x3f286605,0x3f1b02c6,0x3f53fac3,0x3f7dabcc,0x3f55b993,0x3f76ba07,0x3f7f9c18,0x3e888e93,0xbeddbe79,0x3f6db293,0x3f42de29,0xbf6b4b0c,0xbf73913f,
0,0x3ebb31a0,0,0x3f31a81d,0x3f2e3bde,0x3f66becc,0x3f7fd397,0x3f3ebc1b,0x3f7f4e6d,0x3f748422,0x3d96a905,0xbf239da9,0x3f47de65,0x3eff17b2,0xbf7e70b0,0xbf4ac77f,
0x35cccccd,0x35cccccd,0x35cccccd,0x35cccccd,0x35cccccd,0x35cccccd,0x35cccccd,0x35cccccd,0x35cccccd,0x35cccccd,0x35cccccd,0x35cccccd,0x35cccccd,0x35cccccd,0x35cccccd,0x35cccccd,
0x35ccb421,0x35cc2618,0x35bab7a7,0x35b65d28,0x35cb1a27,0x35c990f4,0x35b19232,0x35ac59b8,0x35c78b72,0x35c50adf,0x35a6b6f3,0x35a0ad5c,0x35c210c7,0x35be9eff,0x359a40ae,0x359374de,
0x35cc6a23,0x35ca3307,0x3587a9aa,0x356ff15b,0x35c6096a,0x35bff78f,0x354e3fd4,0x352a91ce,0x35b80c6c,0x35ae5b88,0x35053f42,0x34bd4866,0x35a2fcc6,0x35960c2f,0x345c7f3e,0x33713846,
0x35cbeee4,0x35c6f6c8,0x34f29b58,0x347a57c9,0x35bdb017,0x35b04e38,0x3220d93a,0xb4667457,0x359f1b54,0x358a76bb,0xb4e8fc95,0xb52cd9f0,0x3565a5a1,0x3531652e,0xb56177b4,0xb5889a01,
0x35cb4283,0x35c276a0,0xb4488ec2,0xb5007bea,0x35b2319e,0x359b138d,0xb549e41f,0xb585c511,0x357bffb5,0x3538292a,0xb5a1740f,0xb5b6eeae,0x34da7db8,0x33f10e6e,0xb5c5619f,0xb5cc3ebe,
0x35ca6529,0x35bcb9e0,0xb554ba6c,0xb591b389,0x35a3bec8,0x3580f32d,0xb5b04e38,0xb5c457ac,0x352cd9f0,0x349ae293,0xb5cc9c72,0xb5c89dab,0xb3b4dd20,0xb4f29b58,0xb5b898a3,0xb59d832a,
0x35c9570a,0x35b5c9e1,0xb5a8e03a,0xb5c33cb1,0x359294e9,0x354580a2,0xb5ccc8da,0xb5c4b238,0x34a9aa67,0xb40c9200,0xb5abab1e,0xb583db51,0xb518176e,0xb57ff144,0xb521610f,0xb434968b,
0x35c8186a,0x35adb1ef,0xb5c990f4,0xb5c9fef3,0x357df9b6,0x3502de37,0xb5b2cf52,0xb586b804,0xb2f142bd,0xb51110bd,0xb515c14d,0xb34907c8,0xb584d0d5,0xb5b19232,0x34fc30c0,0x357a0347,
0,0,0,0,0,0,0,0,0,0,0,0,0,0,0,0,
0x334907c8,0x34028d3d,0x35284807,0x353a66f9,0x34528804,0x3491007a,0x354c12f5,0x355d4116,0x34b86384,0x34df54d8,0x356de6c2,0x357df9b6,0x3502de37,0x3515c14d,0x3586b804,0x358e2017,
0x33c8ef90,0x348222f8,0x35996c52,0x35a5fb4c,0x34d0c934,0x350eb659,0x35b0f10f,0x35ba3296,0x3533a83f,0x3556df37,0x35c1a90f,0x35c74213,0x3578046f,0x358b6318,0x35caefd6,0x35cca946,
0x34169569,0x34c22b74,0x35c39ce8,0x35ca6529,0x351a6c18,0x35506ab5,0x35cccbd0,0x35cac390,0x3580f32d,0x3596e669,0x35c457ac,0x35b9abba,0x35a99568,0x35b898a3,0x35aafadc,0x3598967c,
0x34488ec2,0x35007bea,0x35cb4283,0x35c276a0,0x3549e41f,0x3585c511,0x35b2319e,0x359b138d,0x35a1740f,0x35b6eeae,0x357bffb5,0x3538292a,0x35c5619f,0x35cc3ebe,0x34da7db8,0x33f10e6e,
0x347a57c9,0x351f10ee,0x35af0373,0x358fec97,0x35760334,0x359f1b54,0x35506ab5,0x34e8fc95,0x35b9abba,0x35c91b30,0x338cb338,0xb4a4beb3,0x35cc7ce0,0x35c39ce8,0xb531652e,0xb582e487,
0x3495f23f,0x353ca2fc,0x3567b948,0x34f7673d,0x358f0707,0x35b36b4e,0x32a0d873,0xb4e429d0,0x35c85c01,0x35cc0b7a,0xb55f5d78,0xb59cb4cd,0x35be2876,0x359fe51e,0xb5bc3c09,0xb5cb8d5a,
0x34ae9479,0x355901f0,0x3491007a,0xb48718ca,0x35a0ad5c,0x35c210c7,0xb547b357,0xb59a40ae,0x35ccc3eb,0x35bf868d,0xb5be9eff,0xb5ccb421,0x359be4ed,0x354c12f5,0xb5c2da99,0xb5a23933,
0x3f803f80,0,0,0x3f803f80,0x3f803f80,0,0,0x3f803f80,0x3f803f80,0,0,0x3f803f80,0x3f803f80,0,0,0x3f803f80,
0x3f353f80,0x3f350000,0xbf350000,0x3f353f80,0xbf350000,0x3f353f80,0xbf35bf80,0xbf350000,0xbf35bf80,0xbf350000,0x3f350000,0xbf35bf80,0x3f350000,0xbf35bf80,0x3f353f80,0x3f350000,
0x3f80,0x3f800000,0xbf800000,0x3f80,0xbf80,0xbf800000,0x3f800000,0xbf80,0x3f80,0x3f800000,0xbf800000,0x3f80,0xbf80,0xbf800000,0x3f800000,0xbf80,
0xbf353f80,0x3f350000,0xbf350000,0xbf353f80,0x3f350000,0x3f35bf80,0xbf353f80,0x3f350000,0x3f35bf80,0xbf350000,0x3f350000,0x3f35bf80,0xbf350000,0xbf353f80,0x3f35bf80,0xbf350000,
0xbf803f80,0,0,0xbf803f80,0xbf803f80,0,0,0xbf803f80,0xbf803f80,0,0,0xbf803f80,0xbf803f80,0,0,0xbf803f80,
0xbf353f80,0xbf350000,0x3f350000,0xbf353f80,0x3f350000,0xbf353f80,0x3f35bf80,0x3f350000,0x3f35bf80,0x3f350000,0xbf350000,0x3f35bf80,0xbf350000,0x3f35bf80,0xbf353f80,0xbf350000,
0x3f80,0xbf800000,0x3f800000,0x3f80,0xbf80,0x3f800000,0xbf800000,0xbf80,0x3f80,0xbf800000,0x3f800000,0x3f80,0xbf80,0x3f800000,0xbf800000,0xbf80,
0x3f353f80,0xbf350000,0x3f350000,0x3f353f80,0xbf350000,0xbf35bf80,0x3f353f80,0xbf350000,0xbf35bf80,0x3f350000,0xbf350000,0xbf35bf80,0x3f350000,0x3f353f80,0xbf35bf80,0x3f350000,
0x3f80,0x3f80,0x3f623ef1,0x3f623ef1,0x3e893f77,0xbe89bf77,0x3f7a3e60,0xbf7abe60,0x3f043f5c,0x3f043f5c,0x3f80bd49,0x3f80bd49,0x3f393f31,0xbf39bf31,0x3f73bea1,0xbf733ea1,
0x3f80,0x3f80,0x3ef1bf62,0x3ef1bf62,0x3f1d3f4a,0xbf1dbf4a,0xbe2fbf7c,0x3e2f3f7c,0x3f783e79,0x3f783e79,0xbf3ebf2c,0xbf3ebf2c,0x3f6abecf,0xbf6a3ecf,0xbf7fbd97,0x3f7f3d97,
0x3f80,0x3f80,0xbf62bef1,0xbf62bef1,0x3f5f3efc,0xbf5fbefc,0xbf583f09,0x3f58bf09,0x3f5cbf04,0x3f5cbf04,0x3d493f80,0x3d493f80,0xbcc9bf80,0x3cc93f80,0x3f653ee6,0xbf65bee6,
0x3f80,0x3f80,0xbef13f62,0xbef13f62,0x3f7e3dfb,0xbf7ebdfb,0x3f513f13,0xbf51bf13,0x3e79bf78,0x3e79bf78,0x3f2cbf3e,0x3f2cbf3e,0xbf6fbeb8,0x3f6f3eb8,0xbf27bf42,0x3f273f42,
0x3f80,0x3f80,0x3f623ef1,0x3f623ef1,0x3f77be89,0xbf773e89,0x3e60bf7a,0xbe603f7a,0xbf04bf5c,0xbf04bf5c,0xbf803d49,0xbf803d49,0xbf313f39,0x3f31bf39,0x3ea13f73,0xbea1bf73,
0x3f80,0x3f80,0x3ef1bf62,0x3ef1bf62,0x3f4abf1d,0xbf4a3f1d,0xbf7c3e2f,0x3f7cbe2f,0xbf78be79,0xbf78be79,0x3f3e3f2c,0x3f3e3f2c,0x3ecf3f6a,0xbecfbf6a,0x3d97bf7f,0xbd973f7f,
0x3f80,0x3f80,0xbf62bef1,0xbf62bef1,0x3efcbf5f,0xbefc3f5f,0x3f093f58,0xbf09bf58,0xbf5c3f04,0xbf5c3f04,0xbd49bf80,0xbd49bf80,0x3f80bcc9,0xbf803cc9,0xbee63f65,0x3ee6bf65,
0x3f80,0x3f80,0xbef13f62,0xbef13f62,0x3dfbbf7e,0xbdfb3f7e,0x3f13bf51,0xbf133f51,0xbe793f78,0xbe793f78,0xbf2c3f3e,0xbf2c3f3e,0x3eb8bf6f,0xbeb83f6f,0x3f42bf27,0xbf423f27,
0x3f55bf0e,0x3f55bf0e,0xbdc9bf7f,0xbdc9bf7f,0x3f27bf42,0xbf273f42,0xbeb8bf6f,0x3eb83f6f,0x3edbbf67,0x3edbbf67,0xbf18bf4e,0xbf18bf4e,0x3e2fbf7c,0xbe2f3f7c,0xbf4abf1d,0x3f4a3f1d,
0xbf553f0e,0xbf553f0e,0x3f7fbdc9,0x3f7fbdc9,0xbea13f73,0x3ea1bf73,0x3f39bf31,0xbf393f31,0x3eac3f71,0x3eac3f71,0x3e16bf7d,0x3e16bf7d,0x3f583f09,0xbf58bf09,0xbefcbf5f,0x3efc3f5f,
0x3f55bf0e,0x3f55bf0e,0x3dc93f7f,0x3dc93f7f,0xbd97bf7f,0x3d973f7f,0x3f6a3ecf,0xbf6abecf,0xbf67bedb,0xbf67bedb,0x3f4ebf18,0x3f4ebf18,0xbf513f13,0x3f51bf13,0xbdfbbf7e,0x3dfb3f7e,
0xbf553f0e,0xbf553f0e,0xbf7f3dc9,0xbf7f3dc9,0x3ee63f65,0xbee6bf65,0xbcc93f80,0x3cc9bf80,0x3f71beac,0x3f71beac,0x3f7d3e16,0x3f7d3e16,0xbe60bf7a,0x3e603f7a,0x3e89bf77,0xbe893f77,
0x3f55bf0e,0x3f55bf0e,0xbdc9bf7f,0xbdc9bf7f,0xbf42bf27,0x3f423f27,0xbf6f3eb8,0x3f6fbeb8,0xbedb3f67,0xbedb3f67,0x3f183f4e,0x3f183f4e,0x3f7c3e2f,0xbf7cbe2f,0x3f1dbf4a,0xbf1d3f4a,
0xbf553f0e,0xbf553f0e,0x3f7fbdc9,0x3f7fbdc9,0x3f733ea1,0xbf73bea1,0xbf31bf39,0x3f313f39,0xbeacbf71,0xbeacbf71,0xbe163f7d,0xbe163f7d,0xbf093f58,0x3f09bf58,0x3f5fbefc,0xbf5f3efc,
0x3f55bf0e,0x3f55bf0e,0x3dc93f7f,0x3dc93f7f,0xbf7f3d97,0x3f7fbd97,0x3ecfbf6a,0xbecf3f6a,0x3f673edb,0x3f673edb,0xbf4e3f18,0xbf4e3f18,0xbf13bf51,0x3f133f51,0x3f7ebdfb,0xbf7e3dfb,
0xbf553f0e,0xbf553f0e,0xbf7f3dc9,0xbf7f3dc9,0x3f65bee6,0xbf653ee6,0x3f803cc9,0xbf80bcc9,0xbf713eac,0xbf713eac,0xbf7dbe16,0xbf7dbe16,0x3f7abe60,0xbf7a3e60,0x3f773e89,0xbf77be89,
0x3f800000,0x3f800000,0x3ef1bf62,0x3ef1bf62,0x3f77be89,0xbf773e89,0x3e60bf7a,0xbe603f7a,0x3f5cbf04,0x3f5cbf04,0xbd49bf80,0xbd49bf80,0x3f31bf39,0xbf313f39,0xbea1bf73,0x3ea13f73,
0x3f800000,0x3f800000,0xbf62bef1,0xbf62bef1,0x3f4abf1d,0xbf4a3f1d,0xbf7c3e2f,0x3f7cbe2f,0x3e79bf78,0x3e79bf78,0xbf2c3f3e,0xbf2c3f3e,0xbecfbf6a,0x3ecf3f6a,0xbd973f7f,0x3d97bf7f,
0x3f800000,0x3f800000,0xbef13f62,0xbef13f62,0x3efcbf5f,0xbefc3f5f,0x3f093f58,0xbf09bf58,0xbf04bf5c,0xbf04bf5c,0x3f80bd49,0x3f80bd49,0xbf803cc9,0x3f80bcc9,0x3ee6bf65,0xbee63f65,
0x3f800000,0x3f800000,0x3f623ef1,0x3f623ef1,0x3dfbbf7e,0xbdfb3f7e,0x3f13bf51,0xbf133f51,0xbf78be79,0xbf78be79,0xbf3ebf2c,0xbf3ebf2c,0xbeb83f6f,0x3eb8bf6f,0xbf423f27,0x3f42bf27,
0x3f800000,0x3f800000,0x3ef1bf62,0x3ef1bf62,0xbe89bf77,0x3e893f77,0xbf7abe60,0x3f7a3e60,0xbf5c3f04,0xbf5c3f04,0x3d493f80,0x3d493f80,0x3f393f31,0xbf39bf31,0x3f73bea1,0xbf733ea1,
0x3f800000,0x3f800000,0xbf62bef1,0xbf62bef1,0xbf1dbf4a,0x3f1d3f4a,0x3e2f3f7c,0xbe2fbf7c,0xbe793f78,0xbe793f78,0x3f2cbf3e,0x3f2cbf3e,0x3f6abecf,0xbf6a3ecf,0xbf7fbd97,0x3f7f3d97,
0x3f800000,0x3f800000,0xbef13f62,0xbef13f62,0xbf5fbefc,0x3f5f3efc,0x3f58bf09,0xbf583f09,0x3f043f5c,0x3f043f5c,0xbf803d49,0xbf803d49,0xbcc9bf80,0x3cc93f80,0x3f653ee6,0xbf65bee6,
0x3f800000,0x3f800000,0x3f623ef1,0x3f623ef1,0xbf7ebdfb,0x3f7e3dfb,0xbf51bf13,0x3f513f13,0x3f783e79,0x3f783e79,0x3f3e3f2c,0x3f3e3f2c,0xbf6fbeb8,0x3f6f3eb8,0xbf27bf42,0x3f273f42,
0xbf0ebf55,0xbf0ebf55,0xbf7f3dc9,0xbf7f3dc9,0xbf42bf27,0x3f423f27,0xbf6f3eb8,0x3f6fbeb8,0xbf67bedb,0xbf67bedb,0xbf4e3f18,0xbf4e3f18,0xbf7cbe2f,0x3f7c3e2f,0xbf1d3f4a,0x3f1dbf4a,
0x3f0e3f55,0x3f0e3f55,0xbdc9bf7f,0xbdc9bf7f,0x3f733ea1,0xbf73bea1,0xbf31bf39,0x3f313f39,0x3f71beac,0x3f71beac,0xbf7dbe16,0xbf7dbe16,0x3f09bf58,0xbf093f58,0xbf5f3efc,0x3f5fbefc,
0xbf0ebf55,0xbf0ebf55,0x3f7fbdc9,0x3f7fbdc9,0xbf7f3d97,0x3f7fbd97,0x3ecfbf6a,0xbecf3f6a,0xbedb3f67,0xbedb3f67,0xbf18bf4e,0xbf18bf4e,0x3f133f51,0xbf13bf51,0xbf7e3dfb,0x3f7ebdfb,
0x3f0e3f55,0x3f0e3f55,0x3dc93f7f,0x3dc93f7f,0x3f65bee6,0xbf653ee6,0x3f803cc9,0xbf80bcc9,0xbeacbf71,0xbeacbf71,0x3e16bf7d,0x3e16bf7d,0xbf7a3e60,0x3f7abe60,0xbf77be89,0x3f773e89,
0xbf0ebf55,0xbf0ebf55,0xbf7f3dc9,0xbf7f3dc9,0xbf273f42,0x3f27bf42,0x3eb83f6f,0xbeb8bf6f,0x3f673edb,0x3f673edb,0x3f4ebf18,0x3f4ebf18,0x3e2fbf7c,0xbe2f3f7c,0xbf4abf1d,0x3f4a3f1d,
0x3f0e3f55,0x3f0e3f55,0xbdc9bf7f,0xbdc9bf7f,0x3ea1bf73,0xbea13f73,0xbf393f31,0x3f39bf31,0xbf713eac,0xbf713eac,0x3f7d3e16,0x3f7d3e16,0x3f583f09,0xbf58bf09,0xbefcbf5f,0x3efc3f5f,
0xbf0ebf55,0xbf0ebf55,0x3f7fbdc9,0x3f7fbdc9,0x3d973f7f,0xbd97bf7f,0xbf6abecf,0x3f6a3ecf,0x3edbbf67,0x3edbbf67,0x3f183f4e,0x3f183f4e,0xbf513f13,0x3f51bf13,0xbdfbbf7e,0x3dfb3f7e,
0x3f0e3f55,0x3f0e3f55,0x3dc93f7f,0x3dc93f7f,0xbee6bf65,0x3ee63f65,0x3cc9bf80,0xbcc93f80,0x3eac3f71,0x3eac3f71,0xbe163f7d,0xbe163f7d,0xbe60bf7a,0x3e603f7a,0x3e89bf77,0xbe893f77,
0x3f803f80,0x3f0ebf0e,0x3f803f80,0x3f0ebf0e,0x3f803f80,0x3f0ebf0e,0x3f803f80,0x3f0ebf0e,0x3f803f80,0x3f0ebf0e,0x3f803f80,0x3f0ebf0e,0x3f803f80,0x3f0ebf0e,0x3f803f80,0x3f0ebf0e,
0x3f4a3f77,0x3f73bf42,0xbf4abf77,0xbf733f42,0x3dfb3efc,0x3f65bf7f,0xbdfbbefc,0xbf653f7f,0xbf1dbe89,0x3ea1bf27,0x3f1d3e89,0xbea13f27,0xbf7ebf5f,0xbee63d97,0x3f7e3f5f,0x3ee6bd97,
0x3e793f5c,0x3f71bf67,0x3e793f5c,0x3f71bf67,0xbf78bf04,0xbeacbedb,0xbf78bf04,0xbeacbedb,0xbe79bf5c,0xbf713f67,0xbe79bf5c,0xbf713f67,0x3f783f04,0x3eac3edb,0x3f783f04,0x3eac3edb,
0xbecf3f31,0x3f09bf7c,0x3ecfbf31,0xbf093f7c,0xbeb8bf80,0xbf7a3f13,0x3eb83f80,0x3f7abf13,0x3f6a3f39,0x3f583e2f,0xbf6abf39,0xbf58be2f,0xbf6fbcc9,0xbe60bf51,0x3f6f3cc9,0x3e603f51,
0xbf623ef1,0xbdc9bf7f,0xbf623ef1,0xbdc9bf7f,0x3f62bef1,0x3dc93f7f,0x3f62bef1,0x3dc93f7f,0xbf623ef1,0xbdc9bf7f,0xbf623ef1,0xbdc9bf7f,0x3f62bef1,0x3dc93f7f,0x3f62bef1,0x3dc93f7f,
0xbf7c3e60,0xbf31bf6f,0x3f7cbe60,0x3f313f6f,0x3f133f09,0x3f803ecf,0xbf13bf09,0xbf80becf,0x3e2fbf7a,0xbf393eb8,0xbe2f3f7a,0x3f39beb8,0xbf513f58,0x3cc9bf6a,0x3f51bf58,0xbcc93f6a,
0xbf2cbd49,0xbf7dbf4e,0xbf2cbd49,0xbf7dbf4e,0xbf3e3f80,0x3e16bf18,0xbf3e3f80,0x3e16bf18,0x3f2c3d49,0x3f7d3f4e,0x3f2c3d49,0x3f7d3f4e,0x3f3ebf80,0xbe163f18,0x3f3ebf80,0xbe163f18,
0xbd97bea1,0xbf5fbf1d,0x3d973ea1,0x3f5f3f1d,0xbf423ee6,0xbf77bf7e,0x3f42bee6,0x3f773f7e,0xbf7f3f73,0xbefcbf4a,0x3f7fbf73,0x3efc3f4a,0xbf273f65,0x3e89bdfb,0x3f27bf65,0xbe893dfb,
0,0xbf553f55,0,0xbf553f55,0,0xbf553f55,0,0xbf553f55,0,0xbf553f55,0,0xbf553f55,0,0xbf553f55,0,0xbf553f55,
0x3f1d3e89,0xbea13f27,0xbf1dbe89,0x3ea1bf27,0x3f7e3f5f,0x3ee6bd97,0xbf7ebf5f,0xbee63d97,0x3f4a3f77,0x3f73bf42,0xbf4abf77,0xbf733f42,0x3dfb3efc,0x3f65bf7f,0xbdfbbefc,0xbf653f7f,
0x3f783f04,0x3eac3edb,0x3f783f04,0x3eac3edb,0x3e793f5c,0x3f71bf67,0x3e793f5c,0x3f71bf67,0xbf78bf04,0xbeacbedb,0xbf78bf04,0xbeacbedb,0xbe79bf5c,0xbf713f67,0xbe79bf5c,0xbf713f67,
0x3f6a3f39,0x3f583e2f,0xbf6abf39,0xbf58be2f,0xbf6fbcc9,0xbe60bf51,0x3f6f3cc9,0x3e603f51,0x3ecfbf31,0xbf093f7c,0xbecf3f31,0x3f09bf7c,0x3eb83f80,0x3f7abf13,0xbeb8bf80,0xbf7a3f13,
0x3ef13f62,0x3f7fbdc9,0x3ef13f62,0x3f7fbdc9,0xbef1bf62,0xbf7f3dc9,0xbef1bf62,0xbf7f3dc9,0x3ef13f62,0x3f7fbdc9,0x3ef13f62,0x3f7fbdc9,0xbef1bf62,0xbf7f3dc9,0xbef1bf62,0xbf7f3dc9,
0xbe2f3f7a,0x3f39beb8,0x3e2fbf7a,0xbf393eb8,0x3f51bf58,0xbcc93f6a,0xbf513f58,0x3cc9bf6a,0xbf7c3e60,0xbf31bf6f,0x3f7cbe60,0x3f313f6f,0x3f133f09,0x3f803ecf,0xbf13bf09,0xbf80becf,
0xbf3e3f80,0x3e16bf18,0xbf3e3f80,0x3e16bf18,0x3f2c3d49,0x3f7d3f4e,0x3f2c3d49,0x3f7d3f4e,0x3f3ebf80,0xbe163f18,0x3f3ebf80,0xbe163f18,0xbf2cbd49,0xbf7dbf4e,0xbf2cbd49,0xbf7dbf4e,
0xbf7f3f73,0xbefcbf4a,0x3f7fbf73,0x3efc3f4a,0xbf273f65,0x3e89bdfb,0x3f27bf65,0xbe893dfb,0x3d973ea1,0x3f5f3f1d,0xbd97bea1,0xbf5fbf1d,0x3f42bee6,0x3f773f7e,0xbf423ee6,0xbf77bf7e,
0,0x3f55bf55,0,0x3f55bf55,0,0x3f55bf55,0,0x3f55bf55,0,0x3f55bf55,0,0x3f55bf55,0,0x3f55bf55,0,0x3f55bf55,
0xbf1dbe89,0x3ea1bf27,0x3f1d3e89,0xbea13f27,0xbf7ebf5f,0xbee63d97,0x3f7e3f5f,0x3ee6bd97,0xbf4abf77,0xbf733f42,0x3f4a3f77,0x3f73bf42,0xbdfbbefc,0xbf653f7f,0x3dfb3efc,0x3f65bf7f,
0xbf78bf04,0xbeacbedb,0xbf78bf04,0xbeacbedb,0xbe79bf5c,0xbf713f67,0xbe79bf5c,0xbf713f67,0x3f783f04,0x3eac3edb,0x3f783f04,0x3eac3edb,0x3e793f5c,0x3f71bf67,0x3e793f5c,0x3f71bf67,
0xbf6abf39,0xbf58be2f,0x3f6a3f39,0x3f583e2f,0x3f6f3cc9,0x3e603f51,0xbf6fbcc9,0xbe60bf51,0xbecf3f31,0x3f09bf7c,0x3ecfbf31,0xbf093f7c,0xbeb8bf80,0xbf7a3f13,0x3eb83f80,0x3f7abf13,
0xbef1bf62,0xbf7f3dc9,0xbef1bf62,0xbf7f3dc9,0x3ef13f62,0x3f7fbdc9,0x3ef13f62,0x3f7fbdc9,0xbef1bf62,0xbf7f3dc9,0xbef1bf62,0xbf7f3dc9,0x3ef13f62,0x3f7fbdc9,0x3ef13f62,0x3f7fbdc9,
0x3e2fbf7a,0xbf393eb8,0xbe2f3f7a,0x3f39beb8,0xbf513f58,0x3cc9bf6a,0x3f51bf58,0xbcc93f6a,0x3f7cbe60,0x3f313f6f,0xbf7c3e60,0xbf31bf6f,0xbf13bf09,0xbf80becf,0x3f133f09,0x3f803ecf,
0x3f3ebf80,0xbe163f18,0x3f3ebf80,0xbe163f18,0xbf2cbd49,0xbf7dbf4e,0xbf2cbd49,0xbf7dbf4e,0xbf3e3f80,0x3e16bf18,0xbf3e3f80,0x3e16bf18,0x3f2c3d49,0x3f7d3f4e,0x3f2c3d49,0x3f7d3f4e,
0x3f7fbf73,0x3efc3f4a,0xbf7f3f73,0xbefcbf4a,0x3f27bf65,0xbe893dfb,0xbf273f65,0x3e89bdfb,0xbd97bea1,0xbf5fbf1d,0x3d973ea1,0x3f5f3f1d,0xbf423ee6,0xbf77bf7e,0x3f42bee6,0x3f773f7e,
0x3f800000,0x3f7fdaaf,0x3f800000,0x3f6912ae,0x3f7f6ac7,0x3f7eb069,0x3f286605,0x3e931f35,0x3f7dabcc,0x3f7c5d3a,0xbe09cf86,0xbf084b92,0x3f7ac516,0x3f78e3d6,0xbf55b993,0xbf7cdf6c,
0x3f800000,0x3f7f1f49,0x3f800000,0x3f6398ac,0x3f7c7eb0,0x3f7822d1,0x3f14b039,0x3e1324ca,0x3f721352,0x3f6a5ad9,0xbea68f12,0xbf38dd65,0x3f6106f2,0x3f5627fe,0xbf756d97,0xbf7b87b2,
0x3f800000,0x3f7dc68c,0x3f800000,0x3f5d924d,0x3f772417,0x3f6c3624,0x3eff17b2,0xbb490fc6,0x3f5d2d53,0x3f4a4c87,0xbf00e7e4,0xbf5e5aa6,0x3f33e7bc,0x3f1a6293,0xbf7ffec4,0xbf5cc7d1,
0x3f800000,0x3f7bd14d,0x3f800000,0x3f570348,0x3f6f6830,0x3f5b2c79,0x3ed25a09,0xbe195be0,0x3f3fc767,0x3f1e1e22,0xbf299415,0xbf76841b,0x3eee9479,0x3e9920fe,0xbf748422,0xbf24381a,
0x3f800000,0x3f7940c0,0x3f800000,0x3f4fefa8,0x3f655e0b,0x3f456439,0x3ea395c5,0xbe9620d2,0x3f1b02c6,0x3ed0eb2a,0xbf4bbbf8,0xbf7fe705,0x3e419b37,0xbd2351cb,0xbf53fac3,0xbeb0eacb,
0x3f800000,0x3f76167a,0x3f800000,0x3f485bca,0x3f591e6a,0x3f2b561b,0x3e667c66,0xbedc53c1,0x3ee0924f,0x3e3228d4,0xbf660f88,0xbf79f35e,0xbdd53db9,0xbebf926f,0xbf212ff9,0xbc16cb58,
0x3f800000,0x3f725470,0x3f800000,0x3f404c5c,0x3f4ac77f,0x3f0d9281,0x3e039502,0xbf0ee0db,0x3e827dc0,0xbd9064b4,0xbf778bc5,0xbf650479,0xbec6d529,0xbf2a2a80,0xbec1071e,0x3ea80b1f,
0x3f800000,0x3f6dfcf2,0x3f800000,0x3f37c655,0x3f3a7ca4,0x3ed97cb9,0x3cfb49ba,0xbf2c800f,0x3d7b2b74,0xbe9f1cdf,0xbf7f84ab,0xbf425b89,0xbf239da9,0xbf60a6cf,0xbdbc3ac3,0x3f209393,
0,0x3d0a342f,0,0x3ed3c867,0x3d8a200a,0x3dcefdb7,0x3f40d0da,0x3f75341d,0x3e09cf86,0x3e2bf804,0x3f7dabcc,0x3f58b3a1,0x3e4dee60,0x3e6fa8b2,0x3f0cead0,0x3e1f917b,
0,0x3da973ba,0,0x3eea6681,0x3e28defc,0x3e7bdba4,0x3f5064af,0x3f7d57de,0x3ea68f12,0x3ece0bea,0x3f721352,0x3f311722,0x3ef41f07,0x3f0c42c9,0x3e919ddd,0xbe3e853e,
0,0x3e06b26e,0,0x3f003a06,0x3e8586ce,0x3ec5625c,0x3f5df6be,0x3f7fffb1,0x3f00e7e4,0x3f1ce11f,0x3f5d2d53,0x3efdbabb,0x3f36206c,0x3f4c3578,0xbbc90f88,0xbf019573,
0,0x3e3857ec,0,0x3f0af1b7,0x3eb554ec,0x3f044889,0x3f696591,0x3f7d1cdd,0x3f299415,0x3f495521,0x3f3fc767,0x3e8a11f7,0x3f628210,0x3f74484b,0xbe97a117,0xbf446337,
0,0x3e698bba,0,0x3f1553b7,0x3ee363fa,0x3f2302d3,0x3f7294f8,0x3f74bf62,0x3f4bbbf8,0x3f69b7e4,0x3f1b02c6,0x3ce22a7a,0x3f7b61fc,0x3f7fcbe2,0xbf0f8784,0xbf703b37,
0,0x3e8d17c0,0,0x3f1f599f,0x3f07a136,0x3f3e35c5,0x3f796e4e,0x3f671599,0x3f660f88,0x3f7c187a,0x3ee0924f,0xbe5d4b1a,0x3f7e9bc9,0x3f6d67a1,0xbf46e22a,0xbf7ffd39,
0,0x3ea5129f,0,0x3f28fd41,0x3f1c420c,0x3f554aa4,0x3f7de0b1,0x3f546b3b,0x3f778bc5,0x3f7f5ce9,0x3e827dc0,0xbee4cbfe,0x3f6be858,0x3f3f41fc,0xbf6d1c1d,0xbf71d19f,
0,0x3ebca7af,0,0x3f3238aa,0x3f2f61a5,0x3f67c187,0x3f7fe129,0x3f3d27b8,0x3f7f84ab,0x3f73530e,0x3d7b2b74,0xbf269de3,0x3f44e3f5,0x3ef58035,0xbf7eea9d,0xbf476085,
0x35cccccd,0x35cccccd,0x35cccccd,0x35cccccd,0x35cccccd,0x35cccccd,0x35cccccd,0x35cccccd,0x35cccccd,0x35cccccd,0x35cccccd,0x35cccccd,0x35cccccd,0x35cccccd,0x35cccccd,0x35cccccd,
0x35ccaef3,0x35cc1907,0x35ba7558,0x35b613bd,0x35cb053d,0x35c9743e,0x35b141d7,0x35ac02a0,0x35c76700,0x35c4dec8,0x35a65953,0x35a0496e,0x35c1dd26,0x35be63f5,0x3599d6b0,0x35930511,
0x35cc556c,0x35c9fef3,0x3586b804,0x356de6c2,0x35c5b679,0x35bf868d,0x354c12f5,0x35284807,0x35b77e6f,0x35adb1ef,0x3502de37,0x34b86384,0x35a23933,0x35953084,0x34528804,0x334907c8,
0x35cbc054,0x35c68241,0x34eb6521,0x346b6e11,0x35bcf81d,0x35af56c7,0xb1a0d96b,0xb4755fcc,0x359de9c7,0x358911af,0xb4f03484,0xb5304301,0x35628401,0x352dfd61,0xb5649af8,0xb58a000c,
0x35caefd6,0x35c1a90f,0xb45c7f3e,0xb5053f42,0x35b0f10f,0x35996c52,0xb54e3fd4,0xb587a9aa,0x3578046f,0x3533a83f,0xb5a2fcc6,0xb5b80c6c,0x34d0c934,0x33c8ef90,0xb5c6096a,0xb5cc6a23,
0x35c9e42e,0x35bb7be1,0xb55a1284,0xb593e451,0x35a1d6d2,0x357cfd04,0xb5b1e21f,0xb5c5367c,0x35272288,0x348e8710,0xb5ccb8d1,0xb5c7f5e5,0xb3e70786,0xb4fe9498,0xb5b736c7,0xb59b7c6d,
0x35c89dab,0x35b4058e,0xb5aafadc,0xb5c457ac,0x358fec97,0x353edd2d,0xb5cccbd0,0xb5c39ce8,0x349ae293,0xb42a97c7,0xb5a99568,0xb580f32d,0xb51f10ee,0xb582e487,0xb51a6c18,0xb4169569,
0x35c71cab,0x35ab5332,0xb5ca4c56,0xb5c9395b,0x3577041e,0x34f50196,0xb5b09fda,0xb5836014,0xb382a7d6,0xb51941f2,0xb50d88a2,0xb271455a,0xb5882200,0xb5b3b8a6,0x35066f4c,0x3580760f,
0,0,0,0,0,0,0,0,0,0,0,0,0,0,0,0,
0x335d204b,0x34078fc8,0x35296d1f,0x353b8534,0x345783e3,0x3493798a,0x354d29a4,0x355e4f8b,0x34bad62f,0x34e1bf99,0x356eec58,0x357ef5cc,0x35040ee5,0x3516ec8c,0x35873101,0x358e93bb,
0x33dd000f,0x348718ca,0x359a40ae,0x35a6b6f3,0x34d5a47e,0x351110bd,0x35b19232,0x35bab7a7,0x3535e995,0x355901f0,0x35c210c7,0x35c78b72,0x357a0347,0x358c4e1d,0x35cb1a27,0x35ccb421,
0x342597c6,0x34c97c83,0x35c429b0,0x35caacb2,0x351de84a,0x3553a742,0x35cccc8e,0x35ca7d7e,0x358268a9,0x35982b04,0x35c3cc4e,0x35b8de14,0x35aaa21d,0x35b9679f,0x35a9ef63,0x359752fa,
0x345c7f3e,0x35053f42,0x35caefd6,0x35c1a90f,0x354e3fd4,0x3587a9aa,0x35b0f10f,0x35996c52,0x35a2fcc6,0x35b80c6c,0x3578046f,0x3533a83f,0x35c6096a,0x35cc6a23,0x34d0c934,0x33c8ef90,
0x34899337,0x3524d655,0x35ad5c81,0x358dac1c,0x357b01cb,0x35a110e7,0x354afbc9,0x34dce98c,0x35baf983,0x35c9ad2f,0x3334eec8,0xb4b108e1,0x35cc4a54,0x35c2a8d8,0xb5370998,0xb5854b1c,
0x34a4beb3,0x35434c06,0x356177b4,0x34e8fc95,0x3591b389,0x35b534da,0xb220d93a,0xb4f29b58,0x35c91b30,0x35cbafd4,0xb565a5a1,0xb59f1b54,0x35bcb9e0,0x359d832a,0xb5bdb017,0xb5cbeee4,
0x34bfba28,0x35606adb,0x347f4f2b,0xb4986a98,0x35a35df9,0x35c36d09,0xb54f5584,0xb59d1c2c,0x35cca31b,0x35bdec81,0xb5c02f5f,0xb5ccca94,0x35990197,0x35446691,0xb5c17480,0xb59f806a,
0x3f803f80,0,0,0x3f803f80,0x3f803f80,0,0,0x3f803f80,0x3f803f80,0,0,0x3f803f80,0x3f803f80,0,0,0x3f803f80,
0x3f353f80,0x3f350000,0xbf350000,0x3f353f80,0xbf350000,0x3f353f80,0xbf35bf80,0xbf350000,0xbf35bf80,0xbf350000,0x3f350000,0xbf35bf80,0x3f350000,0xbf35bf80,0x3f353f80,0x3f350000,
0x3f80,0x3f800000,0xbf800000,0x3f80,0xbf80,0xbf800000,0x3f800000,0xbf80,0x3f80,0x3f800000,0xbf800000,0x3f80,0xbf80,0xbf800000,0x3f800000,0xbf80,
0xbf353f80,0x3f350000,0xbf350000,0xbf353f80,0x3f350000,0x3f35bf80,0xbf353f80,0x3f350000,0x3f35bf80,0xbf350000,0x3f350000,0x3f35bf80,0xbf350000,0xbf353f80,0x3f35bf80,0xbf350000,
0xbf803f80,0,0,0xbf803f80,0xbf803f80,0,0,0xbf803f80,0xbf803f80,0,0,0xbf803f80,0xbf803f80,0,0,0xbf803f80,
0xbf353f80,0xbf350000,0x3f350000,0xbf353f80,0x3f350000,0xbf353f80,0x3f35bf80,0x3f350000,0x3f35bf80,0x3f350000,0xbf350000,0x3f35bf80,0xbf350000,0x3f35bf80,0xbf353f80,0xbf350000,
0x3f80,0xbf800000,0x3f800000,0x3f80,0xbf80,0x3f800000,0xbf800000,0xbf80,0x3f80,0xbf800000,0x3f800000,0x3f80,0xbf80,0x3f800000,0xbf800000,0xbf80,
0x3f353f80,0xbf350000,0x3f350000,0x3f353f80,0xbf350000,0xbf35bf80,0x3f353f80,0xbf350000,0xbf35bf80,0x3f350000,0xbf350000,0xbf35bf80,0x3f350000,0x3f353f80,0xbf35bf80,0x3f350000,
0x3f80,0x3f80,0x3f6d3ec4,0x3f6d3ec4,0x3e953f75,0xbe95bf75,0x3f7f3dc9,0xbf7fbdc9,0x3f0e3f55,0x3f0e3f55,0x3f7bbe48,0x3f7bbe48,0x3f463f22,0xbf46bf22,0x3f62bef1,0xbf623ef1,
0x3f80,0x3f80,0x3ec4bf6d,0x3ec4bf6d,0x3f223f46,0xbf22bf46,0xbe95bf75,0x3e953f75,0x3f7b3e48,0x3f7b3e48,0xbf55bf0e,0xbf55bf0e,0x3f62bef1,0xbf623ef1,0xbf7f3dc9,0x3f7fbdc9,
0x3f80,0x3f80,0xbf6dbec4,0xbf6dbec4,0x3f623ef1,0xbf62bef1,0xbf463f22,0x3f46bf22,0x3f55bf0e,0x3f55bf0e,0x3e483f7b,0x3e483f7b,0xbdc9bf7f,0x3dc93f7f,0x3f753e95,0xbf75be95,
0x3f80,0x3f80,0xbec43f6d,0xbec43f6d,0x3f7f3dc9,0xbf7fbdc9,0x3f623ef1,0xbf62bef1,0x3e48bf7b,0x3e48bf7b,0x3f0ebf55,0x3f0ebf55,0xbf75be95,0x3f753e95,0xbf46bf22,0x3f463f22,
0x3f80,0x3f80,0x3f6d3ec4,0x3f6d3ec4,0x3f75be95,0xbf753e95,0x3dc9bf7f,0xbdc93f7f,0xbf0ebf55,0xbf0ebf55,0xbf7b3e48,0xbf7b3e48,0xbf223f46,0x3f22bf46,0x3ef13f62,0xbef1bf62,
0x3f80,0x3f80,0x3ec4bf6d,0x3ec4bf6d,0x3f46bf22,0xbf463f22,0xbf753e95,0x3f75be95,0xbf7bbe48,0xbf7bbe48,0x3f553f0e,0x3f553f0e,0x3ef13f62,0xbef1bf62,0xbdc9bf7f,0x3dc93f7f,
0x3f80,0x3f80,0xbf6dbec4,0xbf6dbec4,0x3ef1bf62,0xbef13f62,0x3f223f46,0xbf22bf46,0xbf553f0e,0xbf553f0e,0xbe48bf7b,0xbe48bf7b,0x3f7fbdc9,0xbf7f3dc9,0xbe953f75,0x3e95bf75,
0x3f80,0x3f80,0xbec43f6d,0xbec43f6d,0x3dc9bf7f,0xbdc93f7f,0x3ef1bf62,0xbef13f62,0xbe483f7b,0xbe483f7b,0xbf0e3f55,0xbf0e3f55,0x3e95bf75,0xbe953f75,0x3f22bf46,0xbf223f46,
0x3f35bf35,0x3f35bf35,0xbec4bf6d,0xbec4bf6d,0x3ef1bf62,0xbef13f62,0xbf22bf46,0x3f223f46,0x3e48bf7b,0x3e48bf7b,0xbf55bf0e,0xbf55bf0e,0xbdc9bf7f,0x3dc93f7f,0xbf75be95,0x3f753e95,
0xbf353f35,0xbf353f35,0x3f6dbec4,0x3f6dbec4,0xbdc93f7f,0x3dc9bf7f,0x3ef1bf62,0xbef13f62,0x3f0e3f55,0x3f0e3f55,0xbe48bf7b,0xbe48bf7b,0x3f753e95,0xbf75be95,0xbf46bf22,0x3f463f22,
0x3f35bf35,0x3f35bf35,0x3ec43f6d,0x3ec43f6d,0xbe95bf75,0x3e953f75,0x3f7f3dc9,0xbf7fbdc9,0xbf7bbe48,0xbf7bbe48,0x3f0ebf55,0x3f0ebf55,0xbf223f46,0x3f22bf46,0xbef1bf62,0x3ef13f62,
0xbf353f35,0xbf353f35,0xbf6d3ec4,0xbf6d3ec4,0x3f223f46,0xbf22bf46,0x3e953f75,0xbe95bf75,0x3f55bf0e,0x3f55bf0e,0x3f7bbe48,0x3f7bbe48,0xbef1bf62,0x3ef13f62,0xbdc9bf7f,0x3dc93f7f,
0x3f35bf35,0x3f35bf35,0xbec4bf6d,0xbec4bf6d,0xbf62bef1,0x3f623ef1,0xbf463f22,0x3f46bf22,0xbe483f7b,0xbe483f7b,0x3f553f0e,0x3f553f0e,0x3f7fbdc9,0xbf7f3dc9,0x3e95bf75,0xbe953f75,
0xbf353f35,0xbf353f35,0x3f6dbec4,0x3f6dbec4,0x3f7f3dc9,0xbf7fbdc9,0xbf62bef1,0x3f623ef1,0xbf0ebf55,0xbf0ebf55,0x3e483f7b,0x3e483f7b,0xbe953f75,0x3e95bf75,0x3f22bf46,0xbf223f46,
0x3f35bf35,0x3f35bf35,0x3ec43f6d,0x3ec43f6d,0xbf753e95,0x3f75be95,0x3dc9bf7f,0xbdc93f7f,0x3f7b3e48,0x3f7b3e48,0xbf0e3f55,0xbf0e3f55,0xbf46bf22,0x3f463f22,0x3f62bef1,0xbf623ef1,
0xbf353f35,0xbf353f35,0xbf6d3ec4,0xbf6d3ec4,0x3f46bf22,0xbf463f22,0x3f75be95,0xbf753e95,0xbf553f0e,0xbf553f0e,0xbf7b3e48,0xbf7b3e48,0x3f62bef1,0xbf623ef1,0x3f7fbdc9,0xbf7f3dc9,
0x3f800000,0x3f800000,0x3ec4bf6d,0x3ec4bf6d,0x3f75be95,0xbf753e95,0x3dc9bf7f,0xbdc93f7f,0x3f55bf0e,0x3f55bf0e,0xbe48bf7b,0xbe48bf7b,0x3f22bf46,0xbf223f46,0xbef1bf62,0x3ef13f62,
0x3f800000,0x3f800000,0xbf6dbec4,0xbf6dbec4,0x3f46bf22,0xbf463f22,0xbf753e95,0x3f75be95,0x3e48bf7b,0x3e48bf7b,0xbf0e3f55,0xbf0e3f55,0xbef1bf62,0x3ef13f62,0x3dc93f7f,0xbdc9bf7f,
0x3f800000,0x3f800000,0xbec43f6d,0xbec43f6d,0x3ef1bf62,0xbef13f62,0x3f223f46,0xbf22bf46,0xbf0ebf55,0xbf0ebf55,0x3f7bbe48,0x3f7bbe48,0xbf7f3dc9,0x3f7fbdc9,0x3e95bf75,0xbe953f75,
0x3f800000,0x3f800000,0x3f6d3ec4,0x3f6d3ec4,0x3dc9bf7f,0xbdc93f7f,0x3ef1bf62,0xbef13f62,0xbf7bbe48,0xbf7bbe48,0xbf55bf0e,0xbf55bf0e,0xbe953f75,0x3e95bf75,0xbf223f46,0x3f22bf46,
0x3f800000,0x3f800000,0x3ec4bf6d,0x3ec4bf6d,0xbe95bf75,0x3e953f75,0xbf7fbdc9,0x3f7f3dc9,0xbf553f0e,0xbf553f0e,0x3e483f7b,0x3e483f7b,0x3f463f22,0xbf46bf22,0x3f62bef1,0xbf623ef1,
0x3f800000,0x3f800000,0xbf6dbec4,0xbf6dbec4,0xbf22bf46,0x3f223f46,0x3e953f75,0xbe95bf75,0xbe483f7b,0xbe483f7b,0x3f0ebf55,0x3f0ebf55,0x3f62bef1,0xbf623ef1,0xbf7f3dc9,0x3f7fbdc9,
0x3f800000,0x3f800000,0xbec43f6d,0xbec43f6d,0xbf62bef1,0x3f623ef1,0x3f46bf22,0xbf463f22,0x3f0e3f55,0x3f0e3f55,0xbf7b3e48,0xbf7b3e48,0xbdc9bf7f,0x3dc93f7f,0x3f753e95,0xbf75be95,
0x3f800000,0x3f800000,0x3f6d3ec4,0x3f6d3ec4,0xbf7fbdc9,0x3f7f3dc9,0xbf62bef1,0x3f623ef1,0x3f7b3e48,0x3f7b3e48,0x3f553f0e,0x3f553f0e,0xbf75be95,0x3f753e95,0xbf46bf22,0x3f463f22,
0xbf35bf35,0xbf35bf35,0xbf6d3ec4,0xbf6d3ec4,0xbf62bef1,0x3f623ef1,0xbf463f22,0x3f46bf22,0xbf7bbe48,0xbf7bbe48,0xbf0e3f55,0xbf0e3f55,0xbf7f3dc9,0x3f7fbdc9,0xbe953f75,0x3e95bf75,
0x3f353f35,0x3f353f35,0xbec4bf6d,0xbec4bf6d,0x3f7f3dc9,0xbf7fbdc9,0xbf62bef1,0x3f623ef1,0x3f55bf0e,0x3f55bf0e,0xbf7b3e48,0xbf7b3e48,0x3e95bf75,0xbe953f75,0xbf223f46,0x3f22bf46,
0xbf35bf35,0xbf35bf35,0x3f6dbec4,0x3f6dbec4,0xbf753e95,0x3f75be95,0x3dc9bf7f,0xbdc93f7f,0xbe483f7b,0xbe483f7b,0xbf55bf0e,0xbf55bf0e,0x3f463f22,0xbf46bf22,0xbf623ef1,0x3f62bef1,
0x3f353f35,0x3f353f35,0x3ec43f6d,0x3ec43f6d,0x3f46bf22,0xbf463f22,0x3f75be95,0xbf753e95,0xbf0ebf55,0xbf0ebf55,0xbe48bf7b,0xbe48bf7b,0xbf623ef1,0x3f62bef1,0xbf7f3dc9,0x3f7fbdc9,
0xbf35bf35,0xbf35bf35,0xbf6d3ec4,0xbf6d3ec4,0xbef13f62,0x3ef1bf62,0x3f223f46,0xbf22bf46,0x3f7b3e48,0x3f7b3e48,0x3f0ebf55,0x3f0ebf55,0xbdc9bf7f,0x3dc93f7f,0xbf75be95,0x3f753e95,
0x3f353f35,0x3f353f35,0xbec4bf6d,0xbec4bf6d,0x3dc9bf7f,0xbdc93f7f,0xbef13f62,0x3ef1bf62,0xbf553f0e,0xbf553f0e,0x3f7bbe48,0x3f7bbe48,0x3f753e95,0xbf75be95,0xbf46bf22,0x3f463f22,
0xbf35bf35,0xbf35bf35,0x3f6dbec4,0x3f6dbec4,0x3e953f75,0xbe95bf75,0xbf7fbdc9,0x3f7f3dc9,0x3e48bf7b,0x3e48bf7b,0x3f553f0e,0x3f553f0e,0xbf223f46,0x3f22bf46,0xbef1bf62,0x3ef13f62,
0x3f353f35,0x3f353f35,0x3ec43f6d,0x3ec43f6d,0xbf22bf46,0x3f223f46,0xbe95bf75,0x3e953f75,0x3f0e3f55,0x3f0e3f55,0x3e483f7b,0x3e483f7b,0xbef1bf62,0x3ef13f62,0xbdc9bf7f,0x3dc93f7f,
0x3f803f80,0x3f35bf35,0x3f803f80,0x3f35bf35,0x3f803f80,0x3f35bf35,0x3f803f80,0x3f35bf35,0x3f803f80,0x3f35bf35,0x3f803f80,0x3f35bf35,0x3f803f80,0x3f35bf35,0x3f803f80,0x3f35bf35,
0x3f463f75,0x3f7fbf62,0xbf46bf75,0xbf7f3f62,0x3dc93ef1,0x3f46bf75,0xbdc9bef1,0xbf463f75,0xbf22be95,0x3dc9bef1,0x3f223e95,0xbdc93ef1,0xbf7fbf62,0xbf223e95,0x3f7f3f62,0x3f22be95,
0x3e483f55,0x3f55bf7b,0x3e483f55,0x3f55bf7b,0xbf7bbf0e,0xbf0ebe48,0xbf7bbf0e,0xbf0ebe48,0xbe48bf55,0xbf553f7b,0xbe48bf55,0xbf553f7b,0x3f7b3f0e,0x3f0e3e48,0x3f7b3f0e,0x3f0e3e48,
0xbef13f22,0x3e95bf7f,0x3ef1bf22,0xbe953f7f,0xbe95bf7f,0xbf623f46,0x3e953f7f,0x3f62bf46,0x3f623f46,0x3f75bdc9,0xbf62bf46,0xbf753dc9,0xbf75bdc9,0xbef1bf22,0x3f753dc9,0x3ef13f22,
0xbf6d3ec4,0xbec4bf6d,0xbf6d3ec4,0xbec4bf6d,0x3f6dbec4,0x3ec43f6d,0x3f6dbec4,0x3ec43f6d,0xbf6d3ec4,0xbec4bf6d,0xbf6d3ec4,0xbec4bf6d,0x3f6dbec4,0x3ec43f6d,0x3f6dbec4,0x3ec43f6d,
0xbf753dc9,0xbf62bf46,0x3f75bdc9,0x3f623f46,0x3ef13f22,0x3f753dc9,0xbef1bf22,0xbf75bdc9,0x3e95bf7f,0xbef13f22,0xbe953f7f,0x3ef1bf22,0xbf623f46,0xbe95bf7f,0x3f62bf46,0x3e953f7f,
0xbf0ebe48,0xbf7bbf0e,0xbf0ebe48,0xbf7bbf0e,0xbf553f7b,0xbe48bf55,0xbf553f7b,0xbe48bf55,0x3f0e3e48,0x3f7b3f0e,0x3f0e3e48,0x3f7b3f0e,0x3f55bf7b,0x3e483f55,0x3f55bf7b,0x3e483f55,
0x3dc9bef1,0xbf22be95,0xbdc93ef1,0x3f223e95,0xbf223e95,0xbf7fbf62,0x3f22be95,0x3f7f3f62,0xbf7f3f62,0xbf46bf75,0x3f7fbf62,0x3f463f75,0xbf463f75,0xbdc9bef1,0x3f46bf75,0x3dc93ef1,
0,0xbf353f35,0,0xbf353f35,0,0xbf353f35,0,0xbf353f35,0,0xbf353f35,0,0xbf353f35,0,0xbf353f35,0,0xbf353f35,
0x3f223e95,0xbdc93ef1,0xbf22be95,0x3dc9bef1,0x3f7f3f62,0x3f22be95,0xbf7fbf62,0xbf223e95,0x3f463f75,0x3f7fbf62,0xbf46bf75,0xbf7f3f62,0x3dc93ef1,0x3f46bf75,0xbdc9bef1,0xbf463f75,
0x3f7b3f0e,0x3f0e3e48,0x3f7b3f0e,0x3f0e3e48,0x3e483f55,0x3f55bf7b,0x3e483f55,0x3f55bf7b,0xbf7bbf0e,0xbf0ebe48,0xbf7bbf0e,0xbf0ebe48,0xbe48bf55,0xbf553f7b,0xbe48bf55,0xbf553f7b,
0x3f623f46,0x3f75bdc9,0xbf62bf46,0xbf753dc9,0xbf75bdc9,0xbef1bf22,0x3f753dc9,0x3ef13f22,0x3ef1bf22,0xbe953f7f,0xbef13f22,0x3e95bf7f,0x3e953f7f,0x3f62bf46,0xbe95bf7f,0xbf623f46,
0x3ec43f6d,0x3f6dbec4,0x3ec43f6d,0x3f6dbec4,0xbec4bf6d,0xbf6d3ec4,0xbec4bf6d,0xbf6d3ec4,0x3ec43f6d,0x3f6dbec4,0x3ec43f6d,0x3f6dbec4,0xbec4bf6d,0xbf6d3ec4,0xbec4bf6d,0xbf6d3ec4,
0xbe953f7f,0x3ef1bf22,0x3e95bf7f,0xbef13f22,0x3f62bf46,0x3e953f7f,0xbf623f46,0xbe95bf7f,0xbf753dc9,0xbf62bf46,0x3f75bdc9,0x3f623f46,0x3ef13f22,0x3f753dc9,0xbef1bf22,0xbf75bdc9,
0xbf553f7b,0xbe48bf55,0xbf553f7b,0xbe48bf55,0x3f0e3e48,0x3f7b3f0e,0x3f0e3e48,0x3f7b3f0e,0x3f55bf7b,0x3e483f55,0x3f55bf7b,0x3e483f55,0xbf0ebe48,0xbf7bbf0e,0xbf0ebe48,0xbf7bbf0e,
0xbf7f3f62,0xbf46bf75,0x3f7fbf62,0x3f463f75,0xbf463f75,0xbdc9bef1,0x3f46bf75,0x3dc93ef1,0xbdc93ef1,0x3f223e95,0x3dc9bef1,0xbf22be95,0x3f22be95,0x3f7f3f62,0xbf223e95,0xbf7fbf62,
0,0x3f35bf35,0,0x3f35bf35,0,0x3f35bf35,0,0x3f35bf35,0,0x3f35bf35,0,0x3f35bf35,0,0x3f35bf35,0,0x3f35bf35,
0xbf22be95,0x3dc9bef1,0x3f223e95,0xbdc93ef1,0xbf7fbf62,0xbf223e95,0x3f7f3f62,0x3f22be95,0xbf46bf75,0xbf7f3f62,0x3f463f75,0x3f7fbf62,0xbdc9bef1,0xbf463f75,0x3dc93ef1,0x3f46bf75,
0xbf7bbf0e,0xbf0ebe48,0xbf7bbf0e,0xbf0ebe48,0xbe48bf55,0xbf553f7b,0xbe48bf55,0xbf553f7b,0x3f7b3f0e,0x3f0e3e48,0x3f7b3f0e,0x3f0e3e48,0x3e483f55,0x3f55bf7b,0x3e483f55,0x3f55bf7b,
0xbf62bf46,0xbf753dc9,0x3f623f46,0x3f75bdc9,0x3f753dc9,0x3ef13f22,0xbf75bdc9,0xbef1bf22,0xbef13f22,0x3e95bf7f,0x3ef1bf22,0xbe953f7f,0xbe95bf7f,0xbf623f46,0x3e953f7f,0x3f62bf46,
0xbec4bf6d,0xbf6d3ec4,0xbec4bf6d,0xbf6d3ec4,0x3ec43f6d,0x3f6dbec4,0x3ec43f6d,0x3f6dbec4,0xbec4bf6d,0xbf6d3ec4,0xbec4bf6d,0xbf6d3ec4,0x3ec43f6d,0x3f6dbec4,0x3ec43f6d,0x3f6dbec4,
0x3e95bf7f,0xbef13f22,0xbe953f7f,0x3ef1bf22,0xbf623f46,0xbe95bf7f,0x3f62bf46,0x3e953f7f,0x3f75bdc9,0x3f623f46,0xbf753dc9,0xbf62bf46,0xbef1bf22,0xbf75bdc9,0x3ef13f22,0x3f753dc9,
0x3f55bf7b,0x3e483f55,0x3f55bf7b,0x3e483f55,0xbf0ebe48,0xbf7bbf0e,0xbf0ebe48,0xbf7bbf0e,0xbf553f7b,0xbe48bf55,0xbf553f7b,0xbe48bf55,0x3f0e3e48,0x3f7b3f0e,0x3f0e3e48,0x3f7b3f0e,
0x3f7fbf62,0x3f463f75,0xbf7f3f62,0xbf46bf75,0x3f46bf75,0x3dc93ef1,0xbf463f75,0xbdc9bef1,0x3dc9bef1,0xbf22be95,0xbdc93ef1,0x3f223e95,0xbf223e95,0xbf7fbf62,0x3f22be95,0x3f7f3f62,
0x3f800000,0x3f7fd397,0x3f800000,0x3f68bf3c,0x3f7f4e6d,0x3f7e70b0,0x3f273656,0x3e8e9a22,0x3f7d3aac,0x3f7baccd,0xbe164083,0xbf0b9a6b,0x3f79c79d,0x3f778bc5,0xbf584853,0xbf7dabcc,
0x3f800000,0x3f7f0e58,0x3f800000,0x3f633c5a,0x3f7c3b28,0x3f778bc5,0x3f13682a,0x3e09cf86,0x3f710908,0x3f68bf3c,0xbeac7cd4,0xbf3b8f3b,0x3f5ebe05,0x3f531849,0xbf76ba07,0xbf7a7302,
0x3f800000,0x3f7dabcc,0x3f800000,0x3f5d2d53,0x3f76ba07,0x3f6b4b0c,0x3efc5d27,0xbc490e90,0x3f5b941a,0x3f47de65,0xbf039c3d,0xbf604621,0x3f3085bb,0x3f15f6d9,0xbf7fec43,0xbf59f26a,
0x3f800000,0x3f7baccd,0x3f800000,0x3f5695e5,0x3f6ed89e,0x3f59f26a,0x3ecf7bca,0xbe22abb6,0x3f3daef9,0x3f1b02c6,0xbf2beb4a,0xbf778bc5,0x3ee63375,0x3e8e9a22,0xbf731447,0xbf1ff6cb,
0x3f800000,0x3f791298,0x3f800000,0x3f4f7a1f,0x3f64aa59,0x3f43e200,0x3ea09ae5,0xbe9aa086,0x3f187fc0,0x3ec9b953,0xbf4d9f02,0xbf7ffb11,0x3e2f10a2,0xbd7b2b74,0xbf514d3d,0xbea68f12,
0x3f800000,0x3f75dec6,0x3f800000,0x3f47de65,0x3f584853,0x3f299415,0x3e605c13,0xbee0924f,0x3edae880,0x3e22abb6,0xbf676bd8,0xbf791298,0xbdfab273,0xbec9b953,0xbf1d7fd1,0x3c490e90,
0x3f800000,0x3f721352,0x3f800000,0x3f3fc767,0x3f49d112,0x3f0b9a6b,0x3dfab273,0xbf10d3cd,0x3e78cfcc,0xbdafb680,0xbf7853f8,0xbf633c5a,0xbecf7bca,0xbf2e3bde,0xbeb8442a,0x3eb263ef,
0x3f800000,0x3f6db293,0x3f800000,0x3f373a23,0x3f396842,0x3ed53641,0x3cc90ab0,0xbf2e3bde,0x3d48fb30,0xbea68f12,0xbf7fb10f,0xbf3fc767,0xbf273656,0xbf633c5a,0xbd96a905,0x3f24d225,
0,0x3d16c32c,0,0x3ed53641,0x3d96a905,0x3de1bc2e,0x3f41d870,0x3f75dec6,0x3e164083,0x3e3b6ecf,0x3f7d3aac,0x3f5695e5,0x3e605c13,0x3e827dc0,0x3f08f59b,0x3e09cf86,
0,0x3dafb680,0,0x3eebcbbb,0x3e2f10a2,0x3e827dc0,0x3f514d3d,0x3f7dabcc,0x3eac7cd4,0x3ed53641,0x3f710908,0x3f2e3bde,0x3efc5d27,0x3f10d3cd,0x3e888e93,0xbe541501,
0,0x3e09cf86,0,0x3f00e7e4,0x3e888e93,0x3ec9b953,0x3f5ebe05,0x3f7ffb11,0x3f039c3d,0x3f1ff6cb,0x3f5b941a,0x3ef6e0cb,0x3f396842,0x3f4f7a1f,0xbcc90ab0,0xbf064b82,
0,0x3e3b6ecf,0,0x3f0b9a6b,0x3eb8442a,0x3f064b82,0x3f6a09a7,0x3f7cbfc9,0x3f2beb4a,0x3f4bbbf8,0x3f3daef9,0x3e827dc0,0x3f64aa59,0x3f75dec6,0xbea09ae5,0xbf47de65,
0,0x3e6c9a7f,0,0x3f15f6d9,0x3ee63375,0x3f24d225,0x3f731447,0x3f740bdd,0x3f4d9f02,0x3f6b4b0c,0x3f187fc0,0x3c490e90,0x3f7c3b28,0x3f7f84ab,0xbf13682a,0xbf721352,
0,0x3e8e9a22,0,0x3f1ff6cb,0x3f08f59b,0x3f3fc767,0x3f79c79d,0x3f660f88,0x3f676bd8,0x3f7cbfc9,0x3edae880,0xbe6c9a7f,0x3f7e1324,0x3f6b4b0c,0xbf49d112,0xbf7ffb11,
0,0x3ea68f12,0,0x3f299415,0x3f1d7fd1,0x3f5695e5,0x3f7e1324,0x3f531849,0x3f7853f8,0x3f7f0e58,0x3e78cfcc,0xbeebcbbb,0x3f6a09a7,0x3f3b8f3b,0xbf6ed89e,0xbf6ff573,
0,0x3ebe1d4a,0,0x3f32c8c9,0x3f3085bb,0x3f68bf3c,0x3f7fec43,0x3f3b8f3b,0x3f7fb10f,0x3f721352,0x3d48fb30,0xbf299415,0x3f41d870,0x3eebcbbb,0xbf7f4e6d,0xbf43e200,
0x35cccccd,0x35cccccd,0x35cccccd,0x35cccccd,0x35cccccd,0x35cccccd,0x35cccccd,0x35cccccd,0x35cccccd,0x35cccccd,0x35cccccd,0x35cccccd,0x35cccccd,0x35cccccd,0x35cccccd,0x35cccccd,
0x35cca946,0x35cc0b7a,0x35ba3296,0x35b5c9e1,0x35caefd6,0x35c9570a,0x35b0f10f,0x35abab1e,0x35c74213,0x35c4b238,0x35a5fb4c,0x359fe51e,0x35c1a90f,0x35be2876,0x35996c52,0x359294e9,
0x35cc3ebe,0x35c9c8ed,0x3585c511,0x356bd9dd,0x35c5619f,0x35bf13b1,0x3549e41f,0x3525fca2,0x35b6eeae,0x35ad06a9,0x35007bea,0x34b37cdc,0x35a1740f,0x35945368,0x34488ec2,0x3320d559,
0x35cb8d5a,0x35c6096a,0x34e429d0,0x345c7f3e,0x35bc3c09,0x35ae5b88,0xb2a0d873,0xb48222f8,0x359cb4cd,0x3587a9aa,0xb4f7673d,0xb533a83f,0x355f5d78,0x352a91ce,0xb567b948,0xb58b6318,
0x35ca9556,0x35c0d407,0xb4706739,0xb509fd76,0x35afa9af,0x3597bf2e,0xb5529394,0xb5898908,0x3573ff99,0x352f2067,0xb5a47f35,0xb5b92313,0x34c70ca3,0x33a0c8f3,0xb5c6a993,0xb5cc8da6,
0x35c9570a,0x35ba3296,0xb55f5d78,0xb5960c2f,0x359fe51e,0x3578046f,0xb5b36b4e,0xb5c6096a,0x3521610f,0x348222f8,0xb5ccc8da,0xb5c74213,0xb40c9200,0xb5053f42,0xb5b5c9e1,0xb5996c52,
0x35c7d2e4,0x35b2319e,0xb5ad06a9,0xb5c5619f,0x358d37c9,0x3538292a,0xb5ccbd02,0xb5c276a0,0x348c0d4f,0xb4488ec2,0xb5a770fe,0xb57bffb5,0xb525fca2,0xb585c511,0xb51369bb,0xb3f10e6e,
0x35c6096a,0x35a8e03a,0xb5caefd6,0xb5c85c01,0x356ff15b,0x34e429d0,0xb5ae5b88,0xb57ff144,0xb3c8ef90,0xb521610f,0xb5053f42,0x32a0d873,0xb58b6318,0xb5b5c9e1,0x350eb659,0x3583db51,
0,0,0,0,0,0,0,0,0,0,0,0,0,0,0,0,
0x33713846,0x340c9200,0x352a91ce,0x353ca2fc,0x345c7f3e,0x3495f23f,0x354e3fd4,0x355f5d78,0x34bd4866,0x34e429d0,0x356ff15b,0x357ff144,0x35053f42,0x3518176e,0x3587a9aa,0x358f0707,
0x33f10e6e,0x348c0d4f,0x359b138d,0x35a770fe,0x34da7db8,0x351369bb,0x35b2319e,0x35bb3aec,0x3538292a,0x355b2291,0x35c276a0,0x35c7d2e4,0x357bffb5,0x358d37c9,0x35cb4283,0x35ccbd02,
0x3434968b,0x34d0c934,0x35c4b238,0x35caefd6,0x3521610f,0x3556df37,0x35ccc8da,0x35ca3307,0x3583db51,0x35996c52,0x35c33cb1,0x35b80c6c,0x35abab1e,0x35ba3296,0x35a8e03a,0x35960c2f,
0x34706739,0x3509fd76,0x35ca9556,0x35c0d407,0x35529394,0x35898908,0x35afa9af,0x3597bf2e,0x35a47f35,0x35b92313,0x3573ff99,0x352f2067,0x35c6a993,0x35cc8da6,0x34c70ca3,0x33a0c8f3,
0x3495f23f,0x352a91ce,0x35abab1e,0x358b6318,0x357ff144,0x35a2fcc6,0x354580a2,0x34d0c934,0x35bc3c09,0x35ca3307,0x32a0d873,0xb4bd4866,0x35cc0b7a,0x35c1a90f,0xb53ca2fc,0xb587a9aa,
0x34b37cdc,0x3549e41f,0x355b2291,0x34da7db8,0x35945368,0x35b6eeae,0xb320d559,0xb5007bea,0x35c9c8ed,0x35cb4283,0xb56bd9dd,0xb5a1740f,0x35bb3aec,0x359b138d,0xb5bf13b1,0xb5cc3ebe,
0x34d0c934,0x3567b948,0x345c7f3e,0xb4a9aa67,0x35a5fb4c,0x35c4b238,0xb556df37,0xb59fe51e,0x35cc6a23,0x35bc3c09,0xb5c1a90f,0xb5ccc8da,0x35960c2f,0x353ca2fc,0xb5bff78f,0xb59cb4cd,
0x3f803f80,0,0,0x3f803f80,0x3f803f80,0,0,0x3f803f80,0x3f803f80,0,0,0x3f803f80,0x3f803f80,0,0,0x3f803f80,
0x3f353f80,0x3f350000,0xbf350000,0x3f353f80,0xbf350000,0x3f353f80,0xbf35bf80,0xbf350000,0xbf35bf80,0xbf350000,0x3f350000,0xbf35bf80,0x3f350000,0xbf35bf80,0x3f353f80,0x3f350000,
0x3f80,0x3f800000,0xbf800000,0x3f80,0xbf80,0xbf800000,0x3f800000,0xbf80,0x3f80,0x3f800000,0xbf800000,0x3f80,0xbf80,0xbf800000,0x3f800000,0xbf80,
0xbf353f80,0x3f350000,0xbf350000,0xbf353f80,0x3f350000,0x3f35bf80,0xbf353f80,0x3f350000,0x3f35bf80,0xbf350000,0x3f350000,0x3f35bf80,0xbf350000,0xbf353f80,0x3f35bf80,0xbf350000,
0xbf803f80,0,0,0xbf803f80,0xbf803f80,0,0,0xbf803f80,0xbf803f80,0,0,0xbf803f80,0xbf803f80,0,0,0xbf803f80,
0xbf353f80,0xbf350000,0x3f350000,0xbf353f80,0x3f350000,0xbf353f80,0x3f35bf80,0x3f350000,0x3f35bf80,0x3f350000,0xbf350000,0x3f35bf80,0xbf350000,0x3f35bf80,0xbf353f80,0xbf350000,
0x3f80,0xbf800000,0x3f800000,0x3f80,0xbf80,0x3f800000,0xbf800000,0xbf80,0x3f80,0xbf800000,0x3f800000,0x3f80,0xbf80,0x3f800000,0xbf800000,0xbf80,
0x3f353f80,0xbf350000,0x3f350000,0x3f353f80,0xbf350000,0xbf35bf80,0x3f353f80,0xbf350000,0xbf35bf80,0x3f350000,0xbf350000,0xbf35bf80,0x3f350000,0x3f353f80,0xbf35bf80,0x3f350000,
0x3f80,0x3f80,0x3f753e95,0x3f753e95,0x3ea13f73,0xbea1bf73,0x3f80bcc9,0xbf803cc9,0x3f183f4e,0x3f183f4e,0x3f71beac,0x3f71beac,0x3f513f13,0xbf51bf13,0x3f4abf1d,0xbf4a3f1d,
0x3f80,0x3f80,0x3e95bf75,0x3e95bf75,0x3f273f42,0xbf27bf42,0xbecfbf6a,0x3ecf3f6a,0x3f7d3e16,0x3f7d3e16,0xbf67bedb,0xbf67bedb,0x3f58bf09,0xbf583f09,0xbf773e89,0x3f77be89,
0x3f80,0x3f80,0xbf75be95,0xbf75be95,0x3f653ee6,0xbf65bee6,0xbf313f39,0x3f31bf39,0x3f4ebf18,0x3f4ebf18,0x3eac3f71,0x3eac3f71,0xbe2fbf7c,0x3e2f3f7c,0x3f7e3dfb,0xbf7ebdfb,
0x3f80,0x3f80,0xbe953f75,0xbe953f75,0x3f7f3d97,0xbf7fbd97,0x3f6f3eb8,0xbf6fbeb8,0x3e16bf7d,0x3e16bf7d,0x3edbbf67,0x3edbbf67,0xbf7abe60,0x3f7a3e60,0xbf5fbefc,0x3f5f3efc,
0x3f80,0x3f80,0x3f753e95,0x3f753e95,0x3f73bea1,0xbf733ea1,0xbcc9bf80,0x3cc93f80,0xbf18bf4e,0xbf18bf4e,0xbf713eac,0xbf713eac,0xbf133f51,0x3f13bf51,0x3f1d3f4a,0xbf1dbf4a,
0x3f80,0x3f80,0x3e95bf75,0x3e95bf75,0x3f42bf27,0xbf423f27,0xbf6a3ecf,0x3f6abecf,0xbf7dbe16,0xbf7dbe16,0x3f673edb,0x3f673edb,0x3f093f58,0xbf09bf58,0xbe89bf77,0x3e893f77,
0x3f80,0x3f80,0xbf75be95,0xbf75be95,0x3ee6bf65,0xbee63f65,0x3f393f31,0xbf39bf31,0xbf4e3f18,0xbf4e3f18,0xbeacbf71,0xbeacbf71,0x3f7cbe2f,0xbf7c3e2f,0xbdfb3f7e,0x3dfbbf7e,
0x3f80,0x3f80,0xbe953f75,0xbe953f75,0x3d97bf7f,0xbd973f7f,0x3eb8bf6f,0xbeb83f6f,0xbe163f7d,0xbe163f7d,0xbedb3f67,0xbedb3f67,0x3e60bf7a,0xbe603f7a,0x3efcbf5f,0xbefc3f5f,
0x3f0ebf55,0x3f0ebf55,0xbf22bf46,0xbf22bf46,0x3e89bf77,0xbe893f77,0xbf58bf09,0x3f583f09,0xbd49bf80,0xbd49bf80,0xbf78be79,0xbf78be79,0xbeb8bf6f,0x3eb83f6f,0xbf7f3d97,0x3f7fbd97,
0xbf0e3f55,0xbf0e3f55,0x3f46bf22,0x3f46bf22,0x3dfb3f7e,0xbdfbbf7e,0x3e2fbf7c,0xbe2f3f7c,0x3f3e3f2c,0x3f3e3f2c,0xbf04bf5c,0xbf04bf5c,0x3f803cc9,0xbf80bcc9,0xbf73bea1,0x3f733ea1,
0x3f0ebf55,0x3f0ebf55,0x3f223f46,0x3f223f46,0xbefcbf5f,0x3efc3f5f,0x3f7abe60,0xbf7a3e60,0xbf803d49,0xbf803d49,0x3e79bf78,0x3e79bf78,0xbecf3f6a,0x3ecfbf6a,0xbf42bf27,0x3f423f27,
0xbf0e3f55,0xbf0e3f55,0xbf463f22,0xbf463f22,0x3f4a3f1d,0xbf4abf1d,0x3f133f51,0xbf13bf51,0x3f2cbf3e,0x3f2cbf3e,0x3f5cbf04,0x3f5cbf04,0xbf31bf39,0x3f313f39,0xbee6bf65,0x3ee63f65,
0x3f0ebf55,0x3f0ebf55,0xbf22bf46,0xbf22bf46,0xbf77be89,0x3f773e89,0xbf093f58,0x3f09bf58,0x3d493f80,0x3d493f80,0x3f783e79,0x3f783e79,0x3f6fbeb8,0xbf6f3eb8,0xbd97bf7f,0x3d973f7f,
0xbf0e3f55,0xbf0e3f55,0x3f46bf22,0x3f46bf22,0x3f7ebdfb,0xbf7e3dfb,0xbf7cbe2f,0x3f7c3e2f,0xbf3ebf2c,0xbf3ebf2c,0x3f043f5c,0x3f043f5c,0xbcc93f80,0x3cc9bf80,0x3ea1bf73,0xbea13f73,
0x3f0ebf55,0x3f0ebf55,0x3f223f46,0x3f223f46,0xbf5f3efc,0x3f5fbefc,0xbe60bf7a,0x3e603f7a,0x3f80bd49,0x3f80bd49,0xbe793f78,0xbe793f78,0xbf6abecf,0x3f6a3ecf,0x3f27bf42,0xbf273f42,
0xbf0e3f55,0xbf0e3f55,0xbf463f22,0xbf463f22,0x3f1dbf4a,0xbf1d3f4a,0x3f51bf13,0xbf513f13,0xbf2c3f3e,0xbf2c3f3e,0xbf5c3f04,0xbf5c3f04,0x3f39bf31,0xbf393f31,0x3f65bee6,0xbf653ee6,
0x3f800000,0x3f800000,0x3e95bf75,0x3e95bf75,0x3f73bea1,0xbf733ea1,0xbcc9bf80,0x3cc93f80,0x3f4ebf18,0x3f4ebf18,0xbeacbf71,0xbeacbf71,0x3f13bf51,0xbf133f51,0xbf1dbf4a,0x3f1d3f4a,
0x3f800000,0x3f800000,0xbf75be95,0xbf75be95,0x3f42bf27,0xbf423f27,0xbf6a3ecf,0x3f6abecf,0x3e16bf7d,0x3e16bf7d,0xbedb3f67,0xbedb3f67,0xbf09bf58,0x3f093f58,0x3e893f77,0xbe89bf77,
0x3f800000,0x3f800000,0xbe953f75,0xbe953f75,0x3ee6bf65,0xbee63f65,0x3f393f31,0xbf39bf31,0xbf18bf4e,0xbf18bf4e,0x3f71beac,0x3f71beac,0xbf7c3e2f,0x3f7cbe2f,0x3dfbbf7e,0xbdfb3f7e,
0x3f800000,0x3f800000,0x3f753e95,0x3f753e95,0x3d97bf7f,0xbd973f7f,0x3eb8bf6f,0xbeb83f6f,0xbf7dbe16,0xbf7dbe16,0xbf67bedb,0xbf67bedb,0xbe603f7a,0x3e60bf7a,0xbefc3f5f,0x3efcbf5f,
0x3f800000,0x3f800000,0x3e95bf75,0x3e95bf75,0xbea1bf73,0x3ea13f73,0xbf803cc9,0x3f80bcc9,0xbf4e3f18,0xbf4e3f18,0x3eac3f71,0x3eac3f71,0x3f513f13,0xbf51bf13,0x3f4abf1d,0xbf4a3f1d,
0x3f800000,0x3f800000,0xbf75be95,0xbf75be95,0xbf27bf42,0x3f273f42,0x3ecf3f6a,0xbecfbf6a,0xbe163f7d,0xbe163f7d,0x3edbbf67,0x3edbbf67,0x3f58bf09,0xbf583f09,0xbf773e89,0x3f77be89,
0x3f800000,0x3f800000,0xbe953f75,0xbe953f75,0xbf65bee6,0x3f653ee6,0x3f31bf39,0xbf313f39,0x3f183f4e,0x3f183f4e,0xbf713eac,0xbf713eac,0xbe2fbf7c,0x3e2f3f7c,0x3f7e3dfb,0xbf7ebdfb,
0x3f800000,0x3f800000,0x3f753e95,0x3f753e95,0xbf7fbd97,0x3f7f3d97,0xbf6fbeb8,0x3f6f3eb8,0x3f7d3e16,0x3f7d3e16,0x3f673edb,0x3f673edb,0xbf7abe60,0x3f7a3e60,0xbf5fbefc,0x3f5f3efc,
0xbf55bf0e,0xbf55bf0e,0xbf463f22,0xbf463f22,0xbf77be89,0x3f773e89,0xbf093f58,0x3f09bf58,0xbf803d49,0xbf803d49,0xbe793f78,0xbe793f78,0xbf6f3eb8,0x3f6fbeb8,0x3d973f7f,0xbd97bf7f,
0x3f553f0e,0x3f553f0e,0xbf22bf46,0xbf22bf46,0x3f7ebdfb,0xbf7e3dfb,0xbf7cbe2f,0x3f7c3e2f,0x3f2cbf3e,0x3f2cbf3e,0xbf5c3f04,0xbf5c3f04,0x3cc9bf80,0xbcc93f80,0xbea13f73,0x3ea1bf73,
0xbf55bf0e,0xbf55bf0e,0x3f46bf22,0x3f46bf22,0xbf5f3efc,0x3f5fbefc,0xbe60bf7a,0x3e603f7a,0x3d493f80,0x3d493f80,0xbf78be79,0xbf78be79,0x3f6a3ecf,0xbf6abecf,0xbf273f42,0x3f27bf42,
0x3f553f0e,0x3f553f0e,0x3f223f46,0x3f223f46,0x3f1dbf4a,0xbf1d3f4a,0x3f51bf13,0xbf513f13,0xbf3ebf2c,0xbf3ebf2c,0xbf04bf5c,0xbf04bf5c,0xbf393f31,0x3f39bf31,0xbf653ee6,0x3f65bee6,
0xbf55bf0e,0xbf55bf0e,0xbf463f22,0xbf463f22,0xbe893f77,0x3e89bf77,0x3f583f09,0xbf58bf09,0x3f80bd49,0x3f80bd49,0x3e79bf78,0x3e79bf78,0xbeb8bf6f,0x3eb83f6f,0xbf7f3d97,0x3f7fbd97,
0x3f553f0e,0x3f553f0e,0xbf22bf46,0xbf22bf46,0xbdfbbf7e,0x3dfb3f7e,0xbe2f3f7c,0x3e2fbf7c,0xbf2c3f3e,0xbf2c3f3e,0x3f5cbf04,0x3f5cbf04,0x3f803cc9,0xbf80bcc9,0xbf73bea1,0x3f733ea1,
0xbf55bf0e,0xbf55bf0e,0x3f46bf22,0x3f46bf22,0x3efc3f5f,0xbefcbf5f,0xbf7a3e60,0x3f7abe60,0xbd49bf80,0xbd49bf80,0x3f783e79,0x3f783e79,0xbecf3f6a,0x3ecfbf6a,0xbf42bf27,0x3f423f27,
0x3f553f0e,0x3f553f0e,0x3f223f46,0x3f223f46,0xbf4abf1d,0x3f4a3f1d,0xbf13bf51,0x3f133f51,0x3f3e3f2c,0x3f3e3f2c,0x3f043f5c,0x3f043f5c,0xbf31bf39,0x3f313f39,0xbee6bf65,0x3ee63f65,
0x3f803f80,0x3f55bf55,0x3f803f80,0x3f55bf55,0x3f803f80,0x3f55bf55,0x3f803f80,0x3f55bf55,0x3f803f80,0x3f55bf55,0x3f803f80,0x3f55bf55,0x3f803f80,0x3f55bf55,0x3f803f80,0x3f55bf55,
0x3f423f73,0x3f7ebf77,0xbf42bf73,0xbf7e3f77,0x3d973ee6,0x3f1dbf5f,0xbd97bee6,0xbf1d3f5f,0xbf27bea1,0xbdfbbe89,0x3f273ea1,0x3dfb3e89,0xbf7fbf65,0xbf4a3efc,0x3f7f3f65,0x3f4abefc,
0x3e163f4e,0x3f2cbf80,0x3e163f4e,0x3f2cbf80,0xbf7dbf18,0xbf3e3d49,0xbf7dbf18,0xbf3e3d49,0xbe16bf4e,0xbf2c3f80,0xbe16bf4e,0xbf2c3f80,0x3f7d3f18,0x3f3ebd49,0x3f7d3f18,0x3f3ebd49,
0xbf093f13,0x3cc9bf6f,0x3f09bf13,0xbcc93f6f,0xbe60bf7c,0xbf393f6a,0x3e603f7c,0x3f39bf6a,0x3f583f51,0x3f80beb8,0xbf58bf51,0xbf803eb8,0xbf7abe2f,0xbf31becf,0x3f7a3e2f,0x3f313ecf,
0xbf753e95,0xbf22bf46,0xbf753e95,0xbf22bf46,0x3f75be95,0x3f223f46,0x3f75be95,0x3f223f46,0xbf753e95,0xbf22bf46,0xbf753e95,0xbf22bf46,0x3f75be95,0x3f223f46,0x3f75be95,0x3f223f46,
0xbf6abcc9,0xbf7cbf09,0x3f6a3cc9,0x3f7c3f09,0x3eb83f39,0x3f51be60,0xbeb8bf39,0xbf513e60,0x3ecfbf80,0xbe2f3f58,0xbecf3f80,0x3e2fbf58,0xbf6f3f31,0xbf13bf7a,0x3f6fbf31,0x3f133f7a,
0xbedbbeac,0xbf5cbe79,0xbedbbeac,0xbf5cbe79,0xbf673f71,0xbf04bf78,0xbf673f71,0xbf04bf78,0x3edb3eac,0x3f5c3e79,0x3edb3eac,0x3f5c3e79,0x3f67bf71,0x3f043f78,0x3f67bf71,0x3f043f78,
0x3e89bf1d,0xbea13d97,0xbe893f1d,0x3ea1bd97,0xbefc3dfb,0xbf65bf27,0x3efcbdfb,0x3f653f27,0xbf773f4a,0xbf73bf7f,0x3f77bf4a,0x3f733f7f,0xbf5f3f7e,0xbee6bf42,0x3f5fbf7e,0x3ee63f42,
0,0xbf0e3f0e,0,0xbf0e3f0e,0,0xbf0e3f0e,0,0xbf0e3f0e,0,0xbf0e3f0e,0,0xbf0e3f0e,0,0xbf0e3f0e,0,0xbf0e3f0e,
0x3f273ea1,0x3dfb3e89,0xbf27bea1,0xbdfbbe89,0x3f7f3f65,0x3f4abefc,0xbf7fbf65,0xbf4a3efc,0x3f423f73,0x3f7ebf77,0xbf42bf73,0xbf7e3f77,0x3d973ee6,0x3f1dbf5f,0xbd97bee6,0xbf1d3f5f,
0x3f7d3f18,0x3f3ebd49,0x3f7d3f18,0x3f3ebd49,0x3e163f4e,0x3f2cbf80,0x3e163f4e,0x3f2cbf80,0xbf7dbf18,0xbf3e3d49,0xbf7dbf18,0xbf3e3d49,0xbe16bf4e,0xbf2c3f80,0xbe16bf4e,0xbf2c3f80,
0x3f583f51,0x3f80beb8,0xbf58bf51,0xbf803eb8,0xbf7abe2f,0xbf31becf,0x3f7a3e2f,0x3f313ecf,0x3f09bf13,0xbcc93f6f,0xbf093f13,0x3cc9bf6f,0x3e603f7c,0x3f39bf6a,0xbe60bf7c,0xbf393f6a,
0x3e953f75,0x3f46bf22,0x3e953f75,0x3f46bf22,0xbe95bf75,0xbf463f22,0xbe95bf75,0xbf463f22,0x3e953f75,0x3f46bf22,0x3e953f75,0x3f46bf22,0xbe95bf75,0xbf463f22,0xbe95bf75,0xbf463f22,
0xbecf3f80,0x3e2fbf58,0x3ecfbf80,0xbe2f3f58,0x3f6fbf31,0x3f133f7a,0xbf6f3f31,0xbf13bf7a,0xbf6abcc9,0xbf7cbf09,0x3f6a3cc9,0x3f7c3f09,0x3eb83f39,0x3f51be60,0xbeb8bf39,0xbf513e60,
0xbf673f71,0xbf04bf78,0xbf673f71,0xbf04bf78,0x3edb3eac,0x3f5c3e79,0x3edb3eac,0x3f5c3e79,0x3f67bf71,0x3f043f78,0x3f67bf71,0x3f043f78,0xbedbbeac,0xbf5cbe79,0xbedbbeac,0xbf5cbe79,
0xbf773f4a,0xbf73bf7f,0x3f77bf4a,0x3f733f7f,0xbf5f3f7e,0xbee6bf42,0x3f5fbf7e,0x3ee63f42,0xbe893f1d,0x3ea1bd97,0x3e89bf1d,0xbea13d97,0x3efcbdfb,0x3f653f27,0xbefc3dfb,0xbf65bf27,
0,0x3f0ebf0e,0,0x3f0ebf0e,0,0x3f0ebf0e,0,0x3f0ebf0e,0,0x3f0ebf0e,0,0x3f0ebf0e,0,0x3f0ebf0e,0,0x3f0ebf0e,
0xbf27bea1,0xbdfbbe89,0x3f273ea1,0x3dfb3e89,0xbf7fbf65,0xbf4a3efc,0x3f7f3f65,0x3f4abefc,0xbf42bf73,0xbf7e3f77,0x3f423f73,0x3f7ebf77,0xbd97bee6,0xbf1d3f5f,0x3d973ee6,0x3f1dbf5f,
0xbf7dbf18,0xbf3e3d49,0xbf7dbf18,0xbf3e3d49,0xbe16bf4e,0xbf2c3f80,0xbe16bf4e,0xbf2c3f80,0x3f7d3f18,0x3f3ebd49,0x3f7d3f18,0x3f3ebd49,0x3e163f4e,0x3f2cbf80,0x3e163f4e,0x3f2cbf80,
0xbf58bf51,0xbf803eb8,0x3f583f51,0x3f80beb8,0x3f7a3e2f,0x3f313ecf,0xbf7abe2f,0xbf31becf,0xbf093f13,0x3cc9bf6f,0x3f09bf13,0xbcc93f6f,0xbe60bf7c,0xbf393f6a,0x3e603f7c,0x3f39bf6a,
0xbe95bf75,0xbf463f22,0xbe95bf75,0xbf463f22,0x3e953f75,0x3f46bf22,0x3e953f75,0x3f46bf22,0xbe95bf75,0xbf463f22,0xbe95bf75,0xbf463f22,0x3e953f75,0x3f46bf22,0x3e953f75,0x3f46bf22,
0x3ecfbf80,0xbe2f3f58,0xbecf3f80,0x3e2fbf58,0xbf6f3f31,0xbf13bf7a,0x3f6fbf31,0x3f133f7a,0x3f6a3cc9,0x3f7c3f09,0xbf6abcc9,0xbf7cbf09,0xbeb8bf39,0xbf513e60,0x3eb83f39,0x3f51be60,
0x3f67bf71,0x3f043f78,0x3f67bf71,0x3f043f78,0xbedbbeac,0xbf5cbe79,0xbedbbeac,0xbf5cbe79,0xbf673f71,0xbf04bf78,0xbf673f71,0xbf04bf78,0x3edb3eac,0x3f5c3e79,0x3edb3eac,0x3f5c3e79,
0x3f77bf4a,0x3f733f7f,0xbf773f4a,0xbf73bf7f,0x3f5fbf7e,0x3ee63f42,0xbf5f3f7e,0xbee6bf42,0x3e89bf1d,0xbea13d97,0xbe893f1d,0x3ea1bd97,0xbefc3dfb,0xbf65bf27,0x3efcbdfb,0x3f653f27,
0x3f800000,0x3f7fcbe2,0x3f800000,0x3f686b39,0x3f7f2f9d,0x3f7e2b72,0x3f26050a,0x3e8a11f7,0x3f7cbfc9,0x3f7aed37,0xbe22abb6,0xbf0ee0db,0x3f78b47b,0x3f76167a,0xbf5ac450,0xbf7e5a38,
0x3f800000,0x3f7efcc9,0x3f800000,0x3f62df7b,0x3f7bf531,0x3f76ef5b,0x3f121eb0,0x3e007745,0x3f6ff573,0x3f671599,0xbeb263ef,0xbf3e35c5,0x3f5c61c7,0x3f4fefa8,0xbf77f110,0xbf7940c0,
0x3f800000,0x3f7d906e,0x3f800000,0x3f5cc7d1,0x3f764d97,0x3f6a5ad9,0x3ef9a02d,0xbcafea69,0x3f59f26a,0x3f456439,0xbf064b82,0xbf62241a,0x3f2d1469,0x3f11796b,0xbf7fc38f,0xbf570348,
0x3f800000,0x3f7b87b2,0x3f800000,0x3f5627fe,0x3f6e46be,0x3f58b3a1,0x3ecc9b8b,0xbe2bf804,0x3f3b8f3b,0x3f17de12,0xbf2e3bde,0xbf788486,0x3eddbe79,0x3e840270,0xbf718f57,0xbf1ba299,
0x3f800000,0x3f78e3d6,0x3f800000,0x3f4f0417,0x3f63f473,0x3f425b89,0x3e9d9e78,0xbe9f1cdf,0x3f15f6d9,0x3ec27b55,0xbf4f7a1f,0xbf7fffb1,0x3e1c76de,0xbda973ba,0xbf4e8d90,0xbe9c1faf,
0x3f800000,0x3f75a67b,0x3f800000,0x3f476085,0x3f577026,0x3f27ce61,0x3e5a3997,0xbee4cbfe,0x3ed53641,0x3e1324ca,0xbf68bf3c,0xbf7822d1,0xbe1008b7,0xbed3c867,0xbf19c200,0x3d0a342f,
0x3f800000,0x3f71d19f,0x3f800000,0x3f3f41fc,0x3f48d8b3,0x3f099f4e,0x3dee3876,0xbf12c39a,0x3e6c9a7f,0xbdcefdb7,0xbf791298,0xbf61668a,0xbed8106b,0xbf3238aa,0xbeaf713a,0x3ebca7af,
0x3f800000,0x3f6d67a1,0x3f800000,0x3f36ad7f,0x3f385216,0x3ed0eb2a,0x3c96c9b6,0xbf2ff3e6,0x3d16c32c,0xbeadf73c,0xbf7fd397,0xbf3d27b8,0xbf2ac082,0xbf65b710,0xbd621469,0x3f28fd41,
0,0x3d2351cb,0,0x3ed6a399,0x3da3308c,0x3df475c0,0x3f42de29,0x3f76841b,0x3e22abb6,0x3e4ada4f,0x3f7cbfc9,0x3f546b3b,0x3e72b651,0x3e8d17c0,0x3f04f484,0x3de7fa9a,
0,0x3db5f8da,0,0x3eed3063,0x3e354098,0x3e870ada,0x3f5233c6,0x3f7dfa38,0x3eb263ef,0x3edc53c1,0x3f6ff573,0x3f2b561b,0x3f0242b1,0x3f1553b7,0x3e7ee6e1,0xbe698bba,
0,0x3e0cec4a,0,0x3f019573,0x3e8b9507,0x3ece0bea,0x3f5f8327,0x3f7ff0e3,0x3f064b82,0x3f2302d3,0x3f59f26a,0x3eeff7fb,0x3f3ca003,0x3f52a649,0xbd2fe007,0xbf0af1b7,
0,0x3e3e853e,0,0x3f0c42c9,0x3ebb31a0,0x3f084b92,0x3f6aab7b,0x3f7c5d3a,0x3f2e3bde,0x3f4e1689,0x3f3b8f3b,0x3e75c35a,0x3f66becc,0x3f77583a,0xbea986c4,0xbf4b41fa,
0,0x3e6fa8b2,0,0x3f16999f,0x3ee900b7,0x3f269de3,0x3f73913f,0x3f73530e,0x3f4f7a1f,0x3f6cd007,0x3f15f6d9,0xbb490fc6,0x3f7cfe73,0x3f7f1f49,0xbf173c07,0xbf73ced9,
0,0x3e901c2c,0,0x3f209393,0x3f0a48ad,0x3f4154e1,0x3f7a1e84,0x3f650479,0x3f68bf3c,0x3f7d57de,0x3ed53641,0xbe7bdba4,0x3f7d7474,0x3f6912ae,0xbf4cae79,0xbf7fdaaf,
0,0x3ea80b1f,0,0x3f2a2a80,0x3f1ebc12,0x3f57dc7f,0x3f7e4323,0x3f51c0c2,0x3f791298,0x3f7eb069,0x3e6c9a7f,0xbef2bd43,0x3f6816a8,0x3f37c655,0xbf708066,0xbf6dfcf2,
0,0x3ebf926f,0,0x3f33587a,0x3f31a81d,0x3f69b7e4,0x3f7ff4e6,0x3f39f2ac,0x3f7fd397,0x3f70c501,0x3d16c32c,0xbf2c800f,0x3f3ebc1b,0x3ee1fb6a,0xbf7f9c18,0xbf404c5c,
0x35cccccd,0x35cccccd,0x35cccccd,0x35cccccd,0x35cccccd,0x35cccccd,0x35cccccd,0x35cccccd,0x35cccccd,0x35cccccd,0x35cccccd,0x35cccccd,0x35cccccd,0x35cccccd,0x35cccccd,0x35cccccd,
0x35cca31b,0x35cbfd6e,0x35b9ef61,0x35b57f95,0x35cad9f2,0x35c9395b,0x35b09fda,0x35ab5332,0x35c71cab,0x35c4852f,0x35a59ce0,0x359f806a,0x35c17480,0x35bdec81,0x35990197,0x35922466,
0x35cc2618,0x35c990f4,0x3584d0d5,0x3569cab3,0x35c50adf,0x35be9eff,0x3547b357,0x3523afa2,0x35b65d28,0x35ac59b8,0x34fc30c0,0x34ae9479,0x35a0ad5c,0x359374de,0x343e9392,0x32f142bd,
0x35cb55f5,0x35c58c49,0x34dce98c,0x344d8ba2,0x35bb7be1,0x35ad5c81,0xb30cbb87,0xb4899337,0x359b7c6d,0x35863eb4,0xb4fe9498,0xb5370998,0x355c3217,0x35272288,0xb56ad291,0xb58cc31e,
0x35ca3307,0x35bff78f,0xb48222f8,0xb50eb659,0x35ae5b88,0x35960c2f,0xb556df37,0xb58b6318,0x356ff15b,0x352a91ce,0xb5a5fb4c,0xb5ba3296,0x34bd4866,0x33713846,0xb5c74213,0xb5cca946,
0x35c8bdc6,0x35b8de14,0xb5649af8,0xb5982b04,0x359de9c7,0x3572fcea,0xb5b4e9ae,0xb5c6d06b,0x351b95de,0x346b6e11,0xb5cccc8e,0xb5c68241,0xb42597c6,0xb50b2c30,0xb5b45208,0xb59752fa,
0x35c6f6c8,0x35b04e38,0xb5af0373,0xb5c65a74,0x358a76bb,0x3531652e,0xb5cc9c72,0xb5c13f79,0x347a57c9,0xb4667457,0xb5a53e0d,0xb5760334,0xb52cd9f0,0xb5889a01,0xb50c5a95,0xb3b4dd20,
0x35c4dec8,0x35a65953,0xb5cb7b60,0xb5c76700,0x3568c245,0x34d3371a,0xb5ac02a0,0xb5790428,0xb4078fc8,0xb5296d1f,0xb4f9cc4b,0x335d204b,0xb58e93bb,0xb5b7c5a7,0x3516ec8c,0x35873101,
0,0,0,0,0,0,0,0,0,0,0,0,0,0,0,0,
0x3382a7d6,0x341193e2,0x352bb614,0x353dc04f,0x34617a10,0x34986a98,0x354f5584,0x35606adb,0x34bfba28,0x34e6937a,0x3570f5cb,0x3580760f,0x35066f4c,0x351941f2,0x35882200,0x358f79fb,
0x34028d3d,0x3491007a,0x359be4ed,0x35a8296b,0x34df54d8,0x3515c14d,0x35b2cf52,0x35bbbc62,0x353a66f9,0x355d4116,0x35c2da99,0x35c8186a,0x357df9b6,0x358e2017,0x35cb68e9,0x35ccc3eb,
0x34439166,0x34d8115e,0x35c5367c,0x35cb2e94,0x3524d655,0x355a1284,0x35ccc0b6,0x35c9e42e,0x35854b1c,0x359aaa4d,0x35c2a8d8,0x35b736c7,0x35acb065,0x35baf983,0x35a7cd68,0x3594c224,
0x348222f8,0x350eb659,0x35ca3307,0x35bff78f,0x3556df37,0x358b6318,0x35ae5b88,0x35960c2f,0x35a5fb4c,0x35ba3296,0x356ff15b,0x352a91ce,0x35c74213,0x35cca946,0x34bd4866,0x33713846,
0x34a2483f,0x35304301,0x35a9ef63,0x358911af,0x358268a9,0x35a4ded4,0x353ff996,0x34c49c48,0x35bd7339,0x35caacb2,0xb1a0d96b,0xb4c97c83,0x35cbc054,0x35c09d9b,0xb5423103,0xb58a000c,
0x34c22b74,0x35506ab5,0x3554ba6c,0x34cbebe7,0x3596e669,0x35b898a3,0xb38cb338,0xb5079f03,0x35ca6529,0x35cac390,0xb571f9a5,0xb5a3bec8,0x35b9abba,0x3598967c,0xb5c066b8,0xb5cc7ce0,
0x34e1bf99,0x356eec58,0x34399548,0xb4bad62f,0x35a88507,0x35c5e02f,0xb55e4f8b,0xb5a29b2e,0x35cc1907,0x35ba7558,0xb5c30be1,0xb5ccaef3,0x35930511,0x3534c922,0xb5be63f5,0xb599d6b0,
0x3f803f80,0,0,0x3f803f80,0x3f803f80,0,0,0x3f803f80,0x3f803f80,0,0,0x3f803f80,0x3f803f80,0,0,0x3f803f80,
0x3f353f80,0x3f350000,0xbf350000,0x3f353f80,0xbf350000,0x3f353f80,0xbf35bf80,0xbf350000,0xbf35bf80,0xbf350000,0x3f350000,0xbf35bf80,0x3f350000,0xbf35bf80,0x3f353f80,0x3f350000,
0x3f80,0x3f800000,0xbf800000,0x3f80,0xbf80,0xbf800000,0x3f800000,0xbf80,0x3f80,0x3f800000,0xbf800000,0x3f80,0xbf80,0xbf800000,0x3f800000,0xbf80,
0xbf353f80,0x3f350000,0xbf350000,0xbf353f80,0x3f350000,0x3f35bf80,0xbf353f80,0x3f350000,0x3f35bf80,0xbf350000,0x3f350000,0x3f35bf80,0xbf350000,0xbf353f80,0x3f35bf80,0xbf350000,
0xbf803f80,0,0,0xbf803f80,0xbf803f80,0,0,0xbf803f80,0xbf803f80,0,0,0xbf803f80,0xbf803f80,0,0,0xbf803f80,
0xbf353f80,0xbf350000,0x3f350000,0xbf353f80,0x3f350000,0xbf353f80,0x3f35bf80,0x3f350000,0x3f35bf80,0x3f350000,0xbf350000,0x3f35bf80,0xbf350000,0x3f35bf80,0xbf353f80,0xbf350000,
0x3f80,0xbf800000,0x3f800000,0x3f80,0xbf80,0x3f800000,0xbf800000,0xbf80,0x3f80,0xbf800000,0x3f800000,0x3f80,0xbf80,0x3f800000,0xbf800000,0xbf80,
0x3f353f80,0xbf350000,0x3f350000,0x3f353f80,0xbf350000,0xbf35bf80,0x3f353f80,0xbf350000,0xbf35bf80,0x3f350000,0xbf350000,0xbf35bf80,0x3f350000,0x3f353f80,0xbf35bf80,0x3f350000,
0x3f80,0x3f80,0x3f7b3e48,0x3f7b3e48,0x3eac3f71,0xbeacbf71,0x3f7dbe16,0xbf7d3e16,0x3f223f46,0x3f223f46,0x3f62bef1,0x3f62bef1,0x3f5c3f04,0xbf5cbf04,0x3f2cbf3e,0xbf2c3f3e,
0x3f80,0x3f80,0x3e48bf7b,0x3e48bf7b,0x3f2c3f3e,0xbf2cbf3e,0xbf04bf5c,0x3f043f5c,0x3f7f3dc9,0x3f7f3dc9,0xbf75be95,0xbf75be95,0x3f4ebf18,0xbf4e3f18,0xbf673edb,0x3f67bedb,
0x3f80,0x3f80,0xbf7bbe48,0xbf7bbe48,0x3f673edb,0xbf67bedb,0xbf183f4e,0x3f18bf4e,0x3f46bf22,0x3f46bf22,0x3ef13f62,0x3ef13f62,0xbe79bf78,0x3e793f78,0x3f80bd49,0xbf803d49,
0x3f80,0x3f80,0xbe483f7b,0xbe483f7b,0x3f803d49,0xbf80bd49,0x3f783e79,0xbf78be79,0x3dc9bf7f,0x3dc9bf7f,0x3e95bf75,0x3e95bf75,0xbf7dbe16,0x3f7d3e16,0xbf71beac,0x3f713eac,
0x3f80,0x3f80,0x3f7b3e48,0x3f7b3e48,0x3f71beac,0xbf713eac,0xbe16bf7d,0x3e163f7d,0xbf22bf46,0xbf22bf46,0xbf623ef1,0xbf623ef1,0xbf043f5c,0x3f04bf5c,0x3f3e3f2c,0xbf3ebf2c,
0x3f80,0x3f80,0x3e48bf7b,0x3e48bf7b,0x3f3ebf2c,0xbf3e3f2c,0xbf5c3f04,0x3f5cbf04,0xbf7fbdc9,0xbf7fbdc9,0x3f753e95,0x3f753e95,0x3f183f4e,0xbf18bf4e,0xbedbbf67,0x3edb3f67,
0x3f80,0x3f80,0xbf7bbe48,0xbf7bbe48,0x3edbbf67,0xbedb3f67,0x3f4e3f18,0xbf4ebf18,0xbf463f22,0xbf463f22,0xbef1bf62,0xbef1bf62,0x3f78be79,0xbf783e79,0x3d493f80,0xbd49bf80,
0x3f80,0x3f80,0xbe483f7b,0xbe483f7b,0x3d49bf80,0xbd493f80,0x3e79bf78,0xbe793f78,0xbdc93f7f,0xbdc93f7f,0xbe953f75,0xbe953f75,0x3e16bf7d,0xbe163f7d,0x3eacbf71,0xbeac3f71,
0x3ec4bf6d,0x3ec4bf6d,0xbf55bf0e,0xbf55bf0e,0x3d49bf80,0xbd493f80,0xbf78be79,0x3f783e79,0xbe95bf75,0xbe95bf75,0xbf7f3dc9,0xbf7f3dc9,0xbf18bf4e,0x3f183f4e,0xbf673edb,0x3f67bedb,
0xbec43f6d,0xbec43f6d,0x3f0ebf55,0x3f0ebf55,0x3eac3f71,0xbeacbf71,0xbe16bf7d,0x3e163f7d,0x3f623ef1,0x3f623ef1,0xbf46bf22,0xbf46bf22,0x3f78be79,0xbf783e79,0xbf803d49,0x3f80bd49,
0x3ec4bf6d,0x3ec4bf6d,0x3f553f0e,0x3f553f0e,0xbf2cbf3e,0x3f2c3f3e,0x3f5cbf04,0xbf5c3f04,0xbf753e95,0xbf753e95,0xbdc9bf7f,0xbdc9bf7f,0xbe163f7d,0x3e16bf7d,0xbf71beac,0x3f713eac,
0xbec43f6d,0xbec43f6d,0xbf0e3f55,0xbf0e3f55,0x3f673edb,0xbf67bedb,0x3f4e3f18,0xbf4ebf18,0x3ef1bf62,0x3ef1bf62,0x3f22bf46,0x3f22bf46,0xbf5cbf04,0x3f5c3f04,0xbf3ebf2c,0x3f3e3f2c,
0x3ec4bf6d,0x3ec4bf6d,0xbf55bf0e,0xbf55bf0e,0xbf80bd49,0x3f803d49,0xbe793f78,0x3e79bf78,0x3e953f75,0x3e953f75,0x3f7fbdc9,0x3f7fbdc9,0x3f4ebf18,0xbf4e3f18,0xbedbbf67,0x3edb3f67,
0xbec43f6d,0xbec43f6d,0x3f0ebf55,0x3f0ebf55,0x3f71beac,0xbf713eac,0xbf7d3e16,0x3f7dbe16,0xbf62bef1,0xbf62bef1,0x3f463f22,0x3f463f22,0x3e793f78,0xbe79bf78,0xbd49bf80,0x3d493f80,
0x3ec4bf6d,0x3ec4bf6d,0x3f553f0e,0x3f553f0e,0xbf3e3f2c,0x3f3ebf2c,0xbf04bf5c,0x3f043f5c,0x3f75be95,0x3f75be95,0x3dc93f7f,0x3dc93f7f,0xbf7dbe16,0x3f7d3e16,0x3eacbf71,0xbeac3f71,
0xbec43f6d,0xbec43f6d,0xbf0e3f55,0xbf0e3f55,0x3edbbf67,0xbedb3f67,0x3f18bf4e,0xbf183f4e,0xbef13f62,0xbef13f62,0xbf223f46,0xbf223f46,0x3f04bf5c,0xbf043f5c,0x3f2cbf3e,0xbf2c3f3e,
0x3f800000,0x3f800000,0x3e48bf7b,0x3e48bf7b,0x3f71beac,0xbf713eac,0xbe16bf7d,0x3e163f7d,0x3f46bf22,0x3f46bf22,0xbef1bf62,0xbef1bf62,0x3f04bf5c,0xbf043f5c,0xbf3ebf2c,0x3f3e3f2c,
0x3f800000,0x3f800000,0xbf7bbe48,0xbf7bbe48,0x3f3ebf2c,0xbf3e3f2c,0xbf5c3f04,0x3f5cbf04,0x3dc9bf7f,0x3dc9bf7f,0xbe953f75,0xbe953f75,0xbf18bf4e,0x3f183f4e,0x3edb3f67,0xbedbbf67,
0x3f800000,0x3f800000,0xbe483f7b,0xbe483f7b,0x3edbbf67,0xbedb3f67,0x3f4e3f18,0xbf4ebf18,0xbf22bf46,0xbf22bf46,0x3f62bef1,0x3f62bef1,0xbf783e79,0x3f78be79,0xbd49bf80,0x3d493f80,
0x3f800000,0x3f800000,0x3f7b3e48,0x3f7b3e48,0x3d49bf80,0xbd493f80,0x3e79bf78,0xbe793f78,0xbf7fbdc9,0xbf7fbdc9,0xbf75be95,0xbf75be95,0xbe163f7d,0x3e16bf7d,0xbeac3f71,0x3eacbf71,
0x3f800000,0x3f800000,0x3e48bf7b,0x3e48bf7b,0xbeacbf71,0x3eac3f71,0xbf7d3e16,0x3f7dbe16,0xbf463f22,0xbf463f22,0x3ef13f62,0x3ef13f62,0x3f5c3f04,0xbf5cbf04,0x3f2cbf3e,0xbf2c3f3e,
0x3f800000,0x3f800000,0xbf7bbe48,0xbf7bbe48,0xbf2cbf3e,0x3f2c3f3e,0x3f043f5c,0xbf04bf5c,0xbdc93f7f,0xbdc93f7f,0x3e95bf75,0x3e95bf75,0x3f4ebf18,0xbf4e3f18,0xbf673edb,0x3f67bedb,
0x3f800000,0x3f800000,0xbe483f7b,0xbe483f7b,0xbf67bedb,0x3f673edb,0x3f18bf4e,0xbf183f4e,0x3f223f46,0x3f223f46,0xbf623ef1,0xbf623ef1,0xbe79bf78,0x3e793f78,0x3f80bd49,0xbf803d49,
0x3f800000,0x3f800000,0x3f7b3e48,0x3f7b3e48,0xbf80bd49,0x3f803d49,0xbf78be79,0x3f783e79,0x3f7f3dc9,0x3f7f3dc9,0x3f753e95,0x3f753e95,0xbf7dbe16,0x3f7d3e16,0xbf71beac,0x3f713eac,
0xbf6dbec4,0xbf6dbec4,0xbf0e3f55,0xbf0e3f55,0xbf80bd49,0x3f803d49,0xbe793f78,0x3e79bf78,0xbf753e95,0xbf753e95,0x3dc93f7f,0x3dc93f7f,0xbf4e3f18,0x3f4ebf18,0x3edb3f67,0xbedbbf67,
0x3f6d3ec4,0x3f6d3ec4,0xbf55bf0e,0xbf55bf0e,0x3f71beac,0xbf713eac,0xbf7d3e16,0x3f7dbe16,0x3ef1bf62,0x3ef1bf62,0xbf223f46,0xbf223f46,0xbe79bf78,0x3e793f78,0x3d493f80,0xbd49bf80,
0xbf6dbec4,0xbf6dbec4,0x3f0ebf55,0x3f0ebf55,0xbf3e3f2c,0x3f3ebf2c,0xbf04bf5c,0x3f043f5c,0x3e953f75,0x3e953f75,0xbf7f3dc9,0xbf7f3dc9,0x3f7d3e16,0xbf7dbe16,0xbeac3f71,0x3eacbf71,
0x3f6d3ec4,0x3f6d3ec4,0x3f553f0e,0x3f553f0e,0x3edbbf67,0xbedb3f67,0x3f18bf4e,0xbf183f4e,0xbf62bef1,0xbf62bef1,0xbf46bf22,0xbf46bf22,0xbf043f5c,0x3f04bf5c,0xbf2c3f3e,0x3f2cbf3e,
0xbf6dbec4,0xbf6dbec4,0xbf0e3f55,0xbf0e3f55,0xbd493f80,0x3d49bf80,0x3f783e79,0xbf78be79,0x3f75be95,0x3f75be95,0xbdc9bf7f,0xbdc9bf7f,0xbf18bf4e,0x3f183f4e,0xbf673edb,0x3f67bedb,
0x3f6d3ec4,0x3f6d3ec4,0xbf55bf0e,0xbf55bf0e,0xbeacbf71,0x3eac3f71,0x3e163f7d,0xbe16bf7d,0xbef13f62,0xbef13f62,0x3f22bf46,0x3f22bf46,0x3f78be79,0xbf783e79,0xbf803d49,0x3f80bd49,
0xbf6dbec4,0xbf6dbec4,0x3f0ebf55,0x3f0ebf55,0x3f2c3f3e,0xbf2cbf3e,0xbf5c3f04,0x3f5cbf04,0xbe95bf75,0xbe95bf75,0x3f7fbdc9,0x3f7fbdc9,0xbe163f7d,0x3e16bf7d,0xbf71beac,0x3f713eac,
0x3f6d3ec4,0x3f6d3ec4,0x3f553f0e,0x3f553f0e,0xbf67bedb,0x3f673edb,0xbf4ebf18,0x3f4e3f18,0x3f623ef1,0x3f623ef1,0x3f463f22,0x3f463f22,0xbf5cbf04,0x3f5c3f04,0xbf3ebf2c,0x3f3e3f2c,
0x3f803f80,0x3f6dbf6d,0x3f803f80,0x3f6dbf6d,0x3f803f80,0x3f6dbf6d,0x3f803f80,0x3f6dbf6d,0x3f803f80,0x3f6dbf6d,0x3f803f80,0x3f6dbf6d,0x3f803f80,0x3f6dbf6d,0x3f803f80,0x3f6dbf6d,
0x3f3e3f71,0x3f71bf80,0xbf3ebf71,0xbf713f80,0x3d493edb,0x3edbbf3e,0xbd49bedb,0xbedb3f3e,0xbf2cbeac,0xbeacbd49,0x3f2c3eac,0x3eac3d49,0xbf80bf67,0xbf673f2c,0x3f803f67,0x3f67bf2c,
0x3dc93f46,0x3ef1bf75,0x3dc93f46,0x3ef1bf75,0xbf7fbf22,0xbf623e95,0xbf7fbf22,0xbf623e95,0xbdc9bf46,0xbef13f75,0xbdc9bf46,0xbef13f75,0x3f7f3f22,0x3f62be95,0x3f7f3f22,0x3f62be95,
0xbf183f04,0xbe79bf4e,0x3f18bf04,0x3e793f4e,0xbe16bf78,0xbf043f7d,0x3e163f78,0x3f04bf7d,0x3f4e3f5c,0x3f78bf18,0xbf4ebf5c,0xbf783f18,0xbf7dbe79,0xbf5cbe16,0x3f7d3e79,0x3f5c3e16,
0xbf7b3e48,0xbf55bf0e,0xbf7b3e48,0xbf55bf0e,0x3f7bbe48,0x3f553f0e,0x3f7bbe48,0x3f553f0e,0xbf7b3e48,0xbf55bf0e,0xbf7b3e48,0xbf55bf0e,0x3f7bbe48,0x3f553f0e,0x3f7bbe48,0x3f553f0e,
0xbf5cbe16,0xbf7dbe79,0x3f5c3e16,0x3f7d3e79,0x3e793f4e,0x3f18bf04,0xbe79bf4e,0xbf183f04,0x3f04bf7d,0x3e163f78,0xbf043f7d,0xbe16bf78,0xbf783f18,0xbf4ebf5c,0x3f78bf18,0x3f4e3f5c,
0xbe95bef1,0xbf223dc9,0xbe95bef1,0xbf223dc9,0xbf753f62,0xbf46bf7f,0xbf753f62,0xbf46bf7f,0x3e953ef1,0x3f22bdc9,0x3e953ef1,0x3f22bdc9,0x3f75bf62,0x3f463f7f,0x3f75bf62,0x3f463f7f,
0x3edbbf3e,0x3d493edb,0xbedb3f3e,0xbd49bedb,0xbeacbd49,0xbf2cbeac,0x3eac3d49,0x3f2c3eac,0xbf673f2c,0xbf80bf67,0x3f67bf2c,0x3f803f67,0xbf713f80,0xbf3ebf71,0x3f71bf80,0x3f3e3f71,
0,0xbec43ec4,0,0xbec43ec4,0,0xbec43ec4,0,0xbec43ec4,0,0xbec43ec4,0,0xbec43ec4,0,0xbec43ec4,0,0xbec43ec4,
0x3f2c3eac,0x3eac3d49,0xbf2cbeac,0xbeacbd49,0x3f803f67,0x3f67bf2c,0xbf80bf67,0xbf673f2c,0x3f3e3f71,0x3f71bf80,0xbf3ebf71,0xbf713f80,0x3d493edb,0x3edbbf3e,0xbd49bedb,0xbedb3f3e,
0x3f7f3f22,0x3f62be95,0x3f7f3f22,0x3f62be95,0x3dc93f46,0x3ef1bf75,0x3dc93f46,0x3ef1bf75,0xbf7fbf22,0xbf623e95,0xbf7fbf22,0xbf623e95,0xbdc9bf46,0xbef13f75,0xbdc9bf46,0xbef13f75,
0x3f4e3f5c,0x3f78bf18,0xbf4ebf5c,0xbf783f18,0xbf7dbe79,0xbf5cbe16,0x3f7d3e79,0x3f5c3e16,0x3f18bf04,0x3e793f4e,0xbf183f04,0xbe79bf4e,0x3e163f78,0x3f04bf7d,0xbe16bf78,0xbf043f7d,
0x3e483f7b,0x3f0ebf55,0x3e483f7b,0x3f0ebf55,0xbe48bf7b,0xbf0e3f55,0xbe48bf7b,0xbf0e3f55,0x3e483f7b,0x3f0ebf55,0x3e483f7b,0x3f0ebf55,0xbe48bf7b,0xbf0e3f55,0xbe48bf7b,0xbf0e3f55,
0xbf043f7d,0xbe16bf78,0x3f04bf7d,0x3e163f78,0x3f78bf18,0x3f4e3f5c,0xbf783f18,0xbf4ebf5c,0xbf5cbe16,0xbf7dbe79,0x3f5c3e16,0x3f7d3e79,0x3e793f4e,0x3f18bf04,0xbe79bf4e,0xbf183f04,
0xbf753f62,0xbf46bf7f,0xbf753f62,0xbf46bf7f,0x3e953ef1,0x3f22bdc9,0x3e953ef1,0x3f22bdc9,0x3f75bf62,0x3f463f7f,0x3f75bf62,0x3f463f7f,0xbe95bef1,0xbf223dc9,0xbe95bef1,0xbf223dc9,
0xbf673f2c,0xbf80bf67,0x3f67bf2c,0x3f803f67,0xbf713f80,0xbf3ebf71,0x3f71bf80,0x3f3e3f71,0xbedb3f3e,0xbd49bedb,0x3edbbf3e,0x3d493edb,0x3eac3d49,0x3f2c3eac,0xbeacbd49,0xbf2cbeac,
0,0x3ec4bec4,0,0x3ec4bec4,0,0x3ec4bec4,0,0x3ec4bec4,0,0x3ec4bec4,0,0x3ec4bec4,0,0x3ec4bec4,0,0x3ec4bec4,
0xbf2cbeac,0xbeacbd49,0x3f2c3eac,0x3eac3d49,0xbf80bf67,0xbf673f2c,0x3f803f67,0x3f67bf2c,0xbf3ebf71,0xbf713f80,0x3f3e3f71,0x3f71bf80,0xbd49bedb,0xbedb3f3e,0x3d493edb,0x3edbbf3e,
0xbf7fbf22,0xbf623e95,0xbf7fbf22,0xbf623e95,0xbdc9bf46,0xbef13f75,0xbdc9bf46,0xbef13f75,0x3f7f3f22,0x3f62be95,0x3f7f3f22,0x3f62be95,0x3dc93f46,0x3ef1bf75,0x3dc93f46,0x3ef1bf75,
0xbf4ebf5c,0xbf783f18,0x3f4e3f5c,0x3f78bf18,0x3f7d3e79,0x3f5c3e16,0xbf7dbe79,0xbf5cbe16,0xbf183f04,0xbe79bf4e,0x3f18bf04,0x3e793f4e,0xbe16bf78,0xbf043f7d,0x3e163f78,0x3f04bf7d,
0xbe48bf7b,0xbf0e3f55,0xbe48bf7b,0xbf0e3f55,0x3e483f7b,0x3f0ebf55,0x3e483f7b,0x3f0ebf55,0xbe48bf7b,0xbf0e3f55,0xbe48bf7b,0xbf0e3f55,0x3e483f7b,0x3f0ebf55,0x3e483f7b,0x3f0ebf55,
0x3f04bf7d,0x3e163f78,0xbf043f7d,0xbe16bf78,0xbf783f18,0xbf4ebf5c,0x3f78bf18,0x3f4e3f5c,0x3f5c3e16,0x3f7d3e79,0xbf5cbe16,0xbf7dbe79,0xbe79bf4e,0xbf183f04,0x3e793f4e,0x3f18bf04,
0x3f75bf62,0x3f463f7f,0x3f75bf62,0x3f463f7f,0xbe95bef1,0xbf223dc9,0xbe95bef1,0xbf223dc9,0xbf753f62,0xbf46bf7f,0xbf753f62,0xbf46bf7f,0x3e953ef1,0x3f22bdc9,0x3e953ef1,0x3f22bdc9,
0x3f67bf2c,0x3f803f67,0xbf673f2c,0xbf80bf67,0x3f71bf80,0x3f3e3f71,0xbf713f80,0xbf3ebf71,0x3edbbf3e,0x3d493edb,0xbedb3f3e,0xbd49bedb,0xbeacbd49,0xbf2cbeac,0x3eac3d49,0x3f2c3eac,
0x3f800000,0x3f7fc38f,0x3f800000,0x3f6816a8,0x3f7f0e58,0x3f7de0b1,0x3f24d225,0x3e8586ce,0x3f7c3b28,0x3f7a1e84,0xbe2f10a2,0xbf121eb0,0x3f778bc5,0x3f748422,0xbf5d2d53,0xbf7eea9d,
0x3f800000,0x3f7eea9d,0x3f800000,0x3f628210,0x3f7baccd,0x3f764d97,0x3f10d3cd,0x3dee3876,0x3f6ed89e,0x3f655e0b,0xbeb8442a,0xbf40d0da,0x3f59f26a,0x3f4cae79,0xbf791298,0xbf77f110,
0x3f800000,0x3f7d7474,0x3f800000,0x3f5c61c7,0x3f75dec6,0x3f696591,0x3ef6e0cb,0xbcfb49ba,0x3f584853,0x3f42de29,0xbf08f59b,0xbf63f473,0x3f299415,0x3f0cead0,0xbf7f84ab,0xbf53fac3,
0x3f800000,0x3f7b61fc,0x3f800000,0x3f55b993,0x3f6db293,0x3f577026,0x3ec9b953,0xbe354098,0x3f396842,0x3f14b039,0xbf3085bb,0xbf796e4e,0x3ed53641,0x3e72b651,0xbf6ff573,0xbf173c07,
0x3f800000,0x3f78b47b,0x3f800000,0x3f4e8d90,0x3f633c5a,0x3f40d0da,0x3e9aa086,0xbea395c5,0x3f13682a,0x3ebb31a0,0xbf514d3d,0xbf7ff4e6,0x3e09cf86,0xbdd53db9,0xbf4bbbf8,0xbe919ddd,
0x3f800000,0x3f756d97,0x3f800000,0x3f46e22a,0x3f5695e5,0x3f26050a,0x3e541501,0xbee900b7,0x3ecf7bca,0x3e039502,0xbf6a09a7,0xbf772417,0xbe22abb6,0xbeddbe79,0xbf15f6d9,0x3d621469,
0x3f800000,0x3f718f57,0x3f800000,0x3f3ebc1b,0x3f47de65,0x3f07a136,0x3de1bc2e,0xbf14b039,0x3e605c13,0xbdee3876,0xbf79c79d,0xbf5f8327,0xbee0924f,0xbf36206c,0xbea68f12,0x3ec6d529,
0x3f800000,0x3f6d1c1d,0x3f800000,0x3f36206c,0x3f373a23,0x3ecc9b8b,0x3c490e90,0xbf31a81d,0x3cc90ab0,0xbeb554ec,0xbf7fec43,0xbf3a7ca4,0xbf2e3bde,0xbf6816a8,0xbd16c32c,0x3f2d1469,
0,0x3d2fe007,0,0x3ed8106b,0x3dafb680,0x3e039502,0x3f43e200,0x3f772417,0x3e2f10a2,0x3e5a3997,0x3f7c3b28,0x3f5233c6,0x3e827dc0,0x3e97a117,0x3f00e7e4,0x3dbc3ac3,
0,0x3dbc3ac3,0,0x3eee9479,0x3e3b6ecf,0x3e8b9507,0x3f531849,0x3f7e4323,0x3eb8442a,0x3ee363fa,0x3f6ed89e,0x3f286605,0x3f064b82,0x3f19c200,0x3e6c9a7f,0xbe7ee6e1,
0,0x3e1008b7,0,0x3f0242b1,0x3e8e9a22,0x3ed25a09,0x3f604621,0x3f7fe129,0x3f08f59b,0x3f26050a,0x3f584853,0x3ee900b7,0x3f3fc767,0x3f55b993,0xbd7b2b74,0xbf0f8784,
0,0x3e419b37,0,0x3f0cead0,0x3ebe1d4a,0x3f0a48ad,0x3f6b4b0c,0x3f7bf531,0x3f3085bb,0x3f5064af,0x3f396842,0x3e667c66,0x3f68bf3c,0x3f78b47b,0xbeb263ef,0xbf4e8d90,
0,0x3e72b651,0,0x3f173c07,0x3eebcbbb,0x3f286605,0x3f740bdd,0x3f7294f8,0x3f514d3d,0x3f6e46be,0x3f13682a,0xbc96c9b6,0x3f7dabcc,0x3f7e9bc9,0xbf1b02c6,0xbf756d97,
0,0x3e919ddd,0,0x3f212ff9,0x3f0b9a6b,0x3f42de29,0x3f7a7302,0x3f63f473,0x3f6a09a7,0x3f7de0b1,0x3ecf7bca,0xbe8586ce,0x3f7cbfc9,0x3f66becc,0xbf4f7a1f,0xbf7f9c18,
0,0x3ea986c4,0,0x3f2ac082,0x3f1ff6cb,0x3f591e6a,0x3f7e70b0,0x3f5064af,0x3f79c79d,0x3f7e4323,0x3e605c13,0xbef9a02d,0x3f660f88,0x3f33e7bc,0xbf721352,0xbf6be858,
0,0x3ec1071e,0,0x3f33e7bc,0x3f32c8c9,0x3f6aab7b,0x3f7ffb11,0x3f385216,0x3f7fec43,0x3f6f6830,0x3cc90ab0,0xbf2f61a5,0x3f3b8f3b,0x3ed8106b,0xbf7fd397,0xbf3ca003,
0x35cccccd,0x35cccccd,0x35cccccd,0x35cccccd,0x35cccccd,0x35cccccd,0x35cccccd,0x35cccccd,0x35cccccd,0x35cccccd,0x35cccccd,0x35cccccd,0x35cccccd,0x35cccccd,0x35cccccd,0x35cccccd,
0x35cc9c72,0x35cbeee4,0x35b9abba,0x35b534da,0x35cac390,0x35c91b30,0x35b04e38,0x35aafadc,0x35c6f6c8,0x35c457ac,0x35a53e0d,0x359f1b54,0x35c13f79,0x35bdb017,0x3598967c,0x3591b389,
0x35cc0b7a,0x35c9570a,0x3583db51,0x3567b948,0x35c4b238,0x35be2876,0x354580a2,0x3521610f,0x35b5c9e1,0x35abab1e,0x34f7673d,0x34a9aa67,0x359fe51e,0x359294e9,0x3434968b,0x32a0d873,
0x35cb1a27,0x35c50adf,0x34d5a47e,0x343e9392,0x35bab7a7,0x35ac59b8,0xb34907c8,0xb491007a,0x359a40ae,0x3584d0d5,0xb502de37,0xb53a66f9,0x355901f0,0x3523afa2,0xb56de6c2,0xb58e2017,
0x35c9c8ed,0x35bf13b1,0xb48c0d4f,0xb51369bb,0x35ad06a9,0x35945368,0xb55b2291,0xb58d37c9,0x356bd9dd,0x3525fca2,0xb5a770fe,0xb5bb3aec,0x34b37cdc,0x3320d559,0xb5c7d2e4,0xb5ccbd02,
0x35c8186a,0x35b77e6f,0xb569cab3,0xb59a40ae,0x359be4ed,0x356de6c2,0xb5b65d28,0xb5c78b72,0x3515c14d,0x34528804,0xb5ccc3eb,0xb5c5b679,0xb43e9392,0xb51110bd,0xb5b2cf52,0xb5953084,
0x35c6096a,0x35ae5b88,0xb5b0f10f,0xb5c74213,0x3587a9aa,0x352a91ce,0xb5cc6a23,0xb5bff78f,0x345c7f3e,0xb48222f8,0xb5a2fcc6,0xb56ff15b,0xb533a83f,0xb58b6318,0xb5053f42,0xb3713846,
0x35c39ce8,0x35a3bec8,0xb5cbeee4,0xb5c65a74,0x356177b4,0x34c22b74,0xb5a99568,0xb571f9a5,0xb42a97c7,0xb531652e,0xb4e8fc95,0x33b4dd20,0xb591b389,0xb5b9abba,0x351f10ee,0x358a76bb,
0,0,0,0,0,0,0,0,0,0,0,0,0,0,0,0,
0x338cb338,0x34169569,0x352cd9f0,0x353edd2d,0x34667457,0x349ae293,0x35506ab5,0x356177b4,0x34c22b74,0x34e8fc95,0x3571f9a5,0x3580f32d,0x35079f03,0x351a6c18,0x35889a01,0x358fec97,
0x340c9200,0x3495f23f,0x359cb4cd,0x35a8e03a,0x34e429d0,0x3518176e,0x35b36b4e,0x35bc3c09,0x353ca2fc,0x355f5d78,0x35c33cb1,0x35c85c01,0x357ff144,0x358f0707,0x35cb8d5a,0x35ccc8da,
0x34528804,0x34df54d8,0x35c5b679,0x35cb68e9,0x35284807,0x355d4116,0x35ccb421,0x35c990f4,0x3586b804,0x359be4ed,0x35c210c7,0x35b65d28,0x35adb1ef,0x35bbbc62,0x35a6b6f3,0x359374de,
0x348c0d4f,0x351369bb,0x35c9c8ed,0x35bf13b1,0x355b2291,0x358d37c9,0x35ad06a9,0x35945368,0x35a770fe,0x35bb3aec,0x356bd9dd,0x3525fca2,0x35c7d2e4,0x35ccbd02,0x34b37cdc,0x3320d559,
0x34ae9479,0x3535e995,0x35a8296b,0x3586b804,0x3584d0d5,0x35a6b6f3,0x353a66f9,0x34b86384,0x35be9eff,0x35cb1a27,0xb2f142bd,0xb4d5a47e,0x35cb68e9,0x35bf868d,0xb547b357,0xb58c4e1d,
0x34d0c934,0x3556df37,0x354e3fd4,0x34bd4866,0x35996c52,0x35ba3296,0xb3c8ef90,0xb50eb659,0x35caefd6,0x35ca3307,0xb578046f,0xb5a5fb4c,0x35b80c6c,0x35960c2f,0xb5c1a90f,0xb5cca946,
0x34f29b58,0x35760334,0x34169569,0xb4cbebe7,0x35aafadc,0x35c6f6c8,0xb565a5a1,0xb5a53e0d,0x35cbafd4,0x35b898a3,0xb5c457ac,0xb5cc7ce0,0x358fec97,0x352cd9f0,0xb5bcb9e0,0xb596e669,
0x3f803f80,0,0,0x3f803f80,0x3f803f80,0,0,0x3f803f80,0x3f803f80,0,0,0x3f803f80,0x3f803f80,0,0,0x3f803f80,
0x3f353f80,0x3f350000,0xbf350000,0x3f353f80,0xbf350000,0x3f353f80,0xbf35bf80,0xbf350000,0xbf35bf80,0xbf350000,0x3f350000,0xbf35bf80,0x3f350000,0xbf35bf80,0x3f353f80,0x3f350000,
0x3f80,0x3f800000,0xbf800000,0x3f80,0xbf80,0xbf800000,0x3f800000,0xbf80,0x3f80,0x3f800000,0xbf800000,0x3f80,0xbf80,0xbf800000,0x3f800000,0xbf80,
0xbf353f80,0x3f350000,0xbf350000,0xbf353f80,0x3f350000,0x3f35bf80,0xbf353f80,0x3f350000,0x3f35bf80,0xbf350000,0x3f350000,0x3f35bf80,0xbf350000,0xbf353f80,0x3f35bf80,0xbf350000,
0xbf803f80,0,0,0xbf803f80,0xbf803f80,0,0,0xbf803f80,0xbf803f80,0,0,0xbf803f80,0xbf803f80,0,0,0xbf803f80,
0xbf353f80,0xbf350000,0x3f350000,0xbf353f80,0x3f350000,0xbf353f80,0x3f35bf80,0x3f350000,0x3f35bf80,0x3f350000,0xbf350000,0x3f35bf80,0xbf350000,0x3f35bf80,0xbf353f80,0xbf350000,
0x3f80,0xbf800000,0x3f800000,0x3f80,0xbf80,0x3f800000,0xbf800000,0xbf80,0x3f80,0xbf800000,0x3f800000,0x3f80,0xbf80,0x3f800000,0xbf800000,0xbf80,
0x3f353f80,0xbf350000,0x3f350000,0x3f353f80,0xbf350000,0xbf35bf80,0x3f353f80,0xbf350000,0xbf35bf80,0x3f350000,0xbf350000,0xbf35bf80,0x3f350000,0x3f353f80,0xbf35bf80,0x3f350000,
0x3f80,0x3f80,0x3f7f3dc9,0x3f7f3dc9,0x3eb83f6f,0xbeb8bf6f,0x3f77be89,0xbf773e89,0x3f2c3f3e,0x3f2c3f3e,0x3f4ebf18,0x3f4ebf18,0x3f653ee6,0xbf65bee6,0x3f09bf58,0xbf093f58,
0x3f80,0x3f80,0x3dc9bf7f,0x3dc9bf7f,0x3f313f39,0xbf31bf39,0xbf1dbf4a,0x3f1d3f4a,0x3f803d49,0x3f803d49,0xbf7dbe16,0xbf7dbe16,0x3f42bf27,0xbf423f27,0xbf513f13,0x3f51bf13,
0x3f80,0x3f80,0xbf7fbdc9,0xbf7fbdc9,0x3f6a3ecf,0xbf6abecf,0xbefc3f5f,0x3efcbf5f,0x3f3ebf2c,0x3f3ebf2c,0x3f183f4e,0x3f183f4e,0xbea1bf73,0x3ea13f73,0x3f7abe60,0xbf7a3e60,
0x3f80,0x3f80,0xbdc93f7f,0xbdc93f7f,0x3f803cc9,0xbf80bcc9,0x3f7e3dfb,0xbf7ebdfb,0x3d49bf80,0x3d49bf80,0x3e16bf7d,0x3e16bf7d,0xbf7fbd97,0x3f7f3d97,0xbf7cbe2f,0x3f7c3e2f,
0x3f80,0x3f80,0x3f7f3dc9,0x3f7f3dc9,0x3f6fbeb8,0xbf6f3eb8,0xbe89bf77,0x3e893f77,0xbf2cbf3e,0xbf2cbf3e,0xbf4e3f18,0xbf4e3f18,0xbee63f65,0x3ee6bf65,0x3f583f09,0xbf58bf09,
0x3f80,0x3f80,0x3dc9bf7f,0x3dc9bf7f,0x3f39bf31,0xbf393f31,0xbf4a3f1d,0x3f4abf1d,0xbf80bd49,0xbf80bd49,0x3f7d3e16,0x3f7d3e16,0x3f273f42,0xbf27bf42,0xbf13bf51,0x3f133f51,
0x3f80,0x3f80,0xbf7fbdc9,0xbf7fbdc9,0x3ecfbf6a,0xbecf3f6a,0x3f5f3efc,0xbf5fbefc,0xbf3e3f2c,0xbf3e3f2c,0xbf18bf4e,0xbf18bf4e,0x3f73bea1,0xbf733ea1,0x3e603f7a,0xbe60bf7a,
0x3f80,0x3f80,0xbdc93f7f,0xbdc93f7f,0x3cc9bf80,0xbcc93f80,0x3dfbbf7e,0xbdfb3f7e,0xbd493f80,0xbd493f80,0xbe163f7d,0xbe163f7d,0x3d97bf7f,0xbd973f7f,0x3e2fbf7c,0xbe2f3f7c,
0x3e48bf7b,0x3e48bf7b,0xbf75be95,0xbf75be95,0xbe2fbf7c,0x3e2f3f7c,0xbf7f3d97,0x3f7fbd97,0xbf04bf5c,0xbf04bf5c,0xbf673edb,0xbf673edb,0xbf4abf1d,0x3f4a3f1d,0xbf313f39,0x3f31bf39,
0xbe483f7b,0xbe483f7b,0x3e95bf75,0x3e95bf75,0x3f093f58,0xbf09bf58,0xbee6bf65,0x3ee63f65,0x3f783e79,0x3f783e79,0xbf71beac,0xbf71beac,0x3f5fbefc,0xbf5f3efc,0xbf6a3ecf,0x3f6abecf,
0x3e48bf7b,0x3e48bf7b,0x3f753e95,0x3f753e95,0xbf51bf13,0x3f513f13,0x3f27bf42,0xbf273f42,0xbf5c3f04,0xbf5c3f04,0xbedbbf67,0xbedbbf67,0x3dfb3f7e,0xbdfbbf7e,0xbf803cc9,0x3f80bcc9,
0xbe483f7b,0xbe483f7b,0xbe953f75,0xbe953f75,0x3f7a3e60,0xbf7abe60,0x3f733ea1,0xbf73bea1,0x3e79bf78,0x3e79bf78,0x3eacbf71,0x3eacbf71,0xbf77be89,0x3f773e89,0xbf6fbeb8,0x3f6f3eb8,
0x3e48bf7b,0x3e48bf7b,0xbf75be95,0xbf75be95,0xbf7c3e2f,0x3f7cbe2f,0x3d973f7f,0xbd97bf7f,0x3f043f5c,0x3f043f5c,0x3f67bedb,0x3f67bedb,0x3f1dbf4a,0xbf1d3f4a,0xbf39bf31,0x3f393f31,
0xbe483f7b,0xbe483f7b,0x3e95bf75,0x3e95bf75,0x3f58bf09,0xbf583f09,0xbf653ee6,0x3f65bee6,0xbf78be79,0xbf78be79,0x3f713eac,0x3f713eac,0x3efc3f5f,0xbefcbf5f,0xbecfbf6a,0x3ecf3f6a,
0x3e48bf7b,0x3e48bf7b,0x3f753e95,0x3f753e95,0xbf133f51,0x3f13bf51,0xbf42bf27,0x3f423f27,0x3f5cbf04,0x3f5cbf04,0x3edb3f67,0x3edb3f67,0xbf7e3dfb,0x3f7ebdfb,0xbcc9bf80,0x3cc93f80,
0xbe483f7b,0xbe483f7b,0xbe953f75,0xbe953f75,0x3e60bf7a,0xbe603f7a,0x3ea1bf73,0xbea13f73,0xbe793f78,0xbe793f78,0xbeac3f71,0xbeac3f71,0x3e89bf77,0xbe893f77,0x3eb8bf6f,0xbeb83f6f,
0x3f800000,0x3f800000,0x3dc9bf7f,0x3dc9bf7f,0x3f6fbeb8,0xbf6f3eb8,0xbe89bf77,0x3e893f77,0x3f3ebf2c,0x3f3ebf2c,0xbf18bf4e,0xbf18bf4e,0x3ee6bf65,0xbee63f65,0xbf58bf09,0x3f583f09,
0x3f800000,0x3f800000,0xbf7fbdc9,0xbf7fbdc9,0x3f39bf31,0xbf393f31,0xbf4a3f1d,0x3f4abf1d,0x3d49bf80,0x3d49bf80,0xbe163f7d,0xbe163f7d,0xbf27bf42,0x3f273f42,0x3f133f51,0xbf13bf51,
0x3f800000,0x3f800000,0xbdc93f7f,0xbdc93f7f,0x3ecfbf6a,0xbecf3f6a,0x3f5f3efc,0xbf5fbefc,0xbf2cbf3e,0xbf2cbf3e,0x3f4ebf18,0x3f4ebf18,0xbf733ea1,0x3f73bea1,0xbe60bf7a,0x3e603f7a,
0x3f800000,0x3f800000,0x3f7f3dc9,0x3f7f3dc9,0x3cc9bf80,0xbcc93f80,0x3dfbbf7e,0xbdfb3f7e,0xbf80bd49,0xbf80bd49,0xbf7dbe16,0xbf7dbe16,0xbd973f7f,0x3d97bf7f,0xbe2f3f7c,0x3e2fbf7c,
0x3f800000,0x3f800000,0x3dc9bf7f,0x3dc9bf7f,0xbeb8bf6f,0x3eb83f6f,0xbf773e89,0x3f77be89,0xbf3e3f2c,0xbf3e3f2c,0x3f183f4e,0x3f183f4e,0x3f653ee6,0xbf65bee6,0x3f09bf58,0xbf093f58,
0x3f800000,0x3f800000,0xbf7fbdc9,0xbf7fbdc9,0xbf31bf39,0x3f313f39,0x3f1d3f4a,0xbf1dbf4a,0xbd493f80,0xbd493f80,0x3e16bf7d,0x3e16bf7d,0x3f42bf27,0xbf423f27,0xbf513f13,0x3f51bf13,
0x3f800000,0x3f800000,0xbdc93f7f,0xbdc93f7f,0xbf6abecf,0x3f6a3ecf,0x3efcbf5f,0xbefc3f5f,0x3f2c3f3e,0x3f2c3f3e,0xbf4e3f18,0xbf4e3f18,0xbea1bf73,0x3ea13f73,0x3f7abe60,0xbf7a3e60,
0x3f800000,0x3f800000,0x3f7f3dc9,0x3f7f3dc9,0xbf80bcc9,0x3f803cc9,0xbf7ebdfb,0x3f7e3dfb,0x3f803d49,0x3f803d49,0x3f7d3e16,0x3f7d3e16,0xbf7fbd97,0x3f7f3d97,0xbf7cbe2f,0x3f7c3e2f,
0xbf7bbe48,0xbf7bbe48,0xbe953f75,0xbe953f75,0xbf7c3e2f,0x3f7cbe2f,0x3d973f7f,0xbd97bf7f,0xbf5c3f04,0xbf5c3f04,0x3edb3f67,0x3edb3f67,0xbf1d3f4a,0x3f1dbf4a,0x3f393f31,0xbf39bf31,
0x3f7b3e48,0x3f7b3e48,0xbf75be95,0xbf75be95,0x3f58bf09,0xbf583f09,0xbf653ee6,0x3f65bee6,0x3e79bf78,0x3e79bf78,0xbeac3f71,0xbeac3f71,0xbefcbf5f,0x3efc3f5f,0x3ecf3f6a,0xbecfbf6a,
0xbf7bbe48,0xbf7bbe48,0x3e95bf75,0x3e95bf75,0xbf133f51,0x3f13bf51,0xbf42bf27,0x3f423f27,0x3f043f5c,0x3f043f5c,0xbf673edb,0xbf673edb,0x3f7ebdfb,0xbf7e3dfb,0x3cc93f80,0xbcc9bf80,
0x3f7b3e48,0x3f7b3e48,0x3f753e95,0x3f753e95,0x3e60bf7a,0xbe603f7a,0x3ea1bf73,0xbea13f73,0xbf78be79,0xbf78be79,0xbf71beac,0xbf71beac,0xbe893f77,0x3e89bf77,0xbeb83f6f,0x3eb8bf6f,
0xbf7bbe48,0xbf7bbe48,0xbe953f75,0xbe953f75,0x3e2f3f7c,0xbe2fbf7c,0x3f7fbd97,0xbf7f3d97,0x3f5cbf04,0x3f5cbf04,0xbedbbf67,0xbedbbf67,0xbf4abf1d,0x3f4a3f1d,0xbf313f39,0x3f31bf39,
0x3f7b3e48,0x3f7b3e48,0xbf75be95,0xbf75be95,0xbf09bf58,0x3f093f58,0x3ee63f65,0xbee6bf65,0xbe793f78,0xbe793f78,0x3eacbf71,0x3eacbf71,0x3f5fbefc,0xbf5f3efc,0xbf6a3ecf,0x3f6abecf,
0xbf7bbe48,0xbf7bbe48,0x3e95bf75,0x3e95bf75,0x3f513f13,0xbf51bf13,0xbf273f42,0x3f27bf42,0xbf04bf5c,0xbf04bf5c,0x3f67bedb,0x3f67bedb,0x3dfb3f7e,0xbdfbbf7e,0xbf803cc9,0x3f80bcc9,
0x3f7b3e48,0x3f7b3e48,0x3f753e95,0x3f753e95,0xbf7abe60,0x3f7a3e60,0xbf73bea1,0x3f733ea1,0x3f783e79,0x3f783e79,0x3f713eac,0x3f713eac,0xbf77be89,0x3f773e89,0xbf6fbeb8,0x3f6f3eb8,
0x3f803f80,0x3f7bbf7b,0x3f803f80,0x3f7bbf7b,0x3f803f80,0x3f7bbf7b,0x3f803f80,0x3f7bbf7b,0x3f803f80,0x3f7bbf7b,0x3f803f80,0x3f7bbf7b,0x3f803f80,0x3f7bbf7b,0x3f803f80,0x3f7bbf7b,
0x3f393f6f,0x3f58bf7c,0xbf39bf6f,0xbf583f7c,0x3cc93ecf,0x3e60bf13,0xbcc9becf,0xbe603f13,0xbf31beb8,0xbf093e2f,0x3f313eb8,0x3f09be2f,0xbf80bf6a,0xbf7a3f51,0x3f803f6a,0x3f7abf51,
0x3d493f3e,0x3e79bf5c,0x3d493f3e,0x3e79bf5c,0xbf80bf2c,0xbf783f04,0xbf80bf2c,0xbf783f04,0xbd49bf3e,0xbe793f5c,0xbd49bf3e,0xbe793f5c,0x3f803f2c,0x3f78bf04,0x3f803f2c,0x3f78bf04,
0xbf273ee6,0xbefcbf1d,0x3f27bee6,0x3efc3f1d,0xbd97bf73,0xbe893f7e,0x3d973f73,0x3e89bf7e,0x3f423f65,0x3f5fbf4a,0xbf42bf65,0xbf5f3f4a,0xbf7fbea1,0xbf773dfb,0x3f7f3ea1,0x3f77bdfb,
0xbf7f3dc9,0xbf75be95,0xbf7f3dc9,0xbf75be95,0x3f7fbdc9,0x3f753e95,0x3f7fbdc9,0x3f753e95,0xbf7f3dc9,0xbf75be95,0xbf7f3dc9,0xbf75be95,0x3f7fbdc9,0x3f753e95,0x3f7fbdc9,0x3f753e95,
0xbf4abe89,0xbf653d97,0x3f4a3e89,0x3f65bd97,0x3dfb3f5f,0x3ea1bf42,0xbdfbbf5f,0xbea13f42,0x3f1dbf77,0x3ee63f7f,0xbf1d3f77,0xbee6bf7f,0xbf7e3efc,0xbf73bf27,0x3f7ebefc,0x3f733f27,
0xbe16bf18,0xbeac3edb,0xbe16bf18,0xbeac3edb,0xbf7d3f4e,0xbf71bf67,0xbf7d3f4e,0xbf71bf67,0x3e163f18,0x3eacbedb,0x3e163f18,0x3eacbedb,0x3f7dbf4e,0x3f713f67,0x3f7dbf4e,0x3f713f67,
0x3f13bf58,0x3ecf3f39,0xbf133f58,0xbecfbf39,0xbe2fbe60,0xbeb83cc9,0x3e2f3e60,0x3eb8bcc9,0xbf513f09,0xbf6abf31,0x3f51bf09,0x3f6a3f31,0xbf7c3f7a,0xbf6fbf80,0x3f7cbf7a,0x3f6f3f80,
0,0xbe483e48,0,0xbe483e48,0,0xbe483e48,0,0xbe483e48,0,0xbe483e48,0,0xbe483e48,0,0xbe483e48,0,0xbe483e48,
0x3f313eb8,0x3f09be2f,0xbf31beb8,0xbf093e2f,0x3f803f6a,0x3f7abf51,0xbf80bf6a,0xbf7a3f51,0x3f393f6f,0x3f58bf7c,0xbf39bf6f,0xbf583f7c,0x3cc93ecf,0x3e60bf13,0xbcc9becf,0xbe603f13,
0x3f803f2c,0x3f78bf04,0x3f803f2c,0x3f78bf04,0x3d493f3e,0x3e79bf5c,0x3d493f3e,0x3e79bf5c,0xbf80bf2c,0xbf783f04,0xbf80bf2c,0xbf783f04,0xbd49bf3e,0xbe793f5c,0xbd49bf3e,0xbe793f5c,
0x3f423f65,0x3f5fbf4a,0xbf42bf65,0xbf5f3f4a,0xbf7fbea1,0xbf773dfb,0x3f7f3ea1,0x3f77bdfb,0x3f27bee6,0x3efc3f1d,0xbf273ee6,0xbefcbf1d,0x3d973f73,0x3e89bf7e,0xbd97bf73,0xbe893f7e,
0x3dc93f7f,0x3e95bf75,0x3dc93f7f,0x3e95bf75,0xbdc9bf7f,0xbe953f75,0xbdc9bf7f,0xbe953f75,0x3dc93f7f,0x3e95bf75,0x3dc93f7f,0x3e95bf75,0xbdc9bf7f,0xbe953f75,0xbdc9bf7f,0xbe953f75,
0xbf1d3f77,0xbee6bf7f,0x3f1dbf77,0x3ee63f7f,0x3f7ebefc,0x3f733f27,0xbf7e3efc,0xbf73bf27,0xbf4abe89,0xbf653d97,0x3f4a3e89,0x3f65bd97,0x3dfb3f5f,0x3ea1bf42,0xbdfbbf5f,0xbea13f42,
0xbf7d3f4e,0xbf71bf67,0xbf7d3f4e,0xbf71bf67,0x3e163f18,0x3eacbedb,0x3e163f18,0x3eacbedb,0x3f7dbf4e,0x3f713f67,0x3f7dbf4e,0x3f713f67,0xbe16bf18,0xbeac3edb,0xbe16bf18,0xbeac3edb,
0xbf513f09,0xbf6abf31,0x3f51bf09,0x3f6a3f31,0xbf7c3f7a,0xbf6fbf80,0x3f7cbf7a,0x3f6f3f80,0xbf133f58,0xbecfbf39,0x3f13bf58,0x3ecf3f39,0x3e2f3e60,0x3eb8bcc9,0xbe2fbe60,0xbeb83cc9,
0,0x3e48be48,0,0x3e48be48,0,0x3e48be48,0,0x3e48be48,0,0x3e48be48,0,0x3e48be48,0,0x3e48be48,0,0x3e48be48,
0xbf31beb8,0xbf093e2f,0x3f313eb8,0x3f09be2f,0xbf80bf6a,0xbf7a3f51,0x3f803f6a,0x3f7abf51,0xbf39bf6f,0xbf583f7c,0x3f393f6f,0x3f58bf7c,0xbcc9becf,0xbe603f13,0x3cc93ecf,0x3e60bf13,
0xbf80bf2c,0xbf783f04,0xbf80bf2c,0xbf783f04,0xbd49bf3e,0xbe793f5c,0xbd49bf3e,0xbe793f5c,0x3f803f2c,0x3f78bf04,0x3f803f2c,0x3f78bf04,0x3d493f3e,0x3e79bf5c,0x3d493f3e,0x3e79bf5c,
0xbf42bf65,0xbf5f3f4a,0x3f423f65,0x3f5fbf4a,0x3f7f3ea1,0x3f77bdfb,0xbf7fbea1,0xbf773dfb,0xbf273ee6,0xbefcbf1d,0x3f27bee6,0x3efc3f1d,0xbd97bf73,0xbe893f7e,0x3d973f73,0x3e89bf7e,
0xbdc9bf7f,0xbe953f75,0xbdc9bf7f,0xbe953f75,0x3dc93f7f,0x3e95bf75,0x3dc93f7f,0x3e95bf75,0xbdc9bf7f,0xbe953f75,0xbdc9bf7f,0xbe953f75,0x3dc93f7f,0x3e95bf75,0x3dc93f7f,0x3e95bf75,
0x3f1dbf77,0x3ee63f7f,0xbf1d3f77,0xbee6bf7f,0xbf7e3efc,0xbf73bf27,0x3f7ebefc,0x3f733f27,0x3f4a3e89,0x3f65bd97,0xbf4abe89,0xbf653d97,0xbdfbbf5f,0xbea13f42,0x3dfb3f5f,0x3ea1bf42,
0x3f7dbf4e,0x3f713f67,0x3f7dbf4e,0x3f713f67,0xbe16bf18,0xbeac3edb,0xbe16bf18,0xbeac3edb,0xbf7d3f4e,0xbf71bf67,0xbf7d3f4e,0xbf71bf67,0x3e163f18,0x3eacbedb,0x3e163f18,0x3eacbedb,
0x3f51bf09,0x3f6a3f31,0xbf513f09,0xbf6abf31,0x3f7cbf7a,0x3f6f3f80,0xbf7c3f7a,0xbf6fbf80,0x3f13bf58,0x3ecf3f39,0xbf133f58,0xbecfbf39,0xbe2fbe60,0xbeb83cc9,0x3e2f3e60,0x3eb8bcc9,
0x3f800000,0x3f7fba9e,0x3f800000,0x3f67c187,0x3f7eea9d,0x3f7d906e,0x3f239da9,0x3e80f8c0,0x3f7baccd,0x3f7940c0,0xbe3b6ecf,0xbf1553b7,0x3f764d97,0x3f72d4eb,0xbf5f8327,0xbf7f5ce9,
0x3f800000,0x3f7ed7d4,0x3f800000,0x3f62241a,0x3f7b61fc,0x3f75a67b,0x3f0f8784,0x3ddb7d37,0x3f6db293,0x3f6398ac,0xbebe1d4a,0xbf436051,0x3f577026,0x3f495521,0xbf7a1e84,0xbf76841b,
0x3f800000,0x3f7d57de,0x3f800000,0x3f5bfb34,0x3f756d97,0x3f686b39,0x3ef41f07,0xbd2351cb,0x3f5695e5,0x3f404c5c,0xbf0b9a6b,0xbf65b710,0x3f26050a,0x3f084b92,0xbf7f2f9d,0xbf50d937,
0x3f800000,0x3f7b3bab,0x3f800000,0x3f554aa4,0x3f6d1c1d,0x3f5627fe,0x3ec6d529,0xbe3e853e,0x3f373a23,0x3f11796b,0xbf32c8c9,0xbf7a4910,0x3ecc9b8b,0x3e5d4b1a,0xbf6e46be,0xbf12c39a,
0x3f800000,0x3f788486,0x3f800000,0x3f4e1689,0x3f628210,0x3f3f41fc,0x3e97a117,0xbea80b1f,0x3f10d3cd,0x3eb3dca5,0xbf531849,0xbf7fdaaf,0x3dee3876,0xbe007745,0xbf48d8b3,0xbe870ada,
0x3f800000,0x3f75341d,0x3f800000,0x3f466354,0x3f55b993,0x3f24381a,0x3e4dee60,0xbeed3063,0x3ec9b953,0x3de7fa9a,0xbf6b4b0c,0xbf76167a,0xbe354098,0xbee79a5d,0xbf121eb0,0x3d9cecf9,
0x3f800000,0x3f714c7a,0x3f800000,0x3f3e35c5,0x3f46e22a,0x3f05a02c,0x3dd53db9,0xbf16999f,0x3e541501,0xbe06b26e,0xbf7a7302,0xbf5d924d,0xbee900b7,0xbf39f2ac,0xbe9d9e78,0x3ed0eb2a,
0x3f800000,0x3f6cd007,0x3f800000,0x3f3592e7,0x3f36206c,0x3ec8477c,0x3bc90f88,0xbf33587a,0x3c490e90,0xbebca7af,0xbf7ffb11,0xbf37c655,0xbf31a81d,0xbf6a5ad9,0xbc96c9b6,0x3f311722,
0,0x3d3c6dd5,0,0x3ed97cb9,0x3dbc3ac3,0x3e0cec4a,0x3f44e3f5,0x3f77beb7,0x3e3b6ecf,0x3e698bba,0x3f7baccd,0x3f4fefa8,0x3e8b9507,0x3ea21887,0x3ef9a02d,0x3d9064b4,
0,0x3dc27c39,0,0x3eeff7fb,0x3e419b37,0x3e901c2c,0x3f53fac3,0x3f7e868b,0x3ebe1d4a,0x3eea6681,0x3f6db293,0x3f256bcb,0x3f0a48ad,0x3f1e1e22,0x3e5a3997,0xbe8a11f7,
0,0x3e1324ca,0,0x3f02ef9f,0x3e919ddd,0x3ed6a399,0x3f6106f2,0x3f7fcbe2,0x3f0b9a6b,0x3f28fd41,0x3f5695e5,0x3ee1fb6a,0x3f42de29,0x3f58b3a1,0xbda3308c,0xbf140c5f,
0,0x3e44b0b9,0,0x3f0d9281,0x3ec1071e,0x3f0c42c9,0x3f6be858,0x3f7b87b2,0x3f32c8c9,0x3f52a649,0x3f373a23,0x3e57278f,0x3f6aab7b,0x3f79f35e,0xbebb31a0,0xbf51c0c2,
0,0x3e75c35a,0,0x3f17de12,0x3eee9479,0x3f2a2a80,0x3f748422,0x3f71d19f,0x3f531849,0x3f6faf1b,0x3f10d3cd,0xbd0a342f,0x3f7e4323,0x3f7dfa38,0xbf1ebc12,0xbf76ef5b,
0,0x3e931f35,0,0x3f21cbfb,0x3f0cead0,0x3f446337,0x3f7ac516,0x3f62df7b,0x3f6b4b0c,0x3f7e5a38,0x3ec9b953,0xbe8d17c0,0x3f7bf531,0x3f644fac,0xbf5233c6,0xbf7f3f54,
0,0x3eab0201,0,0x3f2b561b,0x3f212ff9,0x3f5a5ba0,0x3f7e9bc9,0x3f4f0417,0x3f7a7302,0x3f7dc68c,0x3e541501,0xbf003a06,0x3f63f473,0x3f2ff3e6,0xbf73913f,0xbf69b7e4,
0,0x3ec27b55,0,0x3f34768f,0x3f33e7bc,0x3f6b99fb,0x3f7ffec4,0x3f36ad7f,0x3f7ffb11,0x3f6dfcf2,0x3c490e90,0xbf3238aa,0x3f385216,0x3ece0bea,0xbf7ff4e6,0xbf38dd65,
0x35cccccd,0x35cccccd,0x35cccccd,0x35cccccd,0x35cccccd,0x35cccccd,0x35cccccd,0x35cccccd,0x35cccccd,0x35cccccd,0x35cccccd,0x35cccccd,0x35cccccd,0x35cccccd,0x35cccccd,0x35cccccd,
0x35cc954b,0x35cbdfdd,0x35b9679f,0x35b4e9ae,0x35caacb2,0x35c8fc89,0x35affc2a,0x35aaa21d,0x35c6d06b,0x35c429b0,0x35a4ded4,0x359eb5dd,0x35c109fb,0x35bd7339,0x35982b04,0x35914253,
0x35cbeee4,0x35c91b30,0x3582e487,0x3565a5a1,0x35c457ac,0x35bdb017,0x35434c06,0x351f10ee,0x35b534da,0x35aafadc,0x34f29b58,0x34a4beb3,0x359f1b54,0x3591b389,0x342a97c7,0x3220d93a,
0x35cad9f2,0x35c4852f,0x34ce5acd,0x342f9760,0x35b9ef61,0x35ab5332,0xb382a7d6,0xb4986a98,0x35990197,0x35836014,0xb5066f4c,0xb53dc04f,0x3555cd14,0x35203930,0xb570f5cb,0xb58f79fb,
0x35c9570a,0x35be2876,0xb495f23f,0xb518176e,0x35abab1e,0x359294e9,0xb55f5d78,0xb58f0707,0x3567b948,0x3521610f,0xb5a8e03a,0xb5bc3c09,0x34a9aa67,0x32a0d873,0xb5c85c01,0xb5ccc8da,
0x35c76700,0x35b613bd,0xb56eec58,0xb59c4d0e,0x3599d6b0,0x3568c245,0xb5b7c5a7,0xb5c83a73,0x350fe3b7,0x34399548,0xb5ccaef3,0xb5c4dec8,0xb45783e3,0xb516ec8c,0xb5b141d7,0xb5930511,
0x35c50adf,0x35ac59b8,0xb5b2cf52,0xb5c8186a,0x3584d0d5,0x3523afa2,0xb5cc2618,0xb5be9eff,0x343e9392,0xb491007a,0xb5a0ad5c,0xb569cab3,0xb53a66f9,0xb58e2017,0xb4fc30c0,0xb2f142bd,
0x35c243ef,0x35a110e7,0xb5cc4a54,0xb5c5367c,0x355a1284,0x34b108e1,0xb5a7142c,0xb56ad291,0xb44d8ba2,0xb539484b,0xb4d8115e,0x33fb14c1,0xb594c224,0xb5bb7be1,0x35272288,0x358dac1c,
0,0,0,0,0,0,0,0,0,0,0,0,0,0,0,0,
0x3396be44,0x341b9694,0x352dfd61,0x353ff996,0x346b6e11,0x349d5a2e,0x35517f65,0x35628401,0x34c49c48,0x34eb6521,0x3572fcea,0x35816ffc,0x3508ce67,0x351b95de,0x358911af,0x35905ed9,
0x34169569,0x349ae293,0x359d832a,0x35a99568,0x34e8fc95,0x351a6c18,0x35b4058e,0x35bcb9e0,0x353edd2d,0x356177b4,0x35c39ce8,0x35c89dab,0x3580f32d,0x358fec97,0x35cbafd4,0x35cccbd0,
0x34617a10,0x34e6937a,0x35c6322c,0x35cb9ed5,0x352bb614,0x35606adb,0x35cca31b,0x35c9395b,0x35882200,0x359d1c2c,0x35c17480,0x35b57f95,0x35aeafb3,0x35bc7b2f,0x35a59ce0,0x35922466,
0x3495f23f,0x3518176e,0x35c9570a,0x35be2876,0x355f5d78,0x358f0707,0x35abab1e,0x359294e9,0x35a8e03a,0x35bc3c09,0x3567b948,0x3521610f,0x35c85c01,0x35ccc8da,0x34a9aa67,0x32a0d873,
0x34bad62f,0x353b8534,0x35a65953,0x3584563c,0x35873101,0x35a88507,0x3534c922,0x34ac1fa5,0x35bfbf49,0x35cb7b60,0xb35d204b,0xb4e1bf99,0x35cb053d,0x35be63f5,0xb54d29a4,0xb58e93bb,
0x34df54d8,0x355d4116,0x3547b357,0x34ae9479,0x359be4ed,0x35bbbc62,0xb4028d3d,0xb515c14d,0x35cb68e9,0x35c990f4,0xb57df9b6,0xb5a8296b,0x35b65d28,0x359374de,0xb5c2da99,0xb5ccc3eb,
0x3501ad39,0x357cfd04,0x33e70786,0xb4dce98c,0x35ad5c81,0x35c7f5e5,0xb56ce099,0xb5a7cd68,0x35cb2e94,0x35b6a623,0xb5c58c49,0xb5cc32aa,0x358cc31e,0x3524d655,0xb5baf983,0xb593e451,
0x3f803f80,0,0,0x3f803f80,0x3f803f80,0,0,0x3f803f80,0x3f803f80,0,0,0x3f803f80,0x3f803f80,0,0,0x3f803f80,
0x3f353f80,0x3f350000,0xbf350000,0x3f353f80,0xbf350000,0x3f353f80,0xbf35bf80,0xbf350000,0xbf35bf80,0xbf350000,0x3f350000,0xbf35bf80,0x3f350000,0xbf35bf80,0x3f353f80,0x3f350000,
0x3f80,0x3f800000,0xbf800000,0x3f80,0xbf80,0xbf800000,0x3f800000,0xbf80,0x3f80,0x3f800000,0xbf800000,0x3f80,0xbf80,0xbf800000,0x3f800000,0xbf80,
0xbf353f80,0x3f350000,0xbf350000,0xbf353f80,0x3f350000,0x3f35bf80,0xbf353f80,0x3f350000,0x3f35bf80,0xbf350000,0x3f350000,0x3f35bf80,0xbf350000,0xbf353f80,0x3f35bf80,0xbf350000,
0xbf803f80,0,0,0xbf803f80,0xbf803f80,0,0,0xbf803f80,0xbf803f80,0,0,0xbf803f80,0xbf803f80,0,0,0xbf803f80,
0xbf353f80,0xbf350000,0x3f350000,0xbf353f80,0x3f350000,0xbf353f80,0x3f35bf80,0x3f350000,0x3f35bf80,0x3f350000,0xbf350000,0x3f35bf80,0xbf350000,0x3f35bf80,0xbf353f80,0xbf350000,
0x3f80,0xbf800000,0x3f800000,0x3f80,0xbf80,0x3f800000,0xbf800000,0xbf80,0x3f80,0xbf800000,0x3f800000,0x3f80,0xbf80,0x3f800000,0xbf800000,0xbf80,
0x3f353f80,0xbf350000,0x3f350000,0x3f353f80,0xbf350000,0xbf35bf80,0x3f353f80,0xbf350000,0xbf35bf80,0x3f350000,0xbf350000,0xbf35bf80,0x3f350000,0x3f353f80,0xbf35bf80,0x3f350000,
};

__device__ uint4 g_T[128 * TROW];
__device__ uint4 g_H[16 * 2 * 48 * 256];
__device__ uint4 g_X1[128 * 1280 + 96 * 1280];
__device__ uint4 g_mod[960];
__device__ __align__(128) uint32_t g_sync[64 + 32 * NCTA + 64 * 32];
#define PT(i)
#define PG(i)
#define PINIT()
#define PDUMP()
#define PSET(i, v)
#define PTB(i)
#define PT2(i)
#define PTA(i)
#define PWAIT(acc, stmt) stmt

__device__ __forceinline__ uint32_t pack2(float lo, float hi) { uint32_t r; asm("cvt.rn.bf16x2.f32 %0, %1, %2;" : "=r"(r) : "f"(hi), "f"(lo)); return r; }
__device__ __forceinline__ float blo(uint32_t v) { return __uint_as_float(v << 16); }
__device__ __forceinline__ float bhi(uint32_t v) { return __uint_as_float(v & 0xffff0000u); }
__device__ __forceinline__ uint32_t hfma2(uint32_t a, uint32_t b, uint32_t c) { uint32_t r; asm("fma.rn.bf16x2 %0, %1, %2, %3;" : "=r"(r) : "r"(a), "r"(b), "r"(c)); return r; }
__device__ __forceinline__ uint32_t hmul2(uint32_t a, uint32_t b) { uint32_t r; asm("mul.rn.bf16x2 %0, %1, %2;" : "=r"(r) : "r"(a), "r"(b)); return r; }
__device__ __forceinline__ uint32_t hadd2(uint32_t a, uint32_t b) { uint32_t r; asm("add.rn.bf16x2 %0, %1, %2;" : "=r"(r) : "r"(a), "r"(b)); return r; }
__device__ __forceinline__ uint32_t hsub2(uint32_t a, uint32_t b) { uint32_t r; asm("sub.rn.bf16x2 %0, %1, %2;" : "=r"(r) : "r"(a), "r"(b)); return r; }

__device__ __forceinline__ void mma16816(float (&d)[4], uint32_t a0, uint32_t a1, uint32_t a2, uint32_t a3, uint32_t b0, uint32_t b1) {
  asm("mma.sync.aligned.m16n8k16.row.col.f32.bf16.bf16.f32 {%0,%1,%2,%3}, {%4,%5,%6,%7}, {%8,%9}, {%0,%1,%2,%3};"
      : "+f"(d[0]), "+f"(d[1]), "+f"(d[2]), "+f"(d[3]) : "r"(a0), "r"(a1), "r"(a2), "r"(a3), "r"(b0), "r"(b1));
}
__device__ __forceinline__ uint32_t tc_tick() {
  float d0, d1, d2, d3;
  asm volatile("mma.sync.aligned.m16n8k8.row.col.f32.bf16.bf16.f32 {%0,%1,%2,%3}, {%4,%4}, {%4}, {%5,%5,%5,%5};" : "=f"(d0), "=f"(d1), "=f"(d2), "=f"(d3) : "r"(0), "f"(0.f));
  return __float_as_uint(d0);
}
__device__ __forceinline__ void mma1688(float (&d)[4], uint32_t a0, uint32_t a1, uint32_t b0) {
  asm("mma.sync.aligned.m16n8k8.row.col.f32.bf16.bf16.f32 {%0,%1,%2,%3}, {%4,%5}, {%6}, {%0,%1,%2,%3};"
      : "+f"(d[0]), "+f"(d[1]), "+f"(d[2]), "+f"(d[3]) : "r"(a0), "r"(a1), "r"(b0));
}
__device__ __forceinline__ void mma16816z(float (&d)[4], uint32_t a0, uint32_t a1, uint32_t a2, uint32_t a3, uint32_t b0, uint32_t b1) {
  asm("mma.sync.aligned.m16n8k16.row.col.f32.bf16.bf16.f32 {%0,%1,%2,%3}, {%4,%5,%6,%7}, {%8,%9}, {%10,%10,%10,%10};"
      : "=f"(d[0]), "=f"(d[1]), "=f"(d[2]), "=f"(d[3]) : "r"(a0), "r"(a1), "r"(a2), "r"(a3), "r"(b0), "r"(b1), "f"(0.f));
}
__device__ __forceinline__ void ldsm4(uint32_t (&r)[4], uint32_t a) { asm volatile("ldmatrix.sync.aligned.m8n8.x4.shared.b16 {%0,%1,%2,%3}, [%4];" : "=r"(r[0]), "=r"(r[1]), "=r"(r[2]), "=r"(r[3]) : "r"(a) : "memory"); }
__device__ __forceinline__ void ldsm2(uint32_t (&r)[2], uint32_t a) { asm volatile("ldmatrix.sync.aligned.m8n8.x2.shared.b16 {%0,%1}, [%2];" : "=r"(r[0]), "=r"(r[1]) : "r"(a) : "memory"); }
__device__ __forceinline__ void ldsm4t(uint32_t (&r)[4], uint32_t a) { asm volatile("ldmatrix.sync.aligned.m8n8.x4.trans.shared.b16 {%0,%1,%2,%3}, [%4];" : "=r"(r[0]), "=r"(r[1]), "=r"(r[2]), "=r"(r[3]) : "r"(a) : "memory"); }
__device__ __forceinline__ void stsm4(uint32_t a, uint32_t r0, uint32_t r1, uint32_t r2, uint32_t r3) { asm volatile("stmatrix.sync.aligned.m8n8.x4.shared.b16 [%0], {%1,%2,%3,%4};" :: "r"(a), "r"(r0), "r"(r1), "r"(r2), "r"(r3) : "memory"); }
__device__ __forceinline__ uint32_t movm(uint32_t a) { uint32_t d; asm volatile("movmatrix.sync.aligned.m8n8.trans.b16 %0, %1;" : "=r"(d) : "r"(a)); return d; }
__device__ __forceinline__ uint32_t lds32(uint32_t a) { uint32_t v; asm volatile("ld.shared.u32 %0, [%1];" : "=r"(v) : "r"(a) : "memory"); return v; }
__device__ __forceinline__ uint32_t lds16(uint32_t a) { uint32_t v; asm volatile("ld.shared.u16 %0, [%1];" : "=r"(v) : "r"(a) : "memory"); return v; }
__device__ __forceinline__ uint2 lds64(uint32_t a) { uint2 v; asm volatile("ld.shared.v2.u32 {%0,%1}, [%2];" : "=r"(v.x), "=r"(v.y) : "r"(a) : "memory"); return v; }
__device__ __forceinline__ uint4 lds128(uint32_t a) { uint4 v; asm volatile("ld.shared.v4.u32 {%0,%1,%2,%3}, [%4];" : "=r"(v.x), "=r"(v.y), "=r"(v.z), "=r"(v.w) : "r"(a) : "memory"); return v; }
__device__ __forceinline__ void sts32(uint32_t a, uint32_t v) { asm volatile("st.shared.u32 [%0], %1;" :: "r"(a), "r"(v) : "memory"); }
__device__ __forceinline__ void stsv(uint32_t a, uint32_t v) { asm volatile("st.volatile.shared.u32 [%0], %1;" :: "r"(a), "r"(v) : "memory"); }
__device__ __forceinline__ uint32_t ldsv(uint32_t a) { uint32_t v; asm volatile("ld.volatile.shared.u32 %0, [%1];" : "=r"(v) : "r"(a) : "memory"); return v; }
__device__ __forceinline__ void sts64(uint32_t a, uint32_t x, uint32_t y) { asm volatile("st.shared.v2.u32 [%0], {%1,%2};" :: "r"(a), "r"(x), "r"(y) : "memory"); }
__device__ __forceinline__ void sts128(uint32_t a, uint4 v) { asm volatile("st.shared.v4.u32 [%0], {%1,%2,%3,%4};" :: "r"(a), "r"(v.x), "r"(v.y), "r"(v.z), "r"(v.w) : "memory"); }
__device__ __forceinline__ uint4 ld_unit(const uint4* p) {
  uint4 v; asm volatile("ld.relaxed.gpu.global.v4.b32 {%0,%1,%2,%3}, [%4];" : "=r"(v.x), "=r"(v.y), "=r"(v.z), "=r"(v.w) : "l"(p) : "memory"); return v;
}
__device__ __forceinline__ void st_unit(uint4* p, uint4 v) {
  asm volatile("st.relaxed.gpu.global.v4.b32 [%0], {%1,%2,%3,%4};" :: "l"(p), "r"(v.x), "r"(v.y), "r"(v.z), "r"(v.w) : "memory");
}
constexpr uint32_t TMASK = 0x00010001u;
__device__ __forceinline__ uint32_t mk_tag(uint32_t n) { return (n & 1u) | ((n & 2u) << 15); }
__device__ __forceinline__ uint4 tag_unit(uint4 v, uint32_t tag) { asm("lop3.b32 %0, %1, %2, %3, 0xEA;" : "=r"(v.w) : "r"(v.w), "n"(~TMASK), "r"(tag)); return v; }
__device__ __forceinline__ uint32_t tag_word(uint32_t w, uint32_t tag) { uint32_t r; asm("lop3.b32 %0, %1, %2, %3, 0xEA;" : "=r"(r) : "r"(w), "n"(~TMASK), "r"(tag)); return r; }
__device__ __forceinline__ void tag_acc(uint32_t& acc, const uint4& v, uint32_t tag) { asm("lop3.b32 %0, %0, %1, %2, 0xF6;" : "+r"(acc) : "r"(v.w), "r"(tag)); }
__device__ __forceinline__ uint32_t ld_relaxed(const uint32_t* p) { uint32_t v; asm volatile("ld.relaxed.gpu.global.u32 %0, [%1];" : "=r"(v) : "l"(p) : "memory"); return v; }
__device__ __forceinline__ uint32_t ld_epoch(const uint32_t* p, int lane) { uint32_t z; asm volatile("and.b32 %0, %1, 0;" : "=r"(z) : "r"(lane)); return ld_relaxed(p + z); }
__device__ __forceinline__ uint32_t ld_acquire(const uint32_t* p) { uint32_t v; asm volatile("ld.acquire.gpu.global.u32 %0, [%1];" : "=r"(v) : "l"(p) : "memory"); return v; }
__device__ __forceinline__ void st_relaxed(uint32_t* p, uint32_t v) { asm volatile("st.relaxed.gpu.global.u32 [%0], %1;" :: "l"(p), "r"(v) : "memory"); }
__device__ __forceinline__ uint4 ld_relaxed4(const uint32_t* p) { uint4 v; asm volatile("ld.relaxed.gpu.global.v4.u32 {%0,%1,%2,%3}, [%4];" : "=r"(v.x), "=r"(v.y), "=r"(v.z), "=r"(v.w) : "l"(p) : "memory"); return v; }

__device__ __forceinline__ void bar_sync(int id, int n) { asm volatile("bar.sync %0, %1;" :: "r"(id), "r"(n) : "memory"); }
__device__ __forceinline__ bool bar_or(int id, int n, bool p) {
  uint32_t r; asm volatile("{\n.reg .pred p, q;\nsetp.ne.u32 p, %3, 0;\nbar.red.or.pred q, %1, %2, p;\nselp.u32 %0, 1, 0, q;\n}" : "=r"(r) : "r"(id), "r"(n), "r"((uint32_t)p) : "memory"); return r;
}
__device__ __forceinline__ void bar_arrive(int id, int n) { asm volatile("bar.arrive %0, %1;" :: "r"(id), "r"(n) : "memory"); }
__device__ __forceinline__ void mbar_init(uint32_t b, int c) { asm volatile("mbarrier.init.shared::cta.b64 [%0], %1;" :: "r"(b), "r"(c) : "memory"); }
__device__ __forceinline__ void mbar_expect(uint32_t b, uint32_t bytes) { asm volatile("mbarrier.arrive.expect_tx.shared::cta.b64 _, [%0], %1;" :: "r"(b), "r"(bytes) : "memory"); }
__device__ __forceinline__ void mbar_arrive(uint32_t b) { asm volatile("mbarrier.arrive.shared::cta.b64 _, [%0];" :: "r"(b) : "memory"); }
__device__ __forceinline__ void mbar_arrive_if(uint32_t b, bool p) { asm volatile("{\n.reg .pred p;\nsetp.ne.b32 p, %1, 0;\n@p mbarrier.arrive.shared::cta.b64 _, [%0];\n}" :: "r"(b), "r"((int)p) : "memory"); }
__device__ __forceinline__ void mbar_wait(uint32_t b, uint32_t ph) {
  asm volatile("{\n.reg .pred p;\n.reg .u32 n;\nmov.u32 n, 0;\n"
               "W_%=:\nmbarrier.try_wait.parity.shared::cta.b64 p, [%0], %1;\n@p bra D_%=;\n"
               "add.u32 n, n, 1;\nsetp.lt.u32 p, n, %2;\n@p bra W_%=;\nD_%=:\n}" :: "r"(b), "r"(ph), "n"(SPIN) : "memory");
}
__device__ __forceinline__ uint32_t mbar_test(uint32_t b, uint32_t ph) {
  uint32_t r; asm volatile("{\n.reg .pred p;\nmbarrier.test_wait.parity.shared::cta.b64 p, [%1], %2;\nselp.u32 %0, 1, 0, p;\n}" : "=r"(r) : "r"(b), "r"(ph) : "memory"); return r;
}
__device__ __forceinline__ void mbar_wait_cluster(uint32_t b, uint32_t ph) {
  asm volatile("{\n.reg .pred p;\n.reg .u32 n;\nmov.u32 n, 0;\n"
               "W_%=:\nmbarrier.try_wait.parity.acquire.cluster.shared::cta.b64 p, [%0], %1;\n@p bra D_%=;\n"
               "add.u32 n, n, 1;\nsetp.lt.u32 p, n, %2;\n@p bra W_%=;\nD_%=:\n}" :: "r"(b), "r"(ph), "n"(SPIN) : "memory");
}
__device__ __forceinline__ void bulk_g2s(uint32_t dst, const void* src, uint32_t bytes, uint32_t bar) {
  asm volatile("cp.async.bulk.shared::cluster.global.mbarrier::complete_tx::bytes [%0], [%1], %2, [%3];" :: "r"(dst), "l"(src), "r"(bytes), "r"(bar) : "memory");
}
__device__ __forceinline__ bool elect1() {
  uint32_t p; asm volatile("{\n.reg .pred p;\nelect.sync _|p, 0xffffffff;\nselp.u32 %0, 1, 0, p;\n}" : "=r"(p)); return p;
}
__device__ __forceinline__ void bulk_s2g(void* dst, uint32_t src, uint32_t bytes) {
  asm volatile("cp.async.bulk.global.shared::cta.bulk_group [%0], [%1], %2;" :: "l"(dst), "r"(src), "r"(bytes) : "memory");
}
__device__ __forceinline__ void tma2d_store(const CUtensorMap* m, uint32_t src, int c0, int c1) {
  asm volatile("cp.async.bulk.tensor.2d.global.shared::cta.bulk_group [%0, {%2, %3}], [%1];" :: "l"(m), "r"(src), "r"(c0), "r"(c1) : "memory");
}
#define BULK_COMMIT asm volatile("cp.async.bulk.commit_group;" ::: "memory")
#define BULK_WAIT_READ asm volatile("cp.async.bulk.wait_group.read 0;" ::: "memory")
#define BULK_WAIT asm volatile("cp.async.bulk.wait_group 0;" ::: "memory")
__device__ __forceinline__ void fence_async() { asm volatile("fence.proxy.async.shared::cta;" ::: "memory"); }
__device__ __forceinline__ void tma2d(uint32_t dst, const CUtensorMap* m, int c0, int c1, uint32_t bar) {
  asm volatile("cp.async.bulk.tensor.2d.shared::cluster.global.mbarrier::complete_tx::bytes [%0], [%1, {%3, %4}], [%2];" :: "r"(dst), "l"(m), "r"(bar), "r"(c0), "r"(c1) : "memory");
}
__device__ __forceinline__ void tma3d(uint32_t dst, const CUtensorMap* m, int c0, int c1, int c2, uint32_t bar) {
  asm volatile("cp.async.bulk.tensor.3d.shared::cluster.global.mbarrier::complete_tx::bytes [%0], [%1, {%3, %4, %5}], [%2];" :: "r"(dst), "l"(m), "r"(bar), "r"(c0), "r"(c1), "r"(c2) : "memory");
}
__device__ __forceinline__ void bulk_g2s_e(uint32_t dst, const void* src, uint32_t bytes, uint32_t bar) { if (elect1()) { mbar_expect(bar, bytes); bulk_g2s(dst, src, bytes, bar); } }
__device__ __forceinline__ void tma3d_e(uint32_t dst, const CUtensorMap* m, int c0, int c1, int c2, uint32_t bytes, uint32_t bar) { if (elect1()) { mbar_expect(bar, bytes); tma3d(dst, m, c0, c1, c2, bar); } }
__device__ __forceinline__ uint64_t mkdesc(uint32_t addr, uint32_t lbo, uint32_t sbo, uint32_t swz) {
  return (uint64_t)((addr & 0x3FFFF) >> 4) | ((uint64_t)(lbo >> 4) << 16) | ((uint64_t)(sbo >> 4) << 32) | ((uint64_t)swz << 62);
}
#define WG_FENCE asm volatile("wgmma.fence.sync.aligned;" ::: "memory")
#define WG_COMMIT asm volatile("wgmma.commit_group.sync.aligned;" ::: "memory")
#define WG_WAIT(n) asm volatile("wgmma.wait_group.sync.aligned %0;" :: "n"(n) : "memory")

__device__ __forceinline__ void wgmma_rs_n64_tb(float (&d)[32], uint32_t a0, uint32_t a1, uint32_t a2, uint32_t a3, uint64_t db, int sd) {
  asm volatile("{\n.reg .pred p;\nsetp.ne.b32 p, %37, 0;\n"
    "wgmma.mma_async.sync.aligned.m64n64k16.f32.bf16.bf16 {%0, %1, %2, %3, %4, %5, %6, %7, %8, %9, %10, %11, %12, %13, %14, %15, %16, %17, %18, %19, %20, %21, %22, %23, %24, %25, %26, %27, %28, %29, %30, %31}, {%32, %33, %34, %35}, %36, p, 1, 1, 1;\n}\n"
    : "+f"(d[0]), "+f"(d[1]), "+f"(d[2]), "+f"(d[3]), "+f"(d[4]), "+f"(d[5]), "+f"(d[6]), "+f"(d[7]), "+f"(d[8]), "+f"(d[9]), "+f"(d[10]), "+f"(d[11]), "+f"(d[12]), "+f"(d[13]), "+f"(d[14]), "+f"(d[15]), "+f"(d[16]), "+f"(d[17]), "+f"(d[18]), "+f"(d[19]), "+f"(d[20]), "+f"(d[21]), "+f"(d[22]), "+f"(d[23]), "+f"(d[24]), "+f"(d[25]), "+f"(d[26]), "+f"(d[27]), "+f"(d[28]), "+f"(d[29]), "+f"(d[30]), "+f"(d[31])
    : "r"(a0), "r"(a1), "r"(a2), "r"(a3), "l"(db), "r"(sd));
}
__device__ __forceinline__ void wgmma_rs_n80(float (&d)[40], uint32_t a0, uint32_t a1, uint32_t a2, uint32_t a3, uint64_t db, int sd) {
  asm volatile("{\n.reg .pred p;\nsetp.ne.b32 p, %45, 0;\n"
    "wgmma.mma_async.sync.aligned.m64n80k16.f32.bf16.bf16 {%0, %1, %2, %3, %4, %5, %6, %7, %8, %9, %10, %11, %12, %13, %14, %15, %16, %17, %18, %19, %20, %21, %22, %23, %24, %25, %26, %27, %28, %29, %30, %31, %32, %33, %34, %35, %36, %37, %38, %39}, {%40, %41, %42, %43}, %44, p, 1, 1, 0;\n}\n"
    : "+f"(d[0]), "+f"(d[1]), "+f"(d[2]), "+f"(d[3]), "+f"(d[4]), "+f"(d[5]), "+f"(d[6]), "+f"(d[7]), "+f"(d[8]), "+f"(d[9]), "+f"(d[10]), "+f"(d[11]), "+f"(d[12]), "+f"(d[13]), "+f"(d[14]), "+f"(d[15]), "+f"(d[16]), "+f"(d[17]), "+f"(d[18]), "+f"(d[19]), "+f"(d[20]), "+f"(d[21]), "+f"(d[22]), "+f"(d[23]), "+f"(d[24]), "+f"(d[25]), "+f"(d[26]), "+f"(d[27]), "+f"(d[28]), "+f"(d[29]), "+f"(d[30]), "+f"(d[31]), "+f"(d[32]), "+f"(d[33]), "+f"(d[34]), "+f"(d[35]), "+f"(d[36]), "+f"(d[37]), "+f"(d[38]), "+f"(d[39])
    : "r"(a0), "r"(a1), "r"(a2), "r"(a3), "l"(db), "r"(sd));
}
__device__ __forceinline__ void wgmma_rs_n80_tb(float (&d)[40], uint32_t a0, uint32_t a1, uint32_t a2, uint32_t a3, uint64_t db, int sd) {
  asm volatile("{\n.reg .pred p;\nsetp.ne.b32 p, %45, 0;\n"
    "wgmma.mma_async.sync.aligned.m64n80k16.f32.bf16.bf16 {%0, %1, %2, %3, %4, %5, %6, %7, %8, %9, %10, %11, %12, %13, %14, %15, %16, %17, %18, %19, %20, %21, %22, %23, %24, %25, %26, %27, %28, %29, %30, %31, %32, %33, %34, %35, %36, %37, %38, %39}, {%40, %41, %42, %43}, %44, p, 1, 1, 1;\n}\n"
    : "+f"(d[0]), "+f"(d[1]), "+f"(d[2]), "+f"(d[3]), "+f"(d[4]), "+f"(d[5]), "+f"(d[6]), "+f"(d[7]), "+f"(d[8]), "+f"(d[9]), "+f"(d[10]), "+f"(d[11]), "+f"(d[12]), "+f"(d[13]), "+f"(d[14]), "+f"(d[15]), "+f"(d[16]), "+f"(d[17]), "+f"(d[18]), "+f"(d[19]), "+f"(d[20]), "+f"(d[21]), "+f"(d[22]), "+f"(d[23]), "+f"(d[24]), "+f"(d[25]), "+f"(d[26]), "+f"(d[27]), "+f"(d[28]), "+f"(d[29]), "+f"(d[30]), "+f"(d[31]), "+f"(d[32]), "+f"(d[33]), "+f"(d[34]), "+f"(d[35]), "+f"(d[36]), "+f"(d[37]), "+f"(d[38]), "+f"(d[39])
    : "r"(a0), "r"(a1), "r"(a2), "r"(a3), "l"(db), "r"(sd));
}
__device__ __forceinline__ void wgmma_ss_n160_tb(float (&d)[80], uint64_t da, uint64_t db, int sd) {
  asm volatile("{\n.reg .pred p;\nsetp.ne.b32 p, %82, 0;\n"
    "wgmma.mma_async.sync.aligned.m64n160k16.f32.bf16.bf16 {%0, %1, %2, %3, %4, %5, %6, %7, %8, %9, %10, %11, %12, %13, %14, %15, %16, %17, %18, %19, %20, %21, %22, %23, %24, %25, %26, %27, %28, %29, %30, %31, %32, %33, %34, %35, %36, %37, %38, %39, %40, %41, %42, %43, %44, %45, %46, %47, %48, %49, %50, %51, %52, %53, %54, %55, %56, %57, %58, %59, %60, %61, %62, %63, %64, %65, %66, %67, %68, %69, %70, %71, %72, %73, %74, %75, %76, %77, %78, %79}, %80, %81, p, 1, 1, 0, 1;\n}\n"
    : "+f"(d[0]), "+f"(d[1]), "+f"(d[2]), "+f"(d[3]), "+f"(d[4]), "+f"(d[5]), "+f"(d[6]), "+f"(d[7]), "+f"(d[8]), "+f"(d[9]), "+f"(d[10]), "+f"(d[11]), "+f"(d[12]), "+f"(d[13]), "+f"(d[14]), "+f"(d[15]), "+f"(d[16]), "+f"(d[17]), "+f"(d[18]), "+f"(d[19]), "+f"(d[20]), "+f"(d[21]), "+f"(d[22]), "+f"(d[23]), "+f"(d[24]), "+f"(d[25]), "+f"(d[26]), "+f"(d[27]), "+f"(d[28]), "+f"(d[29]), "+f"(d[30]), "+f"(d[31]), "+f"(d[32]), "+f"(d[33]), "+f"(d[34]), "+f"(d[35]), "+f"(d[36]), "+f"(d[37]), "+f"(d[38]), "+f"(d[39]), "+f"(d[40]), "+f"(d[41]), "+f"(d[42]), "+f"(d[43]), "+f"(d[44]), "+f"(d[45]), "+f"(d[46]), "+f"(d[47]), "+f"(d[48]), "+f"(d[49]), "+f"(d[50]), "+f"(d[51]), "+f"(d[52]), "+f"(d[53]), "+f"(d[54]), "+f"(d[55]), "+f"(d[56]), "+f"(d[57]), "+f"(d[58]), "+f"(d[59]), "+f"(d[60]), "+f"(d[61]), "+f"(d[62]), "+f"(d[63]), "+f"(d[64]), "+f"(d[65]), "+f"(d[66]), "+f"(d[67]), "+f"(d[68]), "+f"(d[69]), "+f"(d[70]), "+f"(d[71]), "+f"(d[72]), "+f"(d[73]), "+f"(d[74]), "+f"(d[75]), "+f"(d[76]), "+f"(d[77]), "+f"(d[78]), "+f"(d[79])
    : "l"(da), "l"(db), "r"(sd));
}

__device__ __forceinline__ uint32_t clk() { uint32_t c; asm volatile("mov.u32 %0, %clock;" : "=r"(c)); return c; }
__device__ __forceinline__ void keep(uint32_t& x) { asm volatile("" : "+r"(x)); }
__device__ __forceinline__ void keep(float& x) { asm volatile("" : "+f"(x)); }
template <typename T> __device__ __forceinline__ void keepp(T*& x) { asm volatile("" : "+l"(x)); }
__device__ __forceinline__ float gelu(float g) {
  float z = g * fmaf(g * g, 0.0356774081f, 0.7978845608f), th;
  asm("tanh.approx.f32 %0, %1;" : "=f"(th) : "f"(z));
  float hg = 0.5f * g;
  return fmaf(hg, th, hg);
}
__device__ __forceinline__ float rsq(float x) { float r; asm("rsqrt.approx.ftz.f32 %0, %1;" : "=f"(r) : "f"(x)); return r; }
__device__ __forceinline__ float silu(float c) {
  float e, r;
  asm("ex2.approx.ftz.f32 %0, %1;" : "=f"(e) : "f"(c * -1.4426950408889634f));
  asm("rcp.approx.ftz.f32 %0, %1;" : "=f"(r) : "f"(1.f + e));
  return c * r;
}
__device__ __forceinline__ uint32_t silu2(uint32_t v) { return pack2(silu(blo(v)), silu(bhi(v))); }
__device__ __forceinline__ uint32_t mod_pair(float v0, float v1, bool plus1) {
  uint32_t b = pack2(v0, v1);
  if (plus1) b = pack2(1.f + blo(b), 1.f + bhi(b));
  return b;
}
__device__ __forceinline__ int slot_kj(int s) { return (s & 1) ? (s > 1 ? 16 - (s >> 1) : 8) : s >> 1; }
__device__ __forceinline__ int kj_slot(int k) { return k < 8 ? 2 * k : (k == 8 ? 1 : 33 - 2 * k); }
__device__ __forceinline__ int rho(int s0) {
  int n1 = s0 >> 3, n2 = s0 & 7;
  return (n1 & 1) | ((n1 ^ n2) & 2) | (((n2 << 2) ^ n2) & 4) | ((n2 & 6) << 2) | ((n1 & 12) << 3);
}
__device__ __forceinline__ uint32_t col_off(int k) { int k1 = k & 15, kq = k >> 4; return k1 < 8 ? k1 * EX_SLOT + kq * 4 : (16 - k1) * EX_SLOT + (39 - kq) * 4; }
__device__ __forceinline__ void col_off2(int k, uint32_t& a, uint32_t& b) {
  int r8 = (k >> 3) & 1, kq = k >> 4;
  bool sp = (k & 7) == 0;
  uint32_t r = col_off(k);
  a = sp ? r8 * 8 * EX_TOK + kq * 4 : r;
  b = sp ? r8 * 8 * EX_TOK + (40 - r8 - kq) * 4 : r + 8 * EX_TOK;
}

template <int K0, int K1, int STRIDE, int N> __device__ __forceinline__ void uload(uint4 (&v)[N], const uint4* p) {
#pragma unroll
  for (int k = K0; k < K1; k++) v[k % N] = ld_unit(p + k * STRIDE);
}
template <int K0, int K1, int STRIDE, int N> __device__ __forceinline__ int ucheck(uint4 (&v)[N], const uint4* p, uint32_t tag) {
  int it = 0;
#pragma unroll 1
  for (; it < SPIN; it++) {
    uint32_t bad = 0;
#pragma unroll
    for (int k = K0; k < K1; k++) tag_acc(bad, v[k % N], tag);
    if (__builtin_expect(!__any_sync(~0u, bad & TMASK), 1)) break;
    uload<K0, K1, STRIDE, N>(v, p);
  }
  return it;
}

struct LnAcc { float sm[4], qa[2][4], qb[2][4]; };
__device__ __forceinline__ void ln_step(LnAcc& A, const uint32_t (&d)[4]) {
  mma16816(A.sm, d[0], d[2], d[1], d[3], 0x3f803f80u, 0x3f803f80u);
#pragma unroll
  for (int h = 0; h < 2; h++) { mma1688(A.qa[h], d[h], d[2 + h], d[h]); mma1688(A.qb[h], d[h], d[2 + h], d[2 + h]); }
}
__device__ __forceinline__ void ln_finish(const LnAcc& A, int g, uint32_t (&d)[5][4]) {
  float sa = A.sm[0], sb = A.sm[2], qa = (g & 1) ? A.qa[0][1] + A.qa[1][1] : A.qa[0][0] + A.qa[1][0], qb = (g & 1) ? A.qb[0][3] + A.qb[1][3] : A.qb[0][2] + A.qb[1][2];
#pragma unroll
  for (int i = 0; i < 3; i++) {
    const int o = i == 0 ? 4 : (i == 1 ? 9 : 18);
    sa += __shfl_xor_sync(~0u, sa, o); sb += __shfl_xor_sync(~0u, sb, o);
    qa += __shfl_xor_sync(~0u, qa, o); qb += __shfl_xor_sync(~0u, qb, o);
  }
  qa = __shfl_sync(~0u, qa, 0); qb = __shfl_sync(~0u, qb, 0);
  sa *= (1.f / 640.f); sb *= (1.f / 640.f);
  const float ra = rsq(fmaxf(qa * (1.f / 640.f) - sa * sa, 0.f) + 1e-5f), rb = rsq(fmaxf(qb * (1.f / 640.f) - sb * sb, 0.f) + 1e-5f);
  const uint32_t rha = pack2(ra, ra), rhb = pack2(rb, rb), rla = pack2(ra - blo(rha), ra - blo(rha)), rlb = pack2(rb - blo(rhb), rb - blo(rhb));
  const uint32_t oa = pack2(-sa * ra, -sa * ra), ob = pack2(-sb * rb, -sb * rb);
#pragma unroll
  for (int m = 0; m < 5; m++)
#pragma unroll
    for (int h = 0; h < 2; h++) { d[m][h] = hfma2(d[m][h], rha, hfma2(d[m][h], rla, oa)); d[m][2 + h] = hfma2(d[m][2 + h], rhb, hfma2(d[m][2 + h], rlb, ob)); }
}

__device__ __forceinline__ void tick_until(uint32_t a, uint32_t v) {
  int it = 0;
  do {
    const uint32_t t = clk() + tc_tick();
    while (clk() - t < TICK) {}
  } while (!__any_sync(~0u, ldsv(a) >= v) && ++it < SPIN);
}

struct Params {
  const __nv_bfloat16 *x, *wr, *wi, *wg, *wu, *wd, *c, *wmod;
  __nv_bfloat16* out;
  uint4 *T, *H, *X1, *mod;
  uint32_t* sync;
  const uint32_t* tab;
};

__global__ void __cluster_dims__(2, 1, 1) __launch_bounds__(NTHR, 1)
fused_kernel(const Params P, const __grid_constant__ CUtensorMap tm_g, const __grid_constant__ CUtensorMap tm_u,
             const __grid_constant__ CUtensorMap tm_d, const __grid_constant__ CUtensorMap tm_wr, const __grid_constant__ CUtensorMap tm_wi,
             const __grid_constant__ CUtensorMap tm_ma, const __grid_constant__ CUtensorMap tm_mb,
             const __grid_constant__ CUtensorMap tm_t8, const __grid_constant__ CUtensorMap tm_t2,
             const __grid_constant__ CUtensorMap tm_zr, const __grid_constant__ CUtensorMap tm_zi, const __grid_constant__ CUtensorMap tm_o) {
  extern __shared__ __align__(1024) uint8_t smem[];
  const uint32_t sb = (uint32_t)__cvta_generic_to_shared(smem);
  const int tid = threadIdx.x, lane = tid & 31, warp = __shfl_sync(~0u, tid >> 5, 0), g = lane >> 2, t = lane & 3;
  const int bid = blockIdx.x;
  const uint32_t bars = sb + OFF_BAR;
  PINIT(); PT(0); PG(31);
  const int rank = bid & 1;
  const bool main_cta = bid < NMAIN;

  uint32_t* const myline = P.sync + 64 + 32 * bid;
  const uint32_t t0 = clk();
  uint4 cv = make_uint4(0, 0, 0, 0);
  if (tid < 256) asm volatile("ld.global.nc.v4.u32 {%0,%1,%2,%3}, [%4];" : "=r"(cv.x), "=r"(cv.y), "=r"(cv.z), "=r"(cv.w) : "l"(reinterpret_cast<const uint4*>(P.c) + (tid >> 5) * 10 + min(lane, 9)) : "memory");
  if (elect1()) {
    const uint32_t b = bars + 8 * warp;
    mbar_init(b, 1);
    if (warp < 8) {
      mbar_expect(b, bid < 80 ? 2560 : 0);
      if (bid < 80) tma2d(sb + 7 * STAGE - 10240 + warp * 2560, &tm_ma, bid * 16, warp * 80, b);
      PT(26);
    } else {
      mbar_expect(b, warp == BAR_WD ? (main_cta ? 6144 : 16 * 6144) : (warp == BAR_WF ? (main_cta ? 2 * WSZ : 32768) : (warp == BAR_TAB ? 25088 : 20480)));
      if (warp == BAR_WD) bulk_g2s(sb + (main_cta ? OFF_CC : 0), P.tab + 6272 + (main_cta ? (bid >> 3) * 1536 : 0), main_cta ? 6144 : 16 * 6144, b);
      if (warp == BAR_TAB && main_cta) { bulk_g2s(sb + OFF_M40, P.tab, 20480, b); bulk_g2s(sb, P.tab + 5120, 4608, b); }
    }
    mbar_init(b + 96, warp < 8 ? 1 : 8);
    mbar_init(b + 192, warp < 4 ? 8 : (warp < 11 ? 1 : 4));
    if (warp >= 6) mbar_init(b + 240, 4);
    asm volatile("fence.mbarrier_init.release.cluster;" ::: "memory");
  }
  __syncwarp();
  asm volatile("barrier.cluster.arrive.relaxed.aligned;" ::: "memory");

  if (warp >= 8) {
    asm volatile("setmaxnreg.dec.sync.aligned.u32 56;");
    const int bt = tid - 288;
    const uint32_t epoch0 = ld_relaxed(myline + threadIdx.y);
    if (warp == 9) { stsv(sb + OFF_EV, tc_tick()); sts32(sb + OFF_ZERO + lane * 4, 0); }
    if (warp == 9 && lane < 12) asm volatile("prefetch.tensormap [%0];" :: "l"(&tm_g + lane) : "memory");
    if (warp == 10) {
      if (bid < 80 && lane < 16 && t == 0) st_unit(P.mod + bid * 4 + g, make_uint4(0, 0, 0, 0));
      if (main_cta && bid >= 48 && rank == 0 && !(lane & 1)) st_unit(P.mod + 320 + (bid - 48) * 8 + (lane >> 1), make_uint4(0, 0, 0, 0));
    }
    asm volatile("barrier.cluster.wait.aligned;" ::: "memory");
    asm volatile("barrier.cluster.arrive.relaxed.aligned;" ::: "memory");
    const uint32_t epoch = __shfl_sync(~0u, epoch0, 0);
    if (warp == 11) sts32(sb + OFF_ROLE + 4, epoch);
    PT(4);
    if (warp == 8) {
      if (main_cta) {
        uint32_t role = 0; const uint32_t tg = (epoch + 1) << 8;
        if (lane == 0 && rank == 0) {
          uint32_t smid; asm volatile("mov.u32 %0, %smid;" : "=r"(smid));
          uint32_t gi = smid < 64 ? (smid >> 1) & 7 : ((smid - 64) >> 1) % 7 + 1, nx = 0, tk;
          while ((tk = atomicAdd(P.sync + 32 + (epoch & 1) * 8 + gi, 1u)) >= 8 && nx < 8) gi = nx++;
          st_relaxed(myline + 2, ((epoch + 1) << 8) | (gi * 8 + tk));
        }
        if (bid == 0 && lane < 8) st_relaxed(P.sync + 32 + ((epoch & 1) ^ 1) * 8 + lane, 0);
        const char* p2 = reinterpret_cast<const char*>(P.wmod) + bid * 38400 + 2560 + lane * 128;
        const char* p3 = lane < 16 ? reinterpret_cast<const char*>(lane & 8 ? P.wu : P.wg) + bid * 15360 + (lane & 4) * 384 + (lane & 3) * 128 : p2 + 2048 - (lane & 8) * 128;
        uint32_t tn = t0 + PF_START;
        const char* p1 = reinterpret_cast<const char*>(lane < 16 ? P.wr : P.wi) + bid * 10272 + (lane & 15) * 128;
#pragma unroll 1
        for (int i = 0; i < 5; i++) { while ((int)(clk() - tn) < 0) {} asm volatile("prefetch.global.L2 [%0];" :: "l"(p1)); p1 += 2048; tn += PF_STEP; }
        { int it = 0; do { role = ld_relaxed(myline - 32 * rank + 2); } while ((role ^ tg) >> 8 && ++it < SPIN); }
        role = __shfl_sync(~0u, role & 63, 0);
        role += rank * 64;
        const int nq = role & 3, kh = role >> 6;
        sts32(sb + OFF_ROLE, role);
#pragma unroll 1
        for (int si = 0; si < NSTAGES; si++) {
          __syncwarp();
          const int st = si == 5 ? 6 : (si == 6 ? 7 : (si == 7 ? 5 : si));
          if (st == 0 || st == RS1B) {
#pragma unroll 1
            for (int i = st ? 1 : 0; i < (st || !RS1B ? 5 : 1); i++) {
              while ((int)(clk() - tn) < 0) {}
              asm volatile("prefetch.global.L2 [%0];" :: "l"(p2)); asm volatile("prefetch.global.L2 [%0];" :: "l"(p3));
              p2 += 7680; p3 += lane < 16 ? 3072 : 7680; tn += PF_STEP * 7 / 4;
            }
            __syncwarp();
          }
          if (st == 0) bar_sync(0, 96);
          if (st == RS1B) bar_sync(8, 288);
          if (st == RS2) {
            bar_sync(11, 288);
            if (elect1()) {
              mbar_expect(bars + 8 * BAR_MA, bid >= 48 ? 40960 : 0);
              if (bid >= 48) tma3d(sb + OFF_MB, &tm_mb, 1280 + (bid >> 1) * 64 - 24 * 64, 0, 2 * rank, bars + 8 * BAR_MA);
            }
            __syncwarp();
            PT(7);
          }
          if (st == RS2B) bar_sync(10, 64);
          if (si == 5) { bar_sync(12, 64); const uint32_t t1 = clk(); while (clk() - t1 < E3_DELAY) {} __syncwarp(); }
          if (si == 7) bar_sync(13, 128);
          const uint32_t fb = bars + 8 * (BAR_FULL + (st & 7)), dst = sb + (st & 7) * STAGE;
          if (st >= 8) mbar_wait(fb + 64, ((st >> 3) - 1) & 1);
          if (st < 24) tma3d_e(dst, (st & 4) ? &tm_u : &tm_g, 0, 160 * (st & 3), 12 * kh + 4 * (st >> 3) + nq, STAGE, fb);
          else bulk_g2s_e(dst, P.X1 + (128 - 24 + (kh * 4 + nq) * 12 + st) * 1280, STAGE, fb);
          if (st == 23) {
            int it = 0;
            while ((int)(ld_acquire(P.sync + 48 + kh * 4 + nq) - 12 * (epoch + 1)) < 0 && ++it < SPIN) {}
            asm volatile("fence.proxy.async.global;" ::: "memory");
          }
        }
      } else if (lane == 0) {
#pragma unroll 1
        for (int i = 0; i < 16; i++) tma2d(sb + OFF_MB + i * 2048, (i & 1) ? &tm_zi : &tm_zr, (slot_kj((bid - NMAIN) * 8 + (i >> 1)) * 321 + 320) & ~7, 0, bars + 8 * BAR_WF);
      }
    } else {
      const uint32_t tagm = epoch | 0x80000000u;
#pragma unroll 1
      for (int pass = 0; pass < 3; pass++) {
        if (main_cta) {
          if (warp == 10 && (pass == 1 || (pass == 0 && bid < 80))) {
            bar_sync(2, 288);
            if (pass) PTA(11); else PTA(14);
            if (pass == 0 || (bid >= 48 && rank == 0)) {
              if (pass) { if (lane == 0) mbar_expect(bars + 8 * (BAR_MA + 1), 1024); mbar_wait_cluster(bars + 8 * (BAR_MA + 1), 1); }
              uint4 p0 = lds128(sb + OFF_RED + lane * 32), p1 = lds128(sb + OFF_RED + lane * 32 + 16);
              float v0 = (__uint_as_float(p0.x) + __uint_as_float(p0.y)) + (__uint_as_float(p0.z) + __uint_as_float(p0.w));
              float v1 = (__uint_as_float(p1.x) + __uint_as_float(p1.y)) + (__uint_as_float(p1.z) + __uint_as_float(p1.w));
              if (!pass) { v0 = (v0 + v1) * (bid < 40 ? 16.f : 1.f); v1 = __shfl_down_sync(~0u, v0, 1); }
              const uint32_t w0 = mod_pair(v0, v1, pass ? (uint32_t)(bid - 88) < 20u : bid >= 40), w1 = __shfl_down_sync(~0u, w0, pass ? 1 : 2);
              if (pass ? !(lane & 1) : lane < 16 && t == 0) st_unit(P.mod + (pass ? 320 + (bid - 48) * 8 + (lane >> 1) : bid * 4 + g), make_uint4(w0, w1, tagm, tagm));
            }
            if (pass) PTA(12); else PTA(15);
          }
          if (pass == 1) {
            if (warp == 9) { tick_until(sb + OFF_EV, 1); mbar_wait(bars + 8 * BAR_MA, 1); } else stsv(sb + OFF_EV, 1);
            if (warp < 11) { const uint32_t t1 = clk(); while (clk() - t1 < MOD_POLL2) {} }
          }
          while (__shfl_sync(~0u, clk() + tc_tick(), 0) - t0 < MOD_POLL) {}
          const int nquad = pass == 0 ? 320 : (pass == 1 ? 480 : 40);
          const uint4* mp = P.mod + (pass == 2 ? 800 + (lds32(sb + OFF_ROLE) & 3) * 40 : pass * 320) + bt;
          const uint32_t dst = sb + (pass == 0 ? OFF_MODA : OFF_MODB) + bt * 8;
          uint4 v[5]; int it = 0; bool bad[5];
#pragma unroll
          for (int k = 0; k < 5; k++) { v[k] = make_uint4(0, 0, tagm, tagm); bad[k] = bt + 96 * k < nquad; }
#pragma unroll 1
          do {
#pragma unroll
            for (int k = 0; k < 5; k++) if (bad[k]) v[k] = ld_unit(mp + 96 * k);
            it += 1 + tc_tick();
#pragma unroll
            for (int k = 0; k < 5; k++) bad[k] = (v[k].z & v[k].w) != tagm;
          } while (__any_sync(~0u, bad[0] | bad[1] | bad[2] | bad[3] | bad[4]) && it < SPIN);
#pragma unroll
          for (int k = 0; k < 5; k++) if (bt + 96 * k < nquad && pass < 2) sts64(dst + 768 * k, v[k].x, v[k].y);
          if (pass == 2 && bt < 40) {
            const uint32_t a = sb + OFF_GB + (bt & 1) * 160 + (bt >> 1) * 4;
            sts32(a, v[0].x); sts32(a + 80, v[0].y);
          }
          if (pass == 1) PTA(13); else if (pass == 0) PTA(9);
          if (pass == 2) bar_sync(15, 96); else if (pass == 0 && warp >= 10) bar_sync(13, 352); else bar_arrive(pass ? 4 : 13, 352);
          if (pass == 0 && warp < 11) {
            if (warp == 9 && elect1())
              asm volatile("cp.async.bulk.tensor.2d.shared::cluster.global.mbarrier::complete_tx::bytes.multicast::cluster [%0], [%1, {%3, %4}], [%2], %5;"
                           :: "r"(sb + OFF_WF + rank * WSZ), "l"(rank ? &tm_wi : &tm_wr), "r"(bars + 8 * BAR_WF), "r"(((bid >> 3) * 321 + (bid & 6) * 40) & ~7), "r"(0), "h"((uint16_t)3) : "memory");
            __syncwarp();
            bar_arrive(0, 96);
          }
        }
        if (pass == 0 && warp == 9 && !main_cta) tick_until(sb + OFF_EV, 1);
        if (pass == 0 && warp == 11) {
          const uint32_t target = (epoch + 1) * NMAIN; int it = 0;
          if (main_cta && lane == 0) asm volatile("red.relaxed.gpu.global.add.u32 [%0], 1;" :: "l"(P.sync) : "memory");
          uint32_t t1 = clk();
          if (main_cta) { while (clk() - t1 < H_POLL) {} }
          while ((int)(ld_relaxed(P.sync) - target) < 0 && ++it < SPIN) {}
          if (!main_cta) t1 = clk() - 1300;
          PTB(6);
          while (clk() - t1 < H_MIN) {}
          __syncwarp();
          const int c8 = (main_cta ? bid * 8 : 1280 + (bid - NMAIN) * 8) * 8, c2 = (1024 + (bid & 7) * 32 + kj_slot(bid >> 3) * 2) * 8;
          it = 0;
#pragma unroll 1
          do {
            if (elect1()) {
              if (it) fence_async();
              mbar_expect(bars + 8 * (BAR_MA + 3), main_cta ? 20480 : 16384);
              tma2d(sb + OFF_EX, &tm_t8, c8, 0, bars + 8 * (BAR_MA + 3));
              if (main_cta) tma2d(sb + OFF_EX + 16384, &tm_t2, c2, 0, bars + 8 * (BAR_MA + 3));
            }
            __syncwarp();
            PTB(5);
          } while (bar_or(14, 288, false) && ++it < SPIN);
          t1 = clk();
          if (elect1()) {
            fence_async();
            tma2d_store(&tm_t8, sb + OFF_EX, c8, 0);
            if (main_cta) tma2d_store(&tm_t2, sb + OFF_EX + 16384, c2, 0);
            BULK_COMMIT;
          }
          __syncwarp();
          if (main_cta) bar_arrive(10, 64);
          BULK_WAIT_READ;
          __syncwarp();
          if (!main_cta) { st_relaxed(myline, epoch + 1); stsv(sb + OFF_EV, 1); }
          else {
            bar_sync(3, 288);
            while (clk() - t1 < D_DELAY) {}
            __syncwarp();
            bulk_g2s_e(sb + OFF_MB, P.T + rho(bid) * TROW, TROW * 16, bars + 8 * (BAR_MA + 2));
            __syncwarp();
            PTB(8);
          }
        }
      }
      if (main_cta) {
        bar_arrive(13, 128);
        const int role = lds32(sb + OFF_ROLE), kh = role >> 6, hblk = (((role >> 2) & 15) * 2 + kh) * 2;
        uint32_t* const hcnt = P.sync + 64 + 32 * NCTA;
        if (warp == 9) {
          tick_until(sb + OFF_EV, 2);
          bar_sync(5, 288);
          const int sl = bid / 12;
          if (bid < 96) tma3d_e(sb + OFF_M40, &tm_d, 0, 768 * (sl >> 2) + 64 * (bid - sl * 12), 5 * (sl & 3), STAGE, bars + 8 * BAR_WD);
          if (lane == 0) {
            fence_async();
            uint32_t tn = clk();
#pragma unroll 1
            for (int i = 0; i < (bid < 96 ? 2 * W9_N : W9_N); i++) {
              if (i == W9_N) mbar_wait(bars + 8 * BAR_WD, 1);
              while ((int)(clk() - tn) < 0) {}
              tn += W9_STEP;
              bulk_s2g(P.X1 + (i < W9_N ? bid : 127 + bid) * 1280 + i * (1280 / W9_N), sb + (i < W9_N ? OFF_XS : OFF_M40 - 20480) + i * (20480 / W9_N), 20480 / W9_N);
            }
            BULK_COMMIT; BULK_WAIT;
            st_relaxed(myline + 1, epoch + 1);
            if (bid < 96) asm volatile("red.relaxed.gpu.global.add.u32 [%0], 1;" :: "l"(P.sync + 48 + sl) : "memory");
          }
          __syncwarp();
          { int it = 0;
            while (__any_sync(~0u, ld_acquire(P.sync + 65 + 32 * ((hblk >> 2) * 8 + (kh ^ 1) * 4 + (lane & 3))) != epoch + 1) && ++it < SPIN) {} }
          const uint4* pe = P.H + (hblk + (kh ^ 1)) * 6144;
          const uint4* pl = P.H + (hblk + kh) * 6144;
          uint32_t hb = bars + 8 * BAR_HF, dst = sb + OFF_M40, hp = 1, rdy = 1, who = 0xfe03e0u, ev = 0x022011u;
#pragma unroll 1
          for (int n = 0; n < 24; n++) {
            if (ev & 1) {
              if (n < 8) {
                int it = 0;
                while (__any_sync(~0u, (int)(ld_acquire(hcnt + (hblk + (lane & 1)) * 32 + (n ? 8 : 0)) - 4 * (epoch + 1)) < 0) && ++it < SPIN) {}
              } else bar_sync(13 + (who & 1), 64);
              asm volatile("fence.proxy.async.global;" ::: "memory");
            }
            if (!rdy) mbar_wait(hb + 56, hp);
            const uint32_t cb = hb, cd = dst; const uint4* cp = (who & 1) ? pl : pe;
            if (who & 1) pl += 512; else pe += 512;
            who >>= 1; ev >>= 1; hb += 8; dst += 8192;
            if (hb == bars + 8 * BAR_HE) { hb -= 56; dst -= 7 * 8192; hp ^= 1; }
            rdy = mbar_test(hb + 56, hp);
            bulk_g2s_e(cd, cp, 8192, cb);
          }
        } else {
          uint32_t* const cnt = hcnt + (hblk + ((warp & 1) ^ kh ^ 1)) * 32;
          {
            uint32_t tn = clk() + PF2_START;
            while ((int)(clk() - tn) < 0) {}
#pragma unroll 1
            for (int i = 0; i < 6; i++) {
              const char* pw = reinterpret_cast<const char*>(i < 2 ? P.wg : (i < 4 ? P.wu : P.wd)) + bid * 15360 + (warp & 1) * 7680 + (i & 1) * 3584 + lane * 128;
              tn += PF2_STEP;
              asm volatile("prefetch.global.L2 [%0];" :: "l"(pw));
              while ((int)(clk() - tn) < 0) {}
            }
          }
#pragma unroll 1
          for (int i = 0; i < 3; i++) {
            bar_sync(warp - 8, 160);
            if (lane < 4) {
              fence_async();
              bulk_s2g(P.H + ((hblk + ((warp & 1) ^ kh ^ 1)) * 12 + 4 * i + (role & 3)) * 512 + lane * 128, sb + (lane == 3 ? OFF_MODB : OFF_HST + lane * 2048), 2048);
              BULK_COMMIT; BULK_WAIT_READ;
            }
            __syncwarp();
            if (i + (warp & 1) < 3) bar_arrive(21 - warp, 160);
            if (lane < 4) BULK_WAIT;
            __syncwarp();
            if (lane == 0) asm volatile("red.relaxed.gpu.global.add.u32 [%0], 1;" :: "l"(cnt + i * 8) : "memory");
            __syncwarp();
          }
          int it = 0;
          while ((int)(ld_acquire(cnt + 16) - 4 * (epoch + 1)) < 0 && ++it < SPIN) {}
          __syncwarp();
          bar_arrive(warp + 3, 64);
        }
      }
    }
    __syncwarp();
    asm volatile("barrier.cluster.wait.aligned;" ::: "memory");
    PDUMP();
  } else {
    PT(23);
    {
      const uint32_t d = sb + OFF_SILU + warp * 160 + (min(lane, 9) >> 1) * 32 + (min(lane, 9) & 1) * 4;
      sts32(d, silu2(cv.x)); sts32(d + 8, silu2(cv.y)); sts32(d + 16, silu2(cv.z)); sts32(d + 24, silu2(cv.w));
      __syncwarp();
    }
    uint4* const trow = P.T + rho(bid) * TROW;
    uint32_t mu0 = 0;
    if (main_cta) {
      while (clk() - t0 < XDELAY) {}
      __syncwarp();
      mu0 = tc_tick();
      const uint4* src = reinterpret_cast<const uint4*>(P.x + (size_t)(bid + 128 * (warp + 8 * (lane >> 4))) * 640) + (lane & 15);
#pragma unroll
      for (int i = 0; i < 5; i++) asm volatile("cp.async.cg.shared.global [%0], [%1], 16;" :: "r"(sb + OFF_XS + warp * 2560 + (lane >> 4) * 1280 + (lane & 15) * 16 + i * 256 + (i == 4 ? mu0 : 0)), "l"(src + i * 16) : "memory");
    }
    PT(18);
    asm volatile("setmaxnreg.inc.sync.aligned.u32 224;");
    asm volatile("barrier.cluster.wait.aligned;" ::: "memory");
    const int s0 = bid, p = warp;
    const uint32_t xs = sb + OFF_XS + p * 2560, ex = sb + OFF_EX;
    const uint32_t lo = (lane >> 4) * 1280 + ((lane & 7) * 2 + ((lane >> 3) & 1)) * 80;
    const uint32_t exm = ex + (p + 8 * ((lane >> 3) & 1)) * EX_TOK + (lane & 7) * EX_SLOT + (lane >> 4) * 16;
    const uint32_t lt = sb + OFF_LANE + lane * 16;
    uint32_t mu2a = 0, mu2b = 0, epoch;
    uint4 K[12];
    if (main_cta) {
      mbar_wait(bars + 8 * BAR_TAB, 0);
      uint4 tw[10], AJ, FS[4];
#pragma unroll
      for (int i = 0; i < 10; i++) tw[i] = lds128(lt + i * 512);
      AJ = lds128(sb + lane * 16);
#pragma unroll
      for (int i = 0; i < 4; i++) FS[i] = lds128(sb + lane * 16 + (warp ? 512 : 2560) + i * 512);
      PT(24);
      if (bid < 80) {
        uint32_t a[5][4]; uint2 b[5];
        const uint32_t wp = sb + 7 * STAGE - 10240 + (warp * 80 + (lane & 7) + (lane >> 4) * 8) * 32 + (lane & 8) * 2;
#pragma unroll
        for (int k = 0; k < 5; k++) b[k] = lds64(sb + OFF_SILU + warp * 160 + t * 8 + 32 * k);
        mbar_wait(bars + 8 * (BAR_MA + warp), 0);
        PT(25);
#pragma unroll
        for (int k = 0; k < 5; k++) ldsm4t(a[k], wp + 512 * k);
        float c0[4], c1[4];
        mma16816z(c0, a[0][0], a[0][1], a[0][2], a[0][3], b[0].x, b[0].y); mma16816z(c1, a[1][0], a[1][1], a[1][2], a[1][3], b[1].x, b[1].y);
        mma16816(c0, a[2][0], a[2][1], a[2][2], a[2][3], b[2].x, b[2].y); mma16816(c1, a[3][0], a[3][1], a[3][2], a[3][3], b[3].x, b[3].y);
        mma16816(c0, a[4][0], a[4][1], a[4][2], a[4][3], b[4].x, b[4].y);
        if (t < 2) sts32(sb + OFF_RED + (g + 8 * t) * 32 + warp * 4, __float_as_uint(t ? c0[2] + c1[2] : c0[0] + c1[0]));
        __syncwarp();
        bar_arrive(2, 288);
      }
      uint32_t hb[5][4];
      {
        asm volatile("cp.async.wait_all;" ::: "memory");
        __syncwarp();
        PT(28);
        const uint32_t co = (lane >> 4) * 128 + (lane & 7) * 16;
        float sm[4] = {0.f, 0.f, 0.f, 0.f};
#pragma unroll
        for (int m = 0; m < 5; m++) {
          ldsm4(hb[m], xs + ((lane >> 3) & 1) * 1280 + co + 256 * m);
          mma16816(sm, hb[m][0], hb[m][1], hb[m][2], hb[m][3], 0x3f803f80u, 0x3f803f80u);
        }
#pragma unroll
        for (int o = 4; o < 32; o <<= 1) { sm[0] += __shfl_xor_sync(~0u, sm[0], o); sm[2] += __shfl_xor_sync(~0u, sm[2], o); }
        mu2a = pack2(sm[0] * (1.f / 640.f), sm[0] * (1.f / 640.f)); mu2b = pack2(sm[2] * (1.f / 640.f), sm[2] * (1.f / 640.f));
        LnAcc A = {};
#pragma unroll
        for (int m = 0; m < 5; m++) {
          const uint32_t b0 = hb[m][1];
          hb[m][0] = hsub2(hb[m][0], mu2a); hb[m][1] = hsub2(hb[m][2], mu2a); hb[m][2] = hsub2(b0, mu2b); hb[m][3] = hsub2(hb[m][3], mu2b);
          ln_step(A, hb[m]);
        }
        ln_finish(A, g, hb);
#pragma unroll
        for (int m = 0; m < 5; m++) stsm4(ex + (p + (lane & 8)) * 1296 + co + 256 * m, hb[m][0], hb[m][2], hb[m][1], hb[m][3]);
        bar_sync(1, 256);
        const uint32_t ja = ex + (lane & 15) * 1296 + warp * 160 + (lane >> 4) * 16;
#pragma unroll
        for (int m = 0; m < 5; m++) ldsm4t(hb[m], ja + 32 * m);
        __syncwarp();
#pragma unroll
        for (int m = 0; m < 5; m++) {
          float c0[4], c1[4];
          mma16816z(c0, AJ.x, AJ.y, AJ.z, AJ.w, hb[m][0], hb[m][1]); mma16816z(c1, AJ.x, AJ.y, AJ.z, AJ.w, hb[m][2], hb[m][3]);
          stsm4(ja + 32 * m, pack2(c0[0], c0[1]), pack2(c0[2], c0[3]), pack2(c1[0], c1[1]), pack2(c1[2], c1[3]));
        }
        bar_sync(1, 256);
#pragma unroll
        for (int m = 0; m < 5; m++) ldsm4t(hb[m], ex + (p + (lane >> 4) * 8) * 1296 + (lane & 15) * 80 + 16 * m);
      }
      const uint32_t ob = sb + OFF_MB + warp * 3232;
      uint32_t aF, aS, bF, bS;
      {
        const int cl = 16 * t + 8 * (t >> 1), ch = 16 * (19 - t) + 8 * ((19 - t) >> 1);
        aF = ob + (cl + g) * 4; aS = g ? aF + 1616 : aF + 32;
        bF = g ? ob + (ch + 16 - g) * 4 + (warp ? 1616 : 0) : ob + 1616 + (16 * (20 - t) + 8 * ((20 - t) >> 1)) * 4;
        bS = g ? ob + (ch + 16 - g) * 4 + (warp ? 0 : 1616) : ob + 1616 + (ch + 8) * 4;
      }
      const int u0 = 10 * (lane >> 3) + (lane & 7), u4 = 10 * g + 8 + (lane & 1), kB = warp ? 16 - warp : 8;
      const uint32_t la0 = ob + (u0 + 2 * (u0 >> 3)) * 16, la4 = ob + (u4 + 2 * (u4 >> 3)) * 16;
      uint4* const oA = trow + warp * 64 + (lane ^ (2 * (warp & 3))); uint4* const oB = trow + kB * 64 + (lane ^ (2 * (kB & 3))); uint4* const o4 = trow + 1024 + g * 32 + warp * 4 + t;
      const uint32_t ma = (lane < 16 && warp) ? sb + OFF_ZERO : sb + OFF_MODA + lane * 80;
      PT(2);
      bar_sync(13, 352);
      {
        uint32_t af[5][4], mv[5][4];
        float acc[40];
        const uint64_t dm = mkdesc(sb + OFF_M40, 128, 1280, 0);
#pragma unroll
        for (int m = 0; m < 5; m++) ldsm4t(mv[m], ma + 16 * m);
        const uint32_t tagA = mk_tag(3 * lds32(sb + OFF_ROLE + 4) + 1);
#pragma unroll
        for (int m = 0; m < 5; m++) {
          const uint32_t a0 = hfma2(hb[m][0], mv[m][2], mv[m][0]), a1 = hfma2(hb[m][1], mv[m][3], mv[m][1]), b0 = hmul2(hb[m][2], mv[m][2]), b1 = hmul2(hb[m][3], mv[m][3]);
          float f[4], sc[4];
          mma16816z(f, FS[0].x, FS[0].y, FS[0].z, FS[0].w, a0, a1); mma16816z(sc, FS[2].x, FS[2].y, FS[2].z, FS[2].w, a0, a1);
          mma16816(f, FS[1].x, FS[1].y, FS[1].z, FS[1].w, b0, b1); mma16816(sc, FS[3].x, FS[3].y, FS[3].z, FS[3].w, b0, b1);
          float fr[2], fi[2], sr[2], si[2];
#pragma unroll
          for (int e = 0; e < 2; e++) {
            const float c1 = __uint_as_float(tw[2 * m + e].x), s1 = __uint_as_float(tw[2 * m + e].y), c2 = __uint_as_float(tw[2 * m + e].z), s2 = __uint_as_float(tw[2 * m + e].w);
            fr[e] = f[e] * c1 + f[2 + e] * s1; fi[e] = f[2 + e] * c1 - f[e] * s1;
            sr[e] = sc[e] * c2 + sc[2 + e] * s2; si[e] = sc[2 + e] * c2 - sc[e] * s2;
          }
          af[m][0] = pack2(fr[0], fr[1]); af[m][1] = pack2(sr[0], sr[1]); af[m][2] = pack2(fi[0], fi[1]); af[m][3] = pack2(si[0], si[1]);
        }
        WG_FENCE;
#pragma unroll
        for (int m = 0; m < 5; m++) wgmma_rs_n80(acc, af[m][0], af[m][1], af[m][2], af[m][3], dm + 16 * m, m > 0);
        WG_COMMIT; WG_WAIT(0);
        PT(4);
#pragma unroll
        for (int nt = 0; nt < 5; nt++) {
          const uint32_t w0 = pack2(acc[4 * nt], acc[4 * nt + 1]), w1 = pack2(acc[20 + 4 * nt], acc[21 + 4 * nt]);
          sts32(aF + 320 * nt, w0); sts32(aS + 320 * nt, pack2(acc[4 * nt + 2], acc[4 * nt + 3]));
          sts32(bF - 320 * nt, w1); sts32(bS - 320 * nt, pack2(acc[22 + 4 * nt], acc[23 + 4 * nt]));
          if (nt == 0 && lane == 0) { sts32(ob + 1616, w0 ^ 0x80000000u); sts32(ob + 1600, w1 ^ 0x80000000u); }
        }
        __syncwarp();
        uint4 q[5];
        q[0] = lds128(la0); q[1] = lds128(la0 + 800); q[2] = lds128(la0 + 1616); q[3] = lds128(la0 + 2416); q[4] = lds128(la4 + (t >> 1) * 1616);
        uint32_t qo = lds32(la4 + 1616 - (t >> 1) * 1616), qz = lds32(ob + 1600 + (lane & 1) * 1616);
        if (warp == 0) {
          if (!(lane & 1)) {
#pragma unroll
            for (int i = 0; i < 2; i++) { const uint32_t pp = q[i].x, qq = q[2 + i].x; q[i].x = hadd2(pp, qq); q[2 + i].x = __byte_perm(hsub2(pp, qq), 0, 0x1032) ^ 0x80000000u; }
            q[4].x = t ? __byte_perm(hsub2(qo, q[4].x), 0, 0x1032) ^ 0x80000000u : hadd2(q[4].x, qo);
          }
          qz = hadd2(qz, qz);
          qz = (lane & 1) ? (qz >> 16) ^ 0x8000u : qz & 0xffffu;
        }
        st_unit(oA, tag_unit(q[0], tagA)); st_unit(oA + 32, tag_unit(q[1], tagA));
        st_unit(oB, tag_unit(q[2], tagA)); st_unit(oB + 32, tag_unit(q[3], tagA));
        st_unit(o4, tag_unit(q[4], tagA));
        if (lane < 2) st_unit(trow + 1280 + 2 * warp + lane, make_uint4(0, 0, 0, tag_word(qz, tagA)));
        __syncwarp();
        bar_arrive(8, 288);
      }
    }
    PT(5);
    {
      const int rl = rho(8 * t + g), r0 = rho(8 * g + 2 * t);
      const uint32_t la = ex + rl * 128 + (((warp ^ rl) & 7) << 4), la5 = ex + 16384 + rl * 32 + (((warp ^ rl) & 4) << 2) + (warp & 3) * 4;
      const uint32_t so0 = ex + r0 * 128 + (((warp ^ r0) & 7) << 4), so5 = ex + 16384 + r0 * 32 + (((warp ^ r0) & 4) << 2) + (warp & 3) * 4;
      float wr[5][4], wi[5][4];
      const int zkj = slot_kj((bid & 1) * 8 + warp);
      {
        mbar_wait(bars + 8 * BAR_WD, 0);
#pragma unroll
        for (int i = 0; i < 12; i++) K[i] = lds128(sb + (main_cta ? OFF_CC : zkj * 6144) + lane * 16 + i * 512);
      }
      const uint32_t wb = sb + OFF_WF + (g + 32 * t) * 176 + ((bid >> 3) & 6) * 2 + rank * 80, wa = wb + (warp ^ ((bid >> 2) & 6)) * 8, wa5 = wb + 64 + warp * 2 + ((bid >> 3) & 1) * 2;
      const uint32_t se = (bid & 8) ? 0x3244 : 0x1044, so = (bid & 8) ? 0x5444 : 0x3244;
      mbar_wait(bars + 8 * BAR_WF, 0);
#pragma unroll
      for (int i = 0; i < 4; i++)
#pragma unroll
        for (int z = 0; z < 2; z++) {
          const uint32_t o = (8 * (i >> 1) + 16 * (i & 1)) * 176 + z * WSZ;
          const uint32_t u0 = lds32(wa + o), u1 = lds32(wa + o + 4), u2 = lds32(wa + o + 8), u5 = lds16(wa5 + o);
          float (&w)[5][4] = z ? wi : wr;
          w[0][i] = __uint_as_float(__byte_perm(u0, 0, se)); w[1][i] = bhi(__byte_perm(u0, u1, so));
          w[2][i] = __uint_as_float(__byte_perm(u1, 0, se)); w[3][i] = bhi(__byte_perm(u1, u2, so)); w[4][i] = blo(u5);
        }
      if (!main_cta) {
#pragma unroll
        for (int i = 0; i < 4; i++) {
          const uint32_t a = sb + OFF_MB + warp * 4096 + (zkj & 7) * 2 + (g + 32 * t + 8 * (i >> 1) + 16 * (i & 1)) * 16;
          wr[3][i] = blo(lds16(a)); wi[3][i] = blo(lds16(a + 2048));
        }
      }
      PT(20);
      uint32_t x[5][4];
      const bool w3 = (warp & 3) == 3;
      {
        int it = 0; uint32_t bad;
#pragma unroll 1
        do {
          mbar_wait(bars + 8 * (BAR_MA + 3), ~it & 1);
          PT(7);
          epoch = lds32(sb + OFF_ROLE + 4);
          const uint32_t tagA = mk_tag(3 * epoch + 1);
          bad = 0;
#pragma unroll
          for (int i = 0; i < 4; i++) {
            uint4 q = lds128(la + i * 4096); x[0][i] = q.x; x[1][i] = q.y; x[2][i] = q.z; x[3][i] = q.w; x[4][i] = lds32(la5 + i * 1024);
            tag_acc(bad, q, tagA);
            if (w3 && main_cta) bad |= x[4][i] ^ tagA;
          }
          if (it == 0 && main_cta) bar_arrive(11, 288);
      const float tcs[4] = {__uint_as_float(K[7].x), __uint_as_float(K[7].y), __uint_as_float(K[7].z), __uint_as_float(K[7].w)};
      const float ts[4] = {__uint_as_float(K[8].x), __uint_as_float(K[8].y), __uint_as_float(K[8].z), __uint_as_float(K[8].w)};
      const float uc[4] = {__uint_as_float(K[9].x), __uint_as_float(K[9].y), __uint_as_float(K[9].z), __uint_as_float(K[9].w)};
      const float us[4] = {__uint_as_float(K[10].x), __uint_as_float(K[10].y), __uint_as_float(K[10].z), __uint_as_float(K[10].w)};
      const uint32_t c8 = K[11].x, s8 = K[11].y, ns8 = K[11].z;
      float R[5][4], I[5][4];
#pragma unroll
      for (int q = 0; q < 5; q++) {
        mma16816z(R[q], K[0].x, K[0].y, K[0].z, K[0].w, x[q][0], x[q][1]);
        mma16816z(I[q], K[2].x, K[2].y, K[2].z, K[2].w, x[q][0], x[q][1]);
      }
#pragma unroll
      for (int q = 0; q < 5; q++) {
        mma16816(R[q], K[1].x, K[1].y, K[1].z, K[1].w, x[q][2], x[q][3]);
        mma16816(I[q], K[3].x, K[3].y, K[3].z, K[3].w, x[q][2], x[q][3]);
      }
#pragma unroll
      for (int q = 0; q < 5; q++) {
        float pp[4], qq[4];
#pragma unroll
        for (int i = 0; i < 4; i++) { pp[i] = R[q][i] * tcs[i] + I[q][i] * ts[i]; qq[i] = I[q][i] * tcs[i] - R[q][i] * ts[i]; }
        uint32_t a0 = pack2(pp[0], pp[1]), a1 = pack2(pp[2], pp[3]), a2 = pack2(qq[0], qq[1]), a3 = pack2(qq[2], qq[3]);
        mma16816z(R[q], a0, a1, a2, a3, c8, s8);
        mma16816z(I[q], a0, a1, a2, a3, ns8, K[11].w);
      }
#pragma unroll
      for (int q = 0; q < 5; q++) {
        float pp[4], qq[4];
#pragma unroll
        for (int i = 0; i < 4; i++) { pp[i] = R[q][i] * wr[q][i] - I[q][i] * wi[q][i]; qq[i] = R[q][i] * wi[q][i] + I[q][i] * wr[q][i]; }
        mma16816z(R[q], c8, s8, ns8, K[11].w, pack2(pp[0], pp[1]), pack2(qq[0], qq[1]));
        mma16816z(I[q], c8, s8, ns8, K[11].w, pack2(pp[2], pp[3]), pack2(qq[2], qq[3]));
      }
#pragma unroll
      for (int q = 0; q < 5; q++) {
        x[q][0] = pack2(R[q][0] * uc[0] - R[q][2] * us[0], R[q][1] * uc[1] - R[q][3] * us[1]);
        x[q][1] = pack2(I[q][0] * uc[2] - I[q][2] * us[2], I[q][1] * uc[3] - I[q][3] * us[3]);
        x[q][2] = pack2(R[q][0] * us[0] + R[q][2] * uc[0], R[q][1] * us[1] + R[q][3] * uc[1]);
        x[q][3] = pack2(I[q][0] * us[2] + I[q][2] * uc[2], I[q][1] * us[3] + I[q][3] * uc[3]);
        mma16816z(R[q], K[4].x, K[4].y, K[4].z, K[4].w, x[q][0], x[q][1]);
        mma16816z(I[q], K[5].x, K[5].y, K[5].z, K[5].w, x[q][0], x[q][1]);
      }
#pragma unroll
      for (int q = 0; q < 5; q++) {
        mma16816(R[q], K[6].x, K[6].y, K[6].z, K[6].w, x[q][2], x[q][3]);
        mma16816(I[q], K[4].x, K[4].y, K[4].z, K[4].w, x[q][2], x[q][3]);
      }
      const uint32_t tagB = mk_tag(3 * epoch + 2);
#pragma unroll
      for (int i = 0; i < 4; i++) {
        sts128((so0 ^ ((i & 1) * 576)) + (i >> 1) * 8192, make_uint4(pack2(R[0][i], I[0][i]), pack2(R[1][i], I[1][i]), pack2(R[2][i], I[2][i]), tag_word(pack2(R[3][i], I[3][i]), tagB)));
        const uint32_t w5 = pack2(R[4][i], I[4][i]);
        sts32((so5 ^ ((i & 1) * 144)) + (i >> 1) * 2048, w3 ? tag_word(w5, tagB) : w5);
      }
        } while (bar_or(14, 288, bad & TMASK) && ++it < SPIN);
        PSET(29, it);
      }
      PT(8);
    }
    if (!main_cta) {
      asm volatile("barrier.cluster.arrive.relaxed.aligned;" ::: "memory");
      asm volatile("barrier.cluster.wait.aligned;" ::: "memory");
      PT(17); PDUMP();
      return;
    }
    const uint32_t tagC = mk_tag(3 * epoch + 3);
    uint32_t th2, g0rdy; int role;
    mbar_wait(bars + 8 * BAR_MA, 1);
    PT(1);
    if (bid >= 48) {
      uint32_t a[10][4]; uint2 b[10];
      const uint32_t wp = sb + OFF_MB + ((warp >> 2) * 160 + (lane & 7) + (lane >> 4) * 8) * 128 + (((2 * (warp & 3) + ((lane >> 3) & 1)) ^ (lane & 7)) << 4);
#pragma unroll
      for (int k = 0; k < 10; k++) { ldsm4t(a[k], wp + 2048 * k); b[k] = lds64(sb + OFF_SILU + (rank * 2 + (warp >> 2)) * 320 + t * 8 + 32 * k); }
      float c0[4], c1[4];
      mma16816z(c0, a[0][0], a[0][1], a[0][2], a[0][3], b[0].x, b[0].y); mma16816z(c1, a[1][0], a[1][1], a[1][2], a[1][3], b[1].x, b[1].y);
#pragma unroll
      for (int k = 2; k < 10; k++) mma16816((k & 1) ? c1 : c0, a[k][0], a[k][1], a[k][2], a[k][3], b[k].x, b[k].y);
      uint32_t ra, rbar;
      asm volatile("mapa.shared::cluster.u32 %0, %1, 0;" : "=r"(ra) : "r"(sb + OFF_RED + ((warp & 3) * 16 + g + 8 * t) * 16 + (rank * 2 + (warp >> 2)) * 4));
      asm volatile("mapa.shared::cluster.u32 %0, %1, 0;" : "=r"(rbar) : "r"(bars + 8 * (BAR_MA + 1)));
      if (t < 2) asm volatile("st.async.shared::cluster.mbarrier::complete_tx::bytes.b32 [%0], %1, [%2];" :: "r"(ra), "r"(__float_as_uint(t ? c0[2] + c1[2] : c0[0] + c1[0])), "r"(rbar) : "memory");
    }
    __syncwarp();
    bar_arrive(2, 288);
    bar_arrive(3, 288);
    {
      uint4 tw[10], A1, FJ[4];
      A1 = lds128(lt + 10 * 512);
#pragma unroll
      for (int i = 0; i < 4; i++) FJ[i] = lds128(lt + (11 + i) * 512);
      uint32_t da[5][2], dq0, dq4;
      {
        const uint32_t tb = ex + g * EX_TOK;
        const int k0 = 40 * warp + 8 * t, k4 = 40 * warp + 32 + 2 * t;
        col_off2(k0, da[0][0], dq0); col_off2(k4, da[4][0], dq4);
        da[0][0] += tb; dq0 += tb; da[4][0] += tb; dq4 += tb; da[4][1] = tb + col_off(k4 + 1);
        const uint32_t a1 = tb + col_off(k0 + 1), stp = (k0 & 8) ? -EX_SLOT : EX_SLOT;
#pragma unroll
        for (int j = 1; j < 8; j++) da[j & 3][j >> 2] = a1 + (j - 1) * stp;
      }
      const uint32_t tp = sb + OFF_MB + (t * 64 + warp * 8 + (g ^ (2 * t))) * 16, tp4 = sb + OFF_MB + (1024 + warp * 32) * 16 + g * 4;
      const int zo[4] = {2 * t, 2 * t + 8, t ? 17 - 2 * t : 1, 9 - 2 * t};
      const uint32_t ho = ex + g * 2560 + p * 64 + t * 16;
      uint32_t xr[5][4], ga[5][2], sc2[5][4];
#pragma unroll
      for (int i = 0; i < 10; i++) tw[i] = lds128(lt + i * 512);
#pragma unroll
      for (int m = 0; m < 5; m++) ldsm4(xr[m], xs + lo + 16 * m);
      PT(9);
      {
        const uint32_t tagB = mk_tag(3 * epoch + 2);
        uint32_t b[5][4], vz[4], bad;
        int it = 0;
#pragma unroll 1
        do {
          mbar_wait(bars + 8 * (BAR_MA + 2), ~it & 1);
          PT(21);
          uint32_t b4 = 0;
          bad = 0;
#pragma unroll
          for (int q = 0; q < 4; q++) {
            const uint4 v = lds128(tp + 4096 * q);
            b[0][q] = v.x; b[1][q] = v.y; b[2][q] = v.z; b[3][q] = v.w;
            b[4][q] = lds32(tp4 + zo[q] * 32); vz[q] = lds32(sb + OFF_MB + 1280 * 16 + 12 + zo[q] * 16);
            bad |= (v.w ^ tagB) | (vz[q] ^ tagB); b4 |= b[4][q] ^ tagB;
          }
          if ((g & 3) == 3) bad |= b4;
        float ca[5][4], cb[5][4], za[4], zb[4];
        mma16816z(za, FJ[0].x, FJ[0].y, FJ[0].z, FJ[0].w, vz[0], vz[1]); mma16816z(zb, FJ[2].x, FJ[2].y, FJ[2].z, FJ[2].w, vz[0], vz[1]);
        mma16816(za, FJ[1].x, FJ[1].y, FJ[1].z, FJ[1].w, vz[2], vz[3]); mma16816(zb, FJ[3].x, FJ[3].y, FJ[3].z, FJ[3].w, vz[2], vz[3]);
        if (g == warp) sts32(ex + g * EX_TOK + 80, pack2(za[0], -zb[0]));
#pragma unroll
        for (int i = 0; i < 5; i++) {
          mma16816z(ca[i], FJ[0].x, FJ[0].y, FJ[0].z, FJ[0].w, b[i][0], b[i][1]);
          mma16816z(cb[i], FJ[2].x, FJ[2].y, FJ[2].z, FJ[2].w, b[i][0], b[i][1]);
        }
#pragma unroll
        for (int i = 0; i < 5; i++) {
          mma16816(ca[i], FJ[1].x, FJ[1].y, FJ[1].z, FJ[1].w, b[i][2], b[i][3]);
          mma16816(cb[i], FJ[3].x, FJ[3].y, FJ[3].z, FJ[3].w, b[i][2], b[i][3]);
        }
        {
          const bool real = (warp | t) == 0;
          float ai = real ? 0.f : ca[0][2], bi = real ? 0.f : cb[0][2];
          sts32(da[0][0], pack2(ca[0][0] - bi, ai + cb[0][0])); sts32(dq0, pack2(ca[0][0] + bi, ai - cb[0][0]));
          uint32_t pp = pack2(ca[4][0] - cb[4][2], ca[4][2] + cb[4][0]), qq = pack2(ca[4][0] + cb[4][2], ca[4][2] - cb[4][0]);
          sts32(da[4][0], t ? pack2(ca[4][0], ca[4][2]) : pp); sts32(dq4, t ? pack2(cb[4][0], cb[4][2]) : qq);
        }
#pragma unroll
        for (int i = 0; i < 5; i++)
#pragma unroll
          for (int e = 0; e < 2; e++)
            if (e == 1 || (i > 0 && i < 4)) { sts32(da[i][e], pack2(ca[i][e], ca[i][2 + e])); sts32(da[i][e] + 8 * EX_TOK, pack2(cb[i][e], cb[i][2 + e])); }
          PT(10);
          if (!bar_or(1, 256, bad & TMASK)) break;
          if (warp == 0) bulk_g2s_e(sb + OFF_MB, trow, TROW * 16, bars + 8 * (BAR_MA + 2));
          __syncwarp();
        } while (++it < SPIN);
        PSET(27, it);
        if (warp == 7) bar_arrive(12, 64);
      }
      float acc[40];
      {
        uint32_t af[5][4];
#pragma unroll
        for (int m = 0; m < 5; m++) ldsm4(af[m], exm + 32 * m);
        const uint64_t dm = mkdesc(sb + OFF_M40, 1280, 128, 0);
        WG_FENCE;
#pragma unroll
        for (int m = 0; m < 5; m++) wgmma_rs_n80_tb(acc, af[m][0], af[m][1], af[m][2], af[m][3], dm + 160 * m, m > 0);
        WG_COMMIT;
        WG_WAIT(0);
      }
      PT(22);
      uint32_t x1[5][4], d[5][4], tb[5][4];
#pragma unroll
      for (int m = 0; m < 5; m++) {
        float f0[2], f1[2], g0[2], g1[2];
#pragma unroll
        for (int e = 0; e < 2; e++) {
          const float c1 = __uint_as_float(tw[2 * m + e].x), s1 = __uint_as_float(tw[2 * m + e].y), c2 = __uint_as_float(tw[2 * m + e].z), s2 = __uint_as_float(tw[2 * m + e].w);
          float fr = acc[8 * m + e], fi = acc[8 * m + 4 + e], sr = acc[8 * m + 2 + e], si = acc[8 * m + 6 + e];
          f0[e] = fr * c1 - fi * s1; f1[e] = fr * s1 + fi * c1; g0[e] = sr * c2 - si * s2; g1[e] = sr * s2 + si * c2;
        }
        const uint32_t pf = pack2(f1[0], f1[1]), pg = pack2(g0[0], g0[1]);
        tb[m][0] = movm(pack2(f0[0], f0[1])); tb[m][1] = movm(g ? pf : pg); tb[m][2] = movm(g ? pg : pf); tb[m][3] = movm(pack2(g1[0], g1[1]));
      }
      PT(3);
      bar_sync(4 + ((tb[4][3] | tb[3][0]) & blockIdx.y), 352);
#pragma unroll
      for (int m = 0; m < 5; m++) ldsm2(ga[m], sb + OFF_MODB + lo + 16 * m);
#pragma unroll
      for (int m = 0; m < 5; m++) ldsm4(sc2[m], sb + OFF_MODB + 1280 + lo + 16 * m);
      role = lds32(sb + OFF_ROLE);
      g0rdy = mbar_test(bars + 8 * BAR_FULL, 0) & mbar_test(bars + 8 * BAR_FULL + 8, 0) & mbar_test(bars + 8 * BAR_FULL + 16, 0) & mbar_test(bars + 8 * BAR_FULL + 24, 0);
      sts32(exm, 0);
      LnAcc A = {};
#pragma unroll
      for (int m = 0; m < 5; m++) {
        float ya[4], yb[4];
        mma16816z(ya, A1.x, A1.y, A1.z, A1.w, tb[m][0], tb[m][1]);
        mma16816z(yb, A1.x, A1.y, A1.z, A1.w, tb[m][2], tb[m][3]);
#pragma unroll
        for (int hh = 0; hh < 2; hh++) {
          x1[m][hh] = hfma2(ga[m][hh], pack2(ya[2 * hh], ya[2 * hh + 1]), xr[m][hh]);
          x1[m][2 + hh] = hfma2(ga[m][hh], pack2(yb[2 * hh], yb[2 * hh + 1]), xr[m][2 + hh]);
          d[m][hh] = hsub2(x1[m][hh], mu2a); d[m][2 + hh] = hsub2(x1[m][2 + hh], mu2b);
        }
        ln_step(A, d[m]);
      }
#pragma unroll
      for (int i = 0; i < 5; i++) {
        const int u0 = 2 * i, u1 = 2 * i + 1;
        sts128(ho + (OFF_XS - OFF_EX) + i * 512, make_uint4(x1[u0 % 5][u0 / 5], x1[u0 % 5][2 + u0 / 5], x1[u1 % 5][u1 / 5], x1[u1 % 5][2 + u1 / 5]));
      }
      ln_finish(A, g, d);
      uint32_t h2[10][2];
#pragma unroll
      for (int uu = 0; uu < 10; uu++) {
        const int m = uu % 5, hh = uu / 5;
        h2[uu][0] = hfma2(d[m][hh], sc2[m][2 + hh], sc2[m][hh]);
        h2[uu][1] = hfma2(d[m][2 + hh], sc2[m][2 + hh], sc2[m][hh]);
        if (uu & 1) st_unit(trow + 160 * g + 4 * p + t + (uu >> 1) * 32, tag_unit(make_uint4(h2[uu - 1][0], h2[uu - 1][1], h2[uu][0], h2[uu][1]), tagC));
      }
      th2 = clk();
      PT(11); PT2(11);
    }
    const int rb = (role >> 2) & 15, nq = role & 3, kh = role >> 6;
    const int wg = warp >> 2, rt = (wg ^ kh ^ 1) * 4 + (warp & 3);
    const bool late0 = wg && lane == 0;
    const int nrel = wg ? 1 : 4, src = rb * 8 + rt;
    {
      uint4 a[40];
      const uint4* ap = P.T + rho(rb * 8 + rt) * TROW + lane;
      if (!g0rdy) {
#pragma unroll 1
        for (int i = 0; i < 4; i++) mbar_wait(bars + 8 * (BAR_FULL + i), 0);
      }
      while (clk() - th2 < A_DELAY) {}
      { const uint32_t* pp = reinterpret_cast<const uint32_t*>(ap + 39 * 32) + 3; int it = 0;
        while (__any_sync(~0u, (ld_relaxed(pp) ^ tagC) & TMASK) && ++it < SPIN) {} }
      PT(12); PT2(12);
      if (wg == 1) { bar_arrive(6, 256); bar_sync(8, 256); }
      {
        int it = 0; uint32_t bad;
#pragma unroll 1
        do {
          uload<0, 20, 32>(a, ap);
          if (it == 0 && wg == 0) bar_arrive(8, 256);
          bad = 0;
#pragma unroll
          for (int k = 0; k < 20; k++) tag_acc(bad, a[k], tagC);
        } while (__any_sync(~0u, bad & TMASK) && ++it < SPIN);
      }
      PT(13);
      if (warp == 0) stsv(sb + OFF_EV, 2);
      const uint32_t hst = sb + ((warp & 3) == 3 ? OFF_MODB : OFF_HST + (warp & 3) * 2048) + (lane & 8) * 128 + (lane >> 4) * 128 + (lane & 7) * 16;
      uint32_t gl[16];
#pragma unroll
      for (int j = 0; j < 16; j++) gl[j] = 0;
#pragma unroll 1
      for (int c = 0; c < 6; c++) {
        float acc[32];
        const uint32_t fb = bars + 8 * BAR_FULL + (c & 1) * 32;
        const uint64_t db = mkdesc(sb + (c & 1) * 4 * STAGE, 1024, 1024, 1);
        if (c && !wg && !(mbar_test(fb, (c >> 1) & 1) & mbar_test(fb + 8, (c >> 1) & 1) & mbar_test(fb + 16, (c >> 1) & 1) & mbar_test(fb + 24, (c >> 1) & 1))) {
#pragma unroll 1
          for (int i = 0; i < 4; i++) mbar_wait(fb + 8 * i, (c >> 1) & 1);
        }
        PWAIT(w_turn, bar_sync(6 + wg, 256));
        WG_FENCE;
#pragma unroll
        for (int i = 0; i < 4; i++) {
          if (i == 2) {
            if (c == 0) {
              bar_arrive(7 - wg, 256);
              int it = 0; uint32_t bad;
#pragma unroll 1
              do {
                uload<20, 40, 32>(a, ap);
                bad = 0;
#pragma unroll
                for (int k = 20; k < 40; k++) tag_acc(bad, a[k], tagC);
              } while (__any_sync(~0u, bad & TMASK) && ++it < SPIN);
              PT2(10);
              bar_arrive(5, 288);
              bar_sync(6 + wg, 256);
            }
            WG_FENCE;
          }
#pragma unroll
          for (int k = 10 * i; k < 10 * i + 10; k++) {
            wgmma_rs_n64_tb(acc, a[k].x, a[k].y, a[k].z, a[k].w, db + 128 * k, k != 0);
            if (k == 30 + HANDOFF) { if (wg == 0 || c < 5) bar_arrive(7 - wg, 256); }
          }
          WG_COMMIT;
          if (i > 0) { WG_WAIT(1); mbar_arrive_if(fb + 64 + 8 * (i - 1), late0); }
        }
        WG_WAIT(0);
        PT2(1 + c);
        mbar_arrive_if(fb + 64 + 24 - 8 * lane, lane < nrel);
        if (c == 4 - wg) {
          mbar_wait(bars + 8 * BAR_HF, 0);
        }
        if (!(c & 1)) {
#pragma unroll
          for (int j = 0; j < 16; j++) gl[j] = j < NG ? pack2(gelu(acc[2 * j]), gelu(acc[2 * j + 1])) : pack2(acc[2 * j], acc[2 * j + 1]);
        } else {
#pragma unroll
          for (int j = 0; j < 16; j++)
            gl[j] = j < NG ? hmul2(gl[j], pack2(acc[2 * j], acc[2 * j + 1])) : pack2(gelu(blo(gl[j])) * acc[2 * j], gelu(bhi(gl[j])) * acc[2 * j + 1]);
          if (c + wg > 1) bar_sync(10 + wg, 160);
#pragma unroll
          for (int kk = 0; kk < 4; kk++) stsm4(hst + kk * 256, gl[4 * kk], gl[4 * kk + 1], gl[4 * kk + 2], gl[4 * kk + 3]);
          bar_arrive(2 + wg, 160);
        }
      }
    }
    PT(14); PT2(14);
    float acc[80];
    uint4 xw[10];
    uint32_t gb[20];
    const int wt = tid & 127;
    {
      if (wg == 0) {
        const uint4* xp = P.X1 + src * 1280 + nq * 320 + lane;
#pragma unroll
        for (int i = 0; i < 10; i++) xw[i] = __ldcg(xp + 32 * i);
      }
      int hs = 5 * wg, hp = 0, j = 0;
      const uint64_t da0 = mkdesc(sb + OFF_M40, 128, 1024, 0), db0 = mkdesc(sb, 4096, 512, 2);
      const int jh = wg ? 99 : G2_HAND;
#pragma unroll 1
      for (int turn = 0; turn < 2; turn++) {
        const int jend = turn ? 12 : 5;
        const bool relh = lane == 0 && !(turn & wg), relw = lane == 0 && !turn;
        uint32_t r1 = 0, r2 = 0; int ps = 0; bool first = true;
#pragma unroll 1
        for (; j < jend; j++) {
          if (!r1) mbar_wait(bars + 8 * (BAR_FULL + (j & 7)), j < 8);
          if (!r2) mbar_wait(bars + 8 * (BAR_HF + hs), hp);
          const uint64_t da = da0 + hs * 512, db = db0 + (j & 7) * (STAGE / 16);
          WG_FENCE;
          wgmma_ss_n160_tb(acc, da, db, j);
          const int pps = ps;
          ps = hs;
          if (++hs == 7) { hs = 0; hp ^= 1; }
          asm volatile("{\n.reg .pred p;\nsetp.eq.s32 p, %0, %1;\n@p bar.arrive 7, 256;\n}" :: "r"(j), "r"(jh) : "memory");
          wgmma_ss_n160_tb(acc, da + 16, db + 64, 1);
          r1 = mbar_test(bars + 8 * (BAR_FULL + ((j + 1) & 7)), j < 7); r2 = mbar_test(bars + 8 * (BAR_HF + hs), hp);
          wgmma_ss_n160_tb(acc, da + 32, db + 128, 1);
          wgmma_ss_n160_tb(acc, da + 48, db + 192, 1);
          WG_COMMIT;
          WG_WAIT(1);
          mbar_arrive_if(bars + 8 * (BAR_HE + pps), relh && !first);
          mbar_arrive_if(bars + 8 * (BAR_EMPTY - 1 + j), relw && !first);
          first = false;
        }
        if (turn == 0) {
          if (!wg) mbar_wait(bars + 8 * (BAR_HF + 5), 0);
          WG_WAIT(0);
          mbar_arrive_if(bars + 8 * (BAR_HE + ps), lane == 0);
          asm volatile("barrier.cluster.arrive.relaxed.aligned;" ::: "memory");
          PT2(7);
#pragma unroll
          for (int i = 0; i < 5; i++) { const uint4 q = lds128(sb + OFF_GB + t * 80 + 16 * i); gb[4 * i] = q.x; gb[4 * i + 1] = q.y; gb[4 * i + 2] = q.z; gb[4 * i + 3] = q.w; }
          if (wg) bar_sync(7, 256);
          hs = 3; hp = 1 - wg;
          PT2(21);
        }
      }
      PT2(9);
    }
    asm volatile("barrier.cluster.wait.aligned;" ::: "memory");
    const uint32_t pofs = (warp & 3) * 5120 + lane * 16;
    if (wg) {
      mbar_wait_cluster(bars + 8 * BAR_PART, 0);
#pragma unroll
      for (int i = 0; i < 10; i++) xw[i] = lds128(sb + 4 * STAGE + pofs + i * 512);
    }
    PT(16); PT2(16);
    WG_WAIT(0);
    mbar_arrive_if(bars + 8 * (BAR_HE + 16 % 7), wg == 0 && lane == 0);
    PT(15); PT2(15);
#pragma unroll
    for (int i = 0; i < 10; i++) {
      xw[i].x = hfma2(gb[2 * i], pack2(acc[8 * i], acc[8 * i + 1]), xw[i].x); xw[i].y = hfma2(gb[2 * i], pack2(acc[8 * i + 2], acc[8 * i + 3]), xw[i].y);
      xw[i].z = hfma2(gb[2 * i + 1], pack2(acc[8 * i + 4], acc[8 * i + 5]), xw[i].z); xw[i].w = hfma2(gb[2 * i + 1], pack2(acc[8 * i + 6], acc[8 * i + 7]), xw[i].w);
    }
    if (wg == 0) {
      uint32_t rex, rbar, ts = clk();
      asm volatile("mapa.shared::cluster.u32 %0, %1, %2;" : "=r"(rex) : "r"(sb + 4 * STAGE + pofs), "r"(rank ^ 1));
      asm volatile("mapa.shared::cluster.u32 %0, %1, %2;" : "=r"(rbar) : "r"(bars + 8 * BAR_PART), "r"(rank ^ 1));
#pragma unroll
      for (int i = 0; i < 10; i++) {
        asm volatile("st.async.shared::cluster.mbarrier::complete_tx::bytes.v4.b32 [%0], {%1,%2,%3,%4}, [%5];"
                     :: "r"(rex + i * 512), "r"(xw[i].x), "r"(xw[i].y), "r"(xw[i].z), "r"(xw[i].w), "r"(rbar) : "memory");
        if (ST_PACE && (i & 1) && i < 9) { ts += 2 * ST_PACE; while ((int)(clk() - ts) < 0) {} }
      }
    } else {
      const uint32_t st = sb + 4 * STAGE + (warp & 3) * 5120;
      const uint32_t s0a = st + (lane & 15) * 64 + (((lane >> 4) ^ ((lane >> 1) & 3)) << 4), s1a = s0a ^ 32;
      __syncwarp();
#pragma unroll
      for (int i = 0; i < 10; i++) stsm4(((i & 1) ? s1a : s0a) + (i >> 1) * 1024, xw[i].x, xw[i].y, xw[i].z, xw[i].w);
      __syncwarp();
      if (elect1()) {
        fence_async();
        asm volatile("cp.async.bulk.tensor.4d.global.shared::cta.bulk_group [%0, {%2, %2, %3, %4}], [%1];" :: "l"(&tm_o), "r"(st), "r"(0), "r"(5 * nq), "r"(src) : "memory");
        BULK_COMMIT; BULK_WAIT_READ;
      }
      if (wt == 0) st_relaxed(myline, epoch + 1);
    }
    PT(17); PG(30); PDUMP();
  }
}

typedef CUresult (*EncodeFn)(CUtensorMap*, CUtensorMapDataType, cuuint32_t, void*, const cuuint64_t*, const cuuint64_t*, const cuuint32_t*, const cuuint32_t*,
                             CUtensorMapInterleave, CUtensorMapSwizzle, CUtensorMapL2promotion, CUtensorMapFloatOOBfill);
void make_map(EncodeFn enc, CUtensorMap* m, const void* base, int rank, const cuuint64_t* dims, const cuuint64_t* strides, const cuuint32_t* box, CUtensorMapSwizzle sw) {
  cuuint32_t es[4] = {1, 1, 1, 1};
  CUresult r = enc(m, CU_TENSOR_MAP_DATA_TYPE_BFLOAT16, rank, const_cast<void*>(base), dims, strides, box, es, CU_TENSOR_MAP_INTERLEAVE_NONE, sw,
      CU_TENSOR_MAP_L2_PROMOTION_L2_128B, CU_TENSOR_MAP_FLOAT_OOB_FILL_NONE);
  (void)r;
}
}

extern "C" void kernel_launch(void* const* d_in, const int* in_sizes, int n_in, void* d_out, int out_size) {
  (void)in_sizes; (void)n_in; (void)out_size;
  Params P;
  P.x = (const __nv_bfloat16*)d_in[0]; P.wr = (const __nv_bfloat16*)d_in[1]; P.wi = (const __nv_bfloat16*)d_in[2];
  P.wg = (const __nv_bfloat16*)d_in[4]; P.wu = (const __nv_bfloat16*)d_in[5]; P.wd = (const __nv_bfloat16*)d_in[6];
  P.c = (const __nv_bfloat16*)d_in[7]; P.wmod = (const __nv_bfloat16*)d_in[8]; P.out = (__nv_bfloat16*)d_out;
  cudaGetSymbolAddress((void**)&P.T, g_T); cudaGetSymbolAddress((void**)&P.H, g_H); cudaGetSymbolAddress((void**)&P.X1, g_X1);
  cudaGetSymbolAddress((void**)&P.mod, g_mod); cudaGetSymbolAddress((void**)&P.sync, g_sync); cudaGetSymbolAddress((void**)&P.tab, g_tab);
  void* fn = nullptr; cudaDriverEntryPointQueryResult qr;
  cudaGetDriverEntryPoint("cuTensorMapEncodeTiled", &fn, cudaEnableDefault, &qr);
  EncodeFn enc = (EncodeFn)fn;
  CUtensorMap tg, tu, td, twr, twi, tma, tmb, tt8, tt2, tzr, tzi, tmo;
  { cuuint64_t d[4] = {32, 16, 20, 128}, s[3] = {128 * 1280, 64, 1280}; cuuint32_t b[4] = {32, 16, 5, 1};
    make_map(enc, &tmo, P.out, 4, d, s, b, CU_TENSOR_MAP_SWIZZLE_64B); }
  { cuuint64_t d[2] = {TROW * 8, 128}, s[1] = {TROW * 16}; cuuint32_t b[2] = {64, 128}, b2[2] = {16, 128};
    make_map(enc, &tt8, P.T, 2, d, s, b, CU_TENSOR_MAP_SWIZZLE_128B); make_map(enc, &tt2, P.T, 2, d, s, b2, CU_TENSOR_MAP_SWIZZLE_32B); }
  { cuuint64_t d[2] = {3840, 640}, s[1] = {7680}; cuuint32_t b[2] = {16, 80};
    make_map(enc, &tma, P.wmod, 2, d, s, b, CU_TENSOR_MAP_SWIZZLE_NONE);
    cuuint64_t d3[3] = {3840, 160, 4}, s3[2] = {7680, 160 * 7680}; cuuint32_t b3[3] = {64, 160, 2};
    make_map(enc, &tmb, P.wmod, 3, d3, s3, b3, CU_TENSOR_MAP_SWIZZLE_128B); }
  { cuuint64_t d[3] = {64, 640, 24}, s[2] = {3072, 128}; cuuint32_t b[3] = {64, 160, 1};
    make_map(enc, &tg, P.wg, 3, d, s, b, CU_TENSOR_MAP_SWIZZLE_128B); make_map(enc, &tu, P.wu, 3, d, s, b, CU_TENSOR_MAP_SWIZZLE_128B); }
  { cuuint64_t d[3] = {32, 1536, 20}, s[2] = {1280, 64}; cuuint32_t b[3] = {32, 64, 5};
    make_map(enc, &td, P.wd, 3, d, s, b, CU_TENSOR_MAP_SWIZZLE_64B); }
  { cuuint64_t d[2] = {5136, 128}, s[1] = {10272}; cuuint32_t b[2] = {88, 128};
    make_map(enc, &twr, P.wr, 2, d, s, b, CU_TENSOR_MAP_SWIZZLE_NONE); make_map(enc, &twi, P.wi, 2, d, s, b, CU_TENSOR_MAP_SWIZZLE_NONE);
    cuuint32_t bz[2] = {8, 128};
    make_map(enc, &tzr, P.wr, 2, d, s, bz, CU_TENSOR_MAP_SWIZZLE_NONE); make_map(enc, &tzi, P.wi, 2, d, s, bz, CU_TENSOR_MAP_SWIZZLE_NONE); }
  cudaFuncSetAttribute(fused_kernel, cudaFuncAttributeMaxDynamicSharedMemorySize, SMEM_BYTES);
  fused_kernel<<<NCTA, NTHR, SMEM_BYTES, cudaStreamPerThread>>>(P, tg, tu, td, twr, twi, tma, tmb, tt8, tt2, tzr, tzi, tmo);
}
```
